```python
import torch

def _softmax(x, axis=-1):
    return torch.softmax(x, dim=axis)
def _gelu(x):
    return torch.nn.functional.gelu(x, approximate="tanh")
def _silu(x):
    return torch.nn.functional.silu(x)
def _sigmoid(x):
    return torch.sigmoid(x)
def _layernorm(x, axis=-1, eps=1e-5):
    m = x.mean(dim=axis, keepdim=True)
    v = x.var(dim=axis, keepdim=True, unbiased=False)
    return (x - m) / torch.sqrt(v + eps)
def _scatter_add(tgt, idx, src, axis=0):
    return tgt.clone().index_add_(axis, idx, src)
def _segment_sum(src, seg, n):
    out = torch.zeros((n,) + src.shape[1:], dtype=src.dtype)
    return out.index_add_(0, seg, src)
def _pad(x, pw):
    flat = tuple(v for pair in reversed(pw) for v in pair)
    return torch.nn.functional.pad(x, flat)

kernel_name = 'gather_scatter__molecular_angular_gemnet__graph'

def setup_inputs():

    _w = (lambda a: (lambda t: t.to(torch.bfloat16) if t.is_floating_point() else t)(torch.as_tensor(a)))
    N, deg, De, L = 10000, 64, 4, 1
    E = N * deg
    T = E * deg
    NR = 8
    dist = torch.rand(E).to(float)
    angle = (torch.rand(T) * torch.pi).to(float)
    centers = torch.linspace(0.0, 1.0, NR).to(float)
    ang_freq = torch.arange(1, L + 1).to(float)
    return {
        "m": _w((lambda *s: torch.randn(*s, dtype=torch.bfloat16) * 0.05)(E, De)),
        "idx_in": _w((lambda lo, hi, *s: torch.randint(lo, hi, s))(0, E, T).to(torch.int64)),
        "idx_out": _w((lambda lo, hi, *s: torch.randint(lo, hi, s))(0, E, T).to(torch.int64)),
        "dist": _w(dist),
        "angle": _w(angle),
        "centers": _w(centers),
        "ang_freq": _w(ang_freq),
        "w_rbf": _w((lambda *s: torch.randn(*s, dtype=torch.bfloat16) * 0.2)(NR, De)),
        "w_sbf": _w((lambda *s: torch.randn(*s, dtype=torch.bfloat16) * 0.2)(NR * L, De)),
        "w_down": _w((lambda *s: torch.randn(*s, dtype=torch.bfloat16) * 0.2)(De, De)),
        "w_up": _w((lambda *s: torch.randn(*s, dtype=torch.bfloat16) * 0.2)(De, De)),
    }

def reference(m, idx_in, idx_out, dist, angle, centers, ang_freq, w_rbf, w_sbf, w_down, w_up):
    E, De = m.shape[0], m.shape[1]
    NR = centers.shape[0]
    L = ang_freq.shape[0]
    rbf = torch.exp(-10.0 * (dist[:, None] - centers[None, :]) ** 2)
    cbf = torch.cos(ang_freq[None, :] * angle[:, None])
    rbf_t = rbf[idx_out]
    sbf = torch.reshape(rbf_t[:, :, None] * cbf[:, None, :], (-1, NR * L))
    x = (m[idx_in] @ w_down) * (sbf @ w_sbf)
    agg = _segment_sum(x, idx_out, E)
    return m + (agg @ w_up) * (rbf @ w_rbf)
```

```cpp
#include <cuda_runtime.h>
#include <cuda_bf16.h>
#include <stdint.h>

#define MAX_E (1 << 20)
__device__ float4 g_acc[MAX_E];

__device__ __forceinline__ float bf_lo(uint32_t w) { return __uint_as_float(w << 16); }
__device__ __forceinline__ float bf_hi(uint32_t w) { return __uint_as_float(w & 0xffff0000u); }
__device__ __forceinline__ float rbf16(float x) { return __bfloat162float(__float2bfloat16_rn(x)); }

__global__ void k_zero(int E) {
    for (int e = blockIdx.x * blockDim.x + threadIdx.x; e < E; e += gridDim.x * blockDim.x)
        g_acc[e] = make_float4(0.f, 0.f, 0.f, 0.f);
}

__global__ void __launch_bounds__(256) k_scatter(const uint2* __restrict__ m, const int* __restrict__ idx_in,
                                                 const int* __restrict__ idx_out, const __nv_bfloat16* __restrict__ angle,
                                                 const __nv_bfloat16* __restrict__ freq, int T) {
    float f = __bfloat162float(freq[0]);
    for (int t = blockIdx.x * blockDim.x + threadIdx.x; t < T; t += gridDim.x * blockDim.x) {
        uint2 r = __ldg(m + idx_in[t]);
        float c = rbf16(cosf(rbf16(f * __bfloat162float(angle[t]))));
        asm volatile("red.global.add.v4.f32 [%0], {%1,%2,%3,%4};" ::"l"(g_acc + idx_out[t]), "f"(bf_lo(r.x) * c),
                     "f"(bf_hi(r.x) * c), "f"(bf_lo(r.y) * c), "f"(bf_hi(r.y) * c) : "memory");
    }
}

__global__ void __launch_bounds__(256) k_final(const uint2* __restrict__ m, const __nv_bfloat16* __restrict__ dist,
                                               const __nv_bfloat16* __restrict__ centers, const __nv_bfloat16* __restrict__ w_rbf,
                                               const __nv_bfloat16* __restrict__ w_sbf, const __nv_bfloat16* __restrict__ w_down,
                                               const __nv_bfloat16* __restrict__ w_up, uint2* __restrict__ out, int E) {
    __shared__ float s_c[8], s_wr[32], s_ws[32], s_wd[16], s_wu[16];
    if (threadIdx.x < 8) s_c[threadIdx.x] = __bfloat162float(centers[threadIdx.x]);
    if (threadIdx.x < 32) { s_wr[threadIdx.x] = __bfloat162float(w_rbf[threadIdx.x]); s_ws[threadIdx.x] = __bfloat162float(w_sbf[threadIdx.x]); }
    if (threadIdx.x < 16) { s_wd[threadIdx.x] = __bfloat162float(w_down[threadIdx.x]); s_wu[threadIdx.x] = __bfloat162float(w_up[threadIdx.x]); }
    __syncthreads();
    for (int e = blockIdx.x * blockDim.x + threadIdx.x; e < E; e += gridDim.x * blockDim.x) {
        float d = __bfloat162float(dist[e]);
        float s[4] = {0, 0, 0, 0}, g[4] = {0, 0, 0, 0};
#pragma unroll
        for (int r = 0; r < 8; r++) {
            float x = rbf16(d - s_c[r]);
            float b = rbf16(expf(rbf16(-10.0f * rbf16(x * x))));
#pragma unroll
            for (int j = 0; j < 4; j++) { s[j] += b * s_ws[r * 4 + j]; g[j] += b * s_wr[r * 4 + j]; }
        }
        float4 a4 = g_acc[e];
        float a[4] = {a4.x, a4.y, a4.z, a4.w}, agg[4], o[4];
#pragma unroll
        for (int j = 0; j < 4; j++)
            agg[j] = s[j] * (a[0] * s_wd[j] + a[1] * s_wd[4 + j] + a[2] * s_wd[8 + j] + a[3] * s_wd[12 + j]);
        uint2 r = m[e];
        float mm[4] = {bf_lo(r.x), bf_hi(r.x), bf_lo(r.y), bf_hi(r.y)};
#pragma unroll
        for (int j = 0; j < 4; j++) {
            float u = agg[0] * s_wu[j] + agg[1] * s_wu[4 + j] + agg[2] * s_wu[8 + j] + agg[3] * s_wu[12 + j];
            o[j] = mm[j] + u * g[j];
        }
        __nv_bfloat162 p0 = __floats2bfloat162_rn(o[0], o[1]), p1 = __floats2bfloat162_rn(o[2], o[3]);
        out[e] = make_uint2(*(uint32_t*)&p0, *(uint32_t*)&p1);
    }
}

extern "C" void kernel_launch(void* const* d_in, const int* in_sizes, int n_in, void* d_out, int out_size) {
    const uint2* m = (const uint2*)d_in[0];
    const int* idx_in = (const int*)d_in[1];
    const int* idx_out = (const int*)d_in[2];
    const __nv_bfloat16* dist = (const __nv_bfloat16*)d_in[3];
    const __nv_bfloat16* angle = (const __nv_bfloat16*)d_in[4];
    const __nv_bfloat16* centers = (const __nv_bfloat16*)d_in[5];
    const __nv_bfloat16* freq = (const __nv_bfloat16*)d_in[6];
    const __nv_bfloat16* w_rbf = (const __nv_bfloat16*)d_in[7];
    const __nv_bfloat16* w_sbf = (const __nv_bfloat16*)d_in[8];
    const __nv_bfloat16* w_down = (const __nv_bfloat16*)d_in[9];
    const __nv_bfloat16* w_up = (const __nv_bfloat16*)d_in[10];
    int E = in_sizes[3], T = in_sizes[1];
    k_zero<<<132 * 4, 256>>>(E);
    k_scatter<<<132 * 8, 256>>>(m, idx_in, idx_out, angle, freq, T);
    k_final<<<132 * 8, 256>>>(m, dist, centers, w_rbf, w_sbf, w_down, w_up, (uint2*)d_out, E);
}
```

```cpp
#include <cuda_runtime.h>
#include <cuda_bf16.h>
#include <stdint.h>

namespace {

constexpr int NI = 24;
constexpr int UN = 6;
constexpr int NG = NI / UN;
constexpr int GR = 2 * NG;
constexpr int NCP = 18;
constexpr int NO = 2 * NCP;
constexpr int KS = 32;
constexpr int NB = UN * NCP;
constexpr int NBUF = 10;
constexpr int NP = 48, NM = 48, NC = 36, NCTA = NP + NM + NC;
#define CPS_ 23
constexpr int CPS = CPS_;
constexpr int NF = 4;
#define RS_ 4
constexpr int RS = RS_;
constexpr int QN = 80, QTRIG = 40;
#define MW_ 18
constexpr int MW = MW_;
constexpr int THREADS = 896, NW = THREADS / 32;
#define DEV_FREE 0
#define PUBSLEEP_ 0
#define SLEEP_ 200

constexpr int SLOT_BYTES = 16 * 8192;
constexpr int RING_BYTES = NP * RS * SLOT_BYTES;
constexpr int NPAGES = RING_BYTES >> 21;
constexpr int MAX_E = 1 << 20;
constexpr int SMEM_BYTES = 232448;

constexpr int SB = 1024;

constexpr int P_CNT = 0;
constexpr int P_BAR = P_CNT + NBUF * NB * 4;
constexpr int P_B = (P_BAR + 2 * NBUF * 8 + 127) / 128 * 128;
constexpr int P_Q = P_B + NBUF * NB * KS * 2;
constexpr int P_A = SMEM_BYTES - 256 - NBUF * NB * KS * 4;
static_assert(P_Q + CPS * QN * 8 + 512 <= P_A && P_A % 128 == 0, "P smem");
constexpr int S_MISC = SMEM_BYTES - 256;
constexpr int S_AUX = S_MISC - 2048;

constexpr unsigned FAST_E = 640000;
constexpr unsigned magic_of(unsigned long long d) { return (unsigned)(((1ull << 32) + d - 1) / d); }
constexpr bool magic_ok(unsigned long long d) { return (magic_of(d) * d - (1ull << 32)) * FAST_E < (1ull << 32); }
constexpr unsigned pick_rows(unsigned lo, unsigned mul) {
    unsigned d = (lo + 3) & ~3u;
    while (!(magic_ok(d) && magic_ok((unsigned long long)d * mul))) d += 4;
    return d;
}
constexpr unsigned ROWS_I = pick_rows((FAST_E + NI - 1) / NI, UN), ROWS_O = pick_rows((FAST_E + NO - 1) / NO, 1);
constexpr unsigned MAG_I = magic_of(ROWS_I), MAG_G = magic_of(ROWS_I * UN), MAG_O = magic_of(ROWS_O), HALF_O = ROWS_O * NCP;
static_assert(ROWS_I * 8 <= S_AUX && ROWS_O * 12 <= S_AUX, "tables");

struct __align__(128) Ctl {
    unsigned ticket[5];
    unsigned pagebits;
    unsigned stat_cnt[2];
    unsigned bad;
    unsigned fin;
    unsigned bar[3];
    unsigned exited;
    unsigned pad[18];
    float stat[2][NI][8];
};

struct Prm {
    const uint2* m; const int* idx_in; const int* idx_out; const __nv_bfloat16* dist; const __nv_bfloat16* angle;
    const __nv_bfloat16* centers; const __nv_bfloat16* freq; const __nv_bfloat16* w_rbf; const __nv_bfloat16* w_sbf;
    const __nv_bfloat16* w_down; const __nv_bfloat16* w_up; uint2* out;
    cudaTextureObject_t t_in, t_out, t_ang;
    int E, T;
    unsigned char* ring;
    int NS;
    int force_bad;
};

__device__ __align__(128) unsigned char g_ring[RING_BYTES + (2 << 20)];
__device__ Ctl g_ctl;
__device__ float4 g_acc[MAX_E];
#define PROF_DECL
#define PROF(k)
#define PROF_END

extern __shared__ __align__(128) unsigned char smem[];

__device__ __forceinline__ float bf_lo(uint32_t w) { return __uint_as_float(w << 16); }
__device__ __forceinline__ float bf_hi(uint32_t w) { return __uint_as_float(w & 0xffff0000u); }
__device__ __forceinline__ float rbf16(float x) { return __bfloat162float(__float2bfloat16_rn(x)); }
__device__ __forceinline__ uint32_t pack_bf16(float hi, float lo) {
    uint32_t r; asm("cvt.rn.bf16x2.f32 %0, %1, %2;" : "=r"(r) : "f"(hi), "f"(lo)); return r;
}
__device__ __forceinline__ uint32_t prmt(uint32_t a, uint32_t b, uint32_t c) {
    uint32_t r; asm("prmt.b32 %0, %1, %2, %3;" : "=r"(r) : "r"(a), "r"(b), "r"(c)); return r;
}
__device__ __forceinline__ uint32_t ld_relaxed(const void* p) {
    uint32_t v; asm volatile("ld.relaxed.gpu.global.u32 %0, [%1];" : "=r"(v) : "l"(p) : "memory"); return v;
}
__device__ __forceinline__ uint2 ld_relaxed2(const void* p) {
    uint2 v; asm volatile("ld.relaxed.gpu.global.v2.u32 {%0,%1}, [%2];" : "=r"(v.x), "=r"(v.y) : "l"(p) : "memory"); return v;
}
__device__ __forceinline__ uint4 ld_relaxed4(const void* p) {
    uint4 v; asm volatile("ld.relaxed.gpu.global.v4.u32 {%0,%1,%2,%3}, [%4];" : "=r"(v.x), "=r"(v.y), "=r"(v.z), "=r"(v.w) : "l"(p) : "memory"); return v;
}
__device__ __forceinline__ void st_relaxed(void* p, uint32_t v) { asm volatile("st.relaxed.gpu.global.u32 [%0], %1;" ::"l"(p), "r"(v) : "memory"); }
__device__ __forceinline__ void st_relaxed16(void* p, uint32_t v) { asm volatile("st.relaxed.gpu.global.u16 [%0], %1;" ::"l"(p), "h"((uint16_t)v) : "memory"); }
__device__ __forceinline__ void red_add(void* p, uint32_t v) { asm volatile("red.relaxed.gpu.global.add.u32 [%0], %1;" ::"l"(p), "r"(v) : "memory"); }
__device__ __forceinline__ void fence_gpu() { asm volatile("fence.acq_rel.gpu;" ::: "memory"); }
__device__ __forceinline__ void fence_release() { asm volatile("fence.release.gpu;" ::: "memory"); }
__device__ __forceinline__ void mbar_init(uint32_t a, uint32_t n) { asm volatile("mbarrier.init.shared.b64 [%0], %1;" ::"r"(a), "r"(n) : "memory"); }
__device__ __forceinline__ void mbar_arrive(uint32_t a) { asm volatile("mbarrier.arrive.shared.b64 _, [%0];" ::"r"(a) : "memory"); }
__device__ __forceinline__ bool mbar_try(uint32_t a, uint32_t ph) {
    uint32_t ok;
    asm volatile("{.reg .pred p; mbarrier.try_wait.parity.shared.b64 p, [%1], %2, %3; selp.u32 %0, 1, 0, p;}" : "=r"(ok) : "r"(a), "r"(ph), "r"(2000) : "memory");
    return ok;
}
constexpr int SPIN_MAX = 1 << 22;
__device__ __forceinline__ void mbar_wait(uint32_t a, uint32_t ph) {
    int it = 0;
    while (!mbar_try(a, ph)) { if (++it > SPIN_MAX) __trap(); }
}
__device__ __forceinline__ void backoff(int& it) { __nanosleep(SLEEP_); if (++it > SPIN_MAX) __trap(); }
__device__ __forceinline__ void wait_ge(const void* p, uint32_t v) {
    int it = 0;
    while (ld_relaxed(p) < v) backoff(it);
}

__device__ __forceinline__ bool elect_one() {
    uint32_t r; asm volatile("{.reg .pred p; elect.sync _|p, 0xffffffff; selp.u32 %0, 1, 0, p;}" : "=r"(r)); return r;
}
__device__ __forceinline__ void lds_lt(uint32_t& v, uint32_t ad, int a, int b) {
    asm volatile("{.reg .pred p; setp.lt.s32 p, %2, %3; @p ld.shared.u32 %0, [%1];}" : "+r"(v) : "r"(ad), "r"(a), "r"(b));
}
__device__ __forceinline__ void ldg4_lt(uint4& v, const void* ad, int a, int b) {
    asm volatile("{.reg .pred p; setp.lt.s32 p, %5, %6; @p ld.relaxed.gpu.global.v4.u32 {%0,%1,%2,%3}, [%4];}"
                 : "=r"(v.x), "=r"(v.y), "=r"(v.z), "=r"(v.w) : "l"(ad), "r"(a), "r"(b) : "memory");
}
__device__ __forceinline__ void ldg2_lt(uint2& v, const void* ad, int a, int b) {
    asm volatile("{.reg .pred p; setp.lt.s32 p, %3, %4; @p ld.relaxed.gpu.global.v2.u32 {%0,%1}, [%2];}"
                 : "=r"(v.x), "=r"(v.y) : "l"(ad), "r"(a), "r"(b) : "memory");
}
__device__ __forceinline__ void stg4_lt(void* ad, const uint32_t v[4], int a, int b) {
    asm volatile("{.reg .pred p; setp.lt.s32 p, %5, %6; @p st.global.v4.u32 [%0], {%1,%2,%3,%4};}"
                 ::"l"(ad), "r"(v[0]), "r"(v[1]), "r"(v[2]), "r"(v[3]), "r"(a), "r"(b) : "memory");
}

__device__ __forceinline__ constexpr uint32_t gran(uint32_t k) { return k * 8192u + (((k ^ (k >> 3)) & 1u) << 12); }
__device__ __forceinline__ uint32_t slot_base(uint32_t s, uint32_t pagebits, uint32_t side) {
    return s * (uint32_t)SLOT_BYTES + (((s ^ (s >> 2) ^ (pagebits >> (s >> 4)) ^ side) & 1u) << 12);
}
constexpr uint32_t OFF_PF = gran(14), OFF_MF = gran(14) + 256, OFF_REL = gran(14) + 640;

__device__ __forceinline__ uint32_t probe(unsigned char* p) {
    volatile uint32_t* sink = (volatile uint32_t*)(smem + S_MISC + 128);
    uint32_t best = 0xffffffffu;
#pragma unroll 1
    for (int r = 0; r < 3; r++) {
        uint32_t t0, t1, v;
        asm volatile("mov.u32 %0, %%clock;" : "=r"(t0)::"memory");
        asm volatile("atom.relaxed.gpu.global.add.u32 %0, [%1], 1;" : "=r"(v) : "l"(p) : "memory");
        *sink = v;
        asm volatile("mov.u32 %0, %%clock;" : "=r"(t1)::"memory");
        best = min(best, t1 - t0);
    }
    return best;
}
__device__ __forceinline__ uint32_t probe_pair(unsigned char* p) {
    asm volatile("st.global.v4.u32 [%0], {%1,%1,%1,%1};" ::"l"(p), "r"(0) : "memory");
    asm volatile("st.global.v4.u32 [%0], {%1,%1,%1,%1};" ::"l"(p + 16), "r"(0) : "memory");
    asm volatile("st.global.v4.u32 [%0], {%1,%1,%1,%1};" ::"l"(p + 4096), "r"(0) : "memory");
    asm volatile("st.global.v4.u32 [%0], {%1,%1,%1,%1};" ::"l"(p + 4112), "r"(0) : "memory");
    uint32_t a = probe(p), b = probe(p + 4096);
    return a > b;
}

struct Wts { float c[8], wr[32], ws[32], wd[16], wu[16]; };
__device__ __forceinline__ void load_wts(const Prm& p, Wts* w) {
    int t = threadIdx.x;
    if (t < 8) w->c[t] = __bfloat162float(p.centers[t]);
    if (t < 32) { w->wr[t] = __bfloat162float(p.w_rbf[t]); w->ws[t] = __bfloat162float(p.w_sbf[t]); }
    if (t < 16) { w->wd[t] = __bfloat162float(p.w_down[t]); w->wu[t] = __bfloat162float(p.w_up[t]); }
}
__device__ __forceinline__ void finish_row(const Prm& p, const Wts* w, int e, const float a[4]) {
    float d = __bfloat162float(p.dist[e]);
    float s[4] = {0, 0, 0, 0}, g[4] = {0, 0, 0, 0};
#pragma unroll
    for (int r = 0; r < 8; r++) {
        float x = rbf16(d - w->c[r]);
        float b = rbf16(__expf(rbf16(-10.0f * rbf16(x * x))));
#pragma unroll
        for (int j = 0; j < 4; j++) { s[j] += b * w->ws[r * 4 + j]; g[j] += b * w->wr[r * 4 + j]; }
    }
    float agg[4], o[4];
#pragma unroll
    for (int j = 0; j < 4; j++)
        agg[j] = s[j] * (a[0] * w->wd[j] + a[1] * w->wd[4 + j] + a[2] * w->wd[8 + j] + a[3] * w->wd[12 + j]);
    uint2 r = p.m[e];
    float mm[4] = {bf_lo(r.x), bf_hi(r.x), bf_lo(r.y), bf_hi(r.y)};
#pragma unroll
    for (int j = 0; j < 4; j++) {
        float u = agg[0] * w->wu[j] + agg[1] * w->wu[4 + j] + agg[2] * w->wu[8 + j] + agg[3] * w->wu[12 + j];
        o[j] = mm[j] + u * g[j];
    }
    p.out[e] = make_uint2(pack_bf16(o[1], o[0]), pack_bf16(o[3], o[2]));
}

__device__ __forceinline__ void get_scales(const Prm& p, int side, float sc[4], bool& bad) {
    const int lane = threadIdx.x & 31;
    wait_ge(&g_ctl.stat_cnt[side], NI);
    fence_gpu();
    uint4 a = make_uint4(0, 0, 0, 0), b = a;
    if (lane < NI) { a = ld_relaxed4(&g_ctl.stat[side][lane][0]); b = ld_relaxed4(&g_ctl.stat[side][lane][4]); }
    uint32_t mxb[4] = {a.x, a.y, a.z, a.w};
    float ss[4] = {__uint_as_float(b.x), __uint_as_float(b.y), __uint_as_float(b.z), __uint_as_float(b.w)};
    bad = false;
    const float kdeg = fminf(3.5f * sqrtf(fmaxf(0.5f * (float)p.T / (float)p.E, 1.0f)), 128.f);
#pragma unroll
    for (int ch = 0; ch < 4; ch++) {
        float mx = __uint_as_float(__reduce_max_sync(0xffffffffu, mxb[ch]));
#pragma unroll
        for (int o = 16; o; o >>= 1) ss[ch] += __shfl_xor_sync(0xffffffffu, ss[ch], o);
        float rms = sqrtf(ss[ch] / (float)p.E);
        float range = fmaxf(mx, kdeg * rms);
        if (!(mx <= 1e15f) || !(range <= 128.f * rms) || (mx > 0.f && mx < 1e-15f)) bad = true;
        sc[ch] = range > 0.f ? 32767.f / range : 0.f;
    }
}

constexpr int PER = 40;
struct __align__(16) PTab { uint32_t map[PER][4]; uint32_t sync[PER][2]; };
constexpr PTab make_ptab() {
    PTab t = {};
    for (int s = 0; s < PER; s++) {
        for (int d = 0; d < GR; d++) {
            int gi = (s + d) % GR, buf = (s + d) % NBUF, X = gi & 1, g = gi >> 1;
            t.map[s][X] |= (uint32_t)(UN * (buf + (NG - 1) - g) + 1 - X) << (8 * g);
            t.map[s][2 + X] |= (uint32_t)(NCP * (buf + 1 - X) + (NG - 1) - g) << (8 * g);
        }
        int mnew = s + GR - 1;
        t.sync[s][0] = (uint32_t)(SB + P_BAR + (NBUF + mnew % NBUF) * 8) | (uint32_t)(((mnew / NBUF) & 1) ^ 1) << 31;
        t.sync[s][1] = (uint32_t)(SB + P_BAR + (s % NBUF) * 8) | (uint32_t)((s + 1) % PER) << 16;
    }
    return t;
}
__constant__ PTab c_ptab = make_ptab();
constexpr int BIAS_A = NCP * (UN * (NG - 1) + 1);
constexpr int BIAS_B = UN * (NCP + NG - 1);

struct PCtx { uint32_t a0, a1, b0, b1; };
struct PElem { uint32_t ba, bb, aw, ol, r4; };

__device__ __forceinline__ void p_bin(const PCtx& c, PElem& e, uint32_t i, uint32_t o, uint32_t cw, uint32_t csel) {
    uint32_t ib = __umulhi(i, MAG_I), ob = __umulhi(o, MAG_O), sel = __umulhi(i, MAG_G);
    asm("{.reg .pred p; setp.ge.u32 p, %1, %2; @p add.u32 %0, %0, 4;}" : "+r"(sel) : "r"(o), "n"(HALF_O));
    e.ba = __dp4a(prmt(c.a0, c.a1, sel), (uint32_t)NCP, ib * NCP + ob);
    e.bb = __dp4a(prmt(c.b0, c.b1, sel), (uint32_t)UN, ob * UN + ib);
    e.aw = prmt(i - ib * ROWS_I, cw, csel);
    e.ol = o - ob * ROWS_O;
}
__device__ __forceinline__ void p_rank(PElem& e) {
    asm volatile("atom.shared.add.u32 %0, [%1+%2], 4;" : "=r"(e.r4) : "r"(e.ba * 4), "n"(SB + P_CNT - BIAS_A * 4) : "memory");
}
__device__ __forceinline__ void p_store(const PElem& e) {
    asm volatile("{.reg .pred p; setp.lt.u32 p, %4, %5; @p st.shared.u32 [%0+%6], %1; @p st.shared.u16 [%2+%7], %3;}"
                 ::"r"(e.ba * (KS * 4) + e.r4), "r"(e.aw), "r"((e.bb * (KS * 4) + e.r4) >> 1), "h"((uint16_t)e.ol), "r"(e.r4), "n"(KS * 4),
                   "n"(SB + P_A - BIAS_A * (KS * 4)), "n"(SB + P_B - BIAS_B * (KS * 2)) : "memory");
}
__device__ __noinline__ uint32_t cos2_slow(uint32_t x) {
    float a = cosf(bf_lo(x)), b = cosf(bf_hi(x));
    if (!(fabsf(a + b) <= 2.f)) { st_relaxed(&g_ctl.bad, 1); a = b = 0.f; }
    return pack_bf16(b, a);
}

struct PIn { uint4 i, o; uint2 a; };
__device__ __forceinline__ void p_fetch(const Prm& p, PIn& x, int v) {
    asm volatile("{.reg .b32 d0, d1; tex.1d.v4.u32.s32 {%0,%1,d0,d1}, [%2, {%3}];}" : "=r"(x.a.x), "=r"(x.a.y) : "l"(p.t_ang), "r"(v));
    asm volatile("tex.1d.v4.u32.s32 {%0,%1,%2,%3}, [%4, {%5}];" : "=r"(x.i.x), "=r"(x.i.y), "=r"(x.i.z), "=r"(x.i.w) : "l"(p.t_in), "r"(v));
    asm volatile("tex.1d.v4.u32.s32 {%0,%1,%2,%3}, [%4, {%5}];" : "=r"(x.o.x), "=r"(x.o.y), "=r"(x.o.z), "=r"(x.o.w) : "l"(p.t_out), "r"(v));
}

struct PFill {
    PCtx c;
    uint32_t qb, qt, lt, f2, nxt;
    __device__ __forceinline__ void begin() {
        const uint32_t idx = nxt >> 16;
        const uint2 s = ((const uint2*)c_ptab.sync)[idx];
        const uint2 m0 = ((const uint2*)c_ptab.map)[2 * idx], m1 = ((const uint2*)c_ptab.map)[2 * idx + 1];
        c.a0 = m0.x; c.a1 = m0.y; c.b0 = m1.x; c.b1 = m1.y;
        nxt = s.y;
        mbar_wait(s.x & 0xffff, s.x >> 31);
    }
    __device__ __forceinline__ void end() {
        __syncwarp();
        asm volatile("{.reg .pred p; setp.eq.u32 p, %1, 0; @p mbarrier.arrive.shared.b64 _, [%0];}" ::"r"(nxt & 0xffff), "r"(lt) : "memory");
    }
    __device__ __forceinline__ void push(bool f, uint32_t x, uint32_t y) {
        uint32_t mask = __ballot_sync(0xffffffffu, f);
        asm volatile("{.reg .pred p; setp.ne.u32 p, %3, 0; @p st.shared.v2.u32 [%0], {%1,%2};}" ::"r"(qt + __popc(mask & lt) * 8), "r"(x), "r"(y), "r"((uint32_t)f) : "memory");
        qt += __popc(mask) * 8;
    }
    __device__ __forceinline__ void push_checked(bool f, uint32_t i, uint32_t o, uint32_t aw) {
        if (qt - qb + __popc(__ballot_sync(0xffffffffu, f)) * 8 > QN * 8) st_relaxed(&g_ctl.bad, 1);
        else push(f, prmt(i, aw, 0x6210), prmt(o, aw, 0x7210));
    }
    __device__ __forceinline__ void chunk(const PIn& x) {
        uint32_t x0, x1, c0, c1;
        asm("mul.rn.bf16x2 %0, %1, %2;" : "=r"(x0) : "r"(x.a.x), "r"(f2));
        asm("mul.rn.bf16x2 %0, %1, %2;" : "=r"(x1) : "r"(x.a.y), "r"(f2));
        c0 = pack_bf16(__cosf(bf_hi(x0)), __cosf(bf_lo(x0)));
        c1 = pack_bf16(__cosf(bf_hi(x1)), __cosf(bf_lo(x1)));
        if (__any_sync(0xffffffffu, (((x0 & 0x7fff7fffu) + 0x3e003e00u) | ((x1 & 0x7fff7fffu) + 0x3e003e00u)) & 0x80008000u)) { c0 = cos2_slow(x0); c1 = cos2_slow(x1); }
        PElem e0, e1, e2, e3;
        p_bin(c, e0, x.i.x, x.o.x, c0, 0x5410); p_rank(e0);
        p_bin(c, e1, x.i.y, x.o.y, c0, 0x7610); p_rank(e1);
        p_bin(c, e2, x.i.z, x.o.z, c1, 0x5410); p_rank(e2);
        p_bin(c, e3, x.i.w, x.o.w, c1, 0x7610); p_rank(e3);
        p_store(e0); p_store(e1); p_store(e2); p_store(e3);
        const bool f0 = e0.r4 >= KS * 4, f1 = e1.r4 >= KS * 4, f2_ = e2.r4 >= KS * 4, f3 = e3.r4 >= KS * 4;
        const uint32_t r01 = e0.r4 | e1.r4, r23 = e2.r4 | e3.r4;
        const bool f01 = r01 >= KS * 4;
        uint32_t si = f01 ? (f0 ? x.i.x : x.i.y) : (f2_ ? x.i.z : x.i.w);
        uint32_t so = f01 ? (f0 ? x.o.x : x.o.y) : (f2_ ? x.o.z : x.o.w);
        uint32_t sc = f01 ? (f0 ? e0.aw : e1.aw) : (f2_ ? e2.aw : e3.aw);
        push((r01 | r23) >= KS * 4, prmt(si, sc, 0x6210), prmt(so, sc, 0x7210));
        uint32_t s2 = max(max(min(e0.r4, e1.r4), min(e2.r4, e3.r4)), min(r01, r23));
        if (__any_sync(0xffffffffu, s2 >= KS * 4)) {
            push_checked(f1 && f0, x.i.y, x.o.y, e1.aw);
            push_checked(f2_ && (f0 || f1), x.i.z, x.o.z, e2.aw);
            push_checked(f3 && (f0 || f1 || f2_), x.i.w, x.o.w, e3.aw);
        }
    }
    __device__ __forceinline__ void retry(uint32_t take) {
        const uint32_t lane8 = (threadIdx.x & 31) * 8;
        uint2 e, r0, r1;
        __syncwarp();
        asm volatile("ld.shared.v2.u32 {%0,%1}, [%2];" : "=r"(e.x), "=r"(e.y) : "r"(qb + lane8) : "memory");
        asm volatile("ld.shared.v2.u32 {%0,%1}, [%2];" : "=r"(r0.x), "=r"(r0.y) : "r"(qb + lane8 + take * 8) : "memory");
        qt -= take * 8;
        const bool more = qt - qb > 256;
        if (more) asm volatile("ld.shared.v2.u32 {%0,%1}, [%2];" : "=r"(r1.x), "=r"(r1.y) : "r"(qb + lane8 + take * 8 + 256) : "memory");
        __syncwarp();
        if (qb + lane8 < qt) asm volatile("st.shared.v2.u32 [%0], {%1,%2};" ::"r"(qb + lane8), "r"(r0.x), "r"(r0.y) : "memory");
        if (more && qb + lane8 + 256 < qt) asm volatile("st.shared.v2.u32 [%0], {%1,%2};" ::"r"(qb + lane8 + 256), "r"(r1.x), "r"(r1.y) : "memory");
        PElem el;
        el.r4 = 0;
        if (lane8 < take * 8) {
            p_bin(c, el, e.x & 0xffffffu, e.y & 0xffffffu, prmt(e.x, e.y, 0x0073), 0x5410);
            p_rank(el);
            p_store(el);
        }
        push(el.r4 >= KS * 4, e.x, e.y);
    }
    __device__ __forceinline__ void drain() {
        if (qt - qb >= QTRIG * 8) {
            retry(32);
            if (qt - qb > (QN - 32) * 8) { st_relaxed(&g_ctl.bad, 1); qt = qb; }
        }
    }
};

__device__ __forceinline__ void p_filler(const Prm& p, int q, int w) {
    PFill F;
    const int lane = threadIdx.x & 31;
    F.lt = __shfl_sync(0xffffffffu, (1u << lane) - 1u, lane);
    F.qb = F.qt = SB + P_Q + w * (QN * 8); F.nxt = (q % GR) << 16;
    F.f2 = __shfl_sync(0xffffffffu, __bfloat16_as_ushort(p.freq[0]) * 0x10001u, 0);
    constexpr int vstep = NP * CPS * 32;
    const int NS = p.NS, vend = (p.T >> 7) * 32;
    int v = (q * CPS + w) * 32 + lane;
    PIn x0, x1, x2;
    p_fetch(p, x0, v); p_fetch(p, x1, v + vstep);
    PROF_DECL
    const int nch = __shfl_sync(0xffffffffu, (vend - v + vstep - 1) / vstep, 0);
    int n = 0;
#pragma unroll 1
    for (; n + 3 <= nch; n += 3) {
        PROF(1); F.begin(); PROF(0); p_fetch(p, x2, v + 2 * vstep); F.chunk(x0); F.drain(); F.end();
        p_fetch(p, x0, v + 3 * vstep); PROF(1); F.begin(); PROF(0); F.chunk(x1); F.drain(); F.end();
        p_fetch(p, x1, v + 4 * vstep); PROF(1); F.begin(); PROF(0); F.chunk(x2); F.drain(); F.end();
        v += 3 * vstep;
    }
    PROF_END;
#pragma unroll 1
    for (; n < nch; n++) {
        F.begin(); F.chunk(x0); F.drain(); F.end();
        x0 = x1;
    }
    if (q == 0 && w < 4) {
        int t = vend * 4 + w * 32 + lane;
        bool f = t < p.T;
        uint32_t i = 0, o = 0, x = 0;
        if (f) { i = p.idx_in[t]; o = p.idx_out[t]; asm("mul.rn.bf16x2 %0, %1, %2;" : "=r"(x) : "r"((uint32_t)__bfloat16_as_ushort(p.angle[t]) << 16), "r"(F.f2)); }
        F.push_checked(f, i, o, cos2_slow(x & 0xffff0000u));
    }
#pragma unroll 1
    for (; n <= NS + GR; n++) {
        F.begin();
        for (uint32_t nq = (F.qt - F.qb) >> 3; nq > 0;) { uint32_t take = min(nq, 32u); F.retry(take); nq -= take; }
        F.end();
    }
    if (F.qt != F.qb) st_relaxed(&g_ctl.bad, 1);
}

__device__ __forceinline__ void p_flusher(const Prm& p, unsigned char* ring, uint32_t pagebits, int q, int f) {
    const int lane = threadIdx.x & 31;
    const uint32_t sb = SB;
    const uint32_t bar = sb + P_BAR;
    const int NS = p.NS, NT = NS + 2 * GR;
    const uint32_t pfo = OFF_PF + (lane / 3) * 32 + (lane % 3) * 4;
    PROF_DECL
#pragma unroll 1
    for (int n = f; n < NT; n += NF) {
        uint32_t buf = (n + q % GR) % NBUF, ph = ((n + q % GR) / NBUF) & 1;
        uint32_t X = (n + q) & 1, h = n >> 1, lap = h / RS;
        uint32_t base = slot_base(q * RS + (h % RS), pagebits, X);
        if (lap > 0 && !DEV_FREE) wait_ge(ring + (base ^ OFF_REL), NCP * lap);
        PROF(0);
        if (n <= NS + GR) mbar_wait(bar + buf * 8, ph);
        else { int nl = NS + GR + q % GR; mbar_wait(bar + (nl % NBUF) * 8, (nl / NBUF) & 1); }
        PROF(1);
        uint2* cnt = (uint2*)(smem + P_CNT) + buf * (NB / 2) + lane * 3;
        bool any = true;
        if (n >= NS) any = __any_sync(0xffffffffu, lane < NB / 6 && (cnt[0].x | cnt[0].y | cnt[1].x | cnt[1].y | cnt[2].x | cnt[2].y));
        if (any && elect_one()) {
            asm volatile("fence.proxy.async.shared::cta;" ::: "memory");
#pragma unroll
            for (int k = 0; k < UN + 2; k++) {
                const uint32_t goff = k < UN ? gran(2 * k) : gran(12 + (k - UN));
                const uint32_t soff = k < UN ? P_A + k * (NCP * KS * 4) + buf * (NB * KS * 4) : P_B + (k - UN) * (NB * KS) + buf * (NB * KS * 2);
                asm volatile("cp.async.bulk.global.shared::cta.bulk_group [%0], [%1], %2;" ::"l"(ring + (base ^ goff)), "r"(sb + soff), "r"(k < UN ? NCP * KS * 4 : NB * KS) : "memory");
            }
            asm volatile("cp.async.bulk.commit_group;" ::: "memory");
        }
        __syncwarp();
        uint32_t w0 = 0, w1 = 0;
        if (lane < NB / 6) {
#pragma unroll
            for (int u = 0; u < 3; u++) {
                uint2 c = cnt[u]; cnt[u] = make_uint2(0, 0);
                w0 |= min(c.x >> 2, (uint32_t)KS) << (6 * u); w1 |= min(c.y >> 2, (uint32_t)KS) << (6 * u);
            }
        }
        PROF(3);
        asm volatile("cp.async.bulk.wait_group 0;" ::: "memory");
        __syncwarp();
        PROF(2);
        if (lane == 0) mbar_arrive(bar + (NBUF + buf) * 8);
        if (any) fence_release();
        PROF(4);
        if (lane < NB / 6) {
            st_relaxed(ring + (base ^ pfo), w0 | ((lap + 1) << 18));
            st_relaxed(ring + (base ^ pfo) + 16, w1 | ((lap + 1) << 18));
        }
    }
    PROF_END;
    for (int s = f; s < 2 * RS; s += NF) {
        uint32_t X = s & 1, r = s >> 1;
        int n0 = (X + q) & 1;
        int nh = (NT - n0 + 1) >> 1;
        int laps = (nh - (int)r + RS - 1) / RS;
        uint32_t base = slot_base(q * RS + r, pagebits, X);
        if (!DEV_FREE) wait_ge(ring + (base ^ OFF_REL), NCP * laps);
        __syncwarp();
        for (int k = lane; k < 48; k += 32) *(uint4*)(ring + (base ^ OFF_PF) + k * 16) = make_uint4(0, 0, 0, 0);
    }
}

__device__ __forceinline__ void m_role(const Prm& p, unsigned char* ring, int X, int ib) {
    const int tid = threadIdx.x, lane = tid & 31, w = __shfl_sync(0xffffffffu, tid >> 5, 0);
    {
        int r0 = ib * ROWS_I, nr = max(min((int)ROWS_I, p.E - r0), 0);
        const uint2* src = p.m + r0;
        uint32_t mx[4] = {0, 0, 0, 0}; float ss[4] = {0, 0, 0, 0};
#pragma unroll 4
        for (int r = tid; r < (int)ROWS_I; r += THREADS) {
            uint2 v = r < nr ? __ldg(src + r) : make_uint2(0, 0);
            ((uint2*)smem)[r] = v;
            float a = bf_lo(v.x), b = bf_hi(v.x), c = bf_lo(v.y), d = bf_hi(v.y);
            mx[0] = max(mx[0], __float_as_uint(a) & 0x7fffffffu); mx[1] = max(mx[1], __float_as_uint(b) & 0x7fffffffu);
            mx[2] = max(mx[2], __float_as_uint(c) & 0x7fffffffu); mx[3] = max(mx[3], __float_as_uint(d) & 0x7fffffffu);
            ss[0] += a * a; ss[1] += b * b; ss[2] += c * c; ss[3] += d * d;
        }
        float* red = (float*)(smem + S_AUX);
#pragma unroll
        for (int ch = 0; ch < 4; ch++) {
            mx[ch] = __reduce_max_sync(0xffffffffu, mx[ch]);
#pragma unroll
            for (int o = 16; o; o >>= 1) ss[ch] += __shfl_xor_sync(0xffffffffu, ss[ch], o);
            if (lane == 0) { red[w * 8 + ch] = __uint_as_float(mx[ch]); red[w * 8 + 4 + ch] = ss[ch]; }
        }
        __syncthreads();
        if (tid < 8) {
            uint32_t m2 = 0; float s2 = 0.f;
            for (int k = 0; k < NW; k++) { float x = red[k * 8 + tid]; m2 = max(m2, __float_as_uint(x)); s2 += x; }
            st_relaxed(&g_ctl.stat[X][ib][tid], tid < 4 ? m2 : __float_as_uint(s2));
            fence_gpu();
            __syncwarp(0xff);
            if (tid == 0) red_add(&g_ctl.stat_cnt[X], 1);
        }
    }
    float* scs = (float*)(smem + S_MISC);
    if (w == 0) {
        __syncwarp();
        float sc[4]; bool bad;
        get_scales(p, X, sc, bad);
        if (bad) { st_relaxed(&g_ctl.bad, 1); sc[0] = sc[1] = sc[2] = sc[3] = 0.f; }
        int it = 0; uint32_t pb;
        while (!((pb = ld_relaxed(&g_ctl.pagebits)) >> 31)) backoff(it);
        ((uint32_t*)(smem + S_AUX))[lane] = 0;
        if (lane == 0) { scs[0] = sc[0]; scs[1] = sc[1]; scs[2] = sc[2]; scs[3] = sc[3]; ((uint32_t*)scs)[4] = pb; }
    }
    __syncthreads();
    uint32_t* mbs = (uint32_t*)(smem + S_AUX);
    uint16_t* mbv = (uint16_t*)(smem + S_AUX + 128);
    if (w > MW) return;
    if (w == MW) {
        int left = (p.NS + 2 * GR) * (NP / GR), it = 0;
        while (left > 0) {
            uint32_t b;
            asm volatile("ld.acquire.cta.shared.u32 %0, [%1];" : "=r"(b) : "r"(SB + S_AUX + lane * 4) : "memory");
            uint32_t mask = __ballot_sync(0xffffffffu, b != 0);
            if (mask == 0) { __nanosleep(40); if (++it > SPIN_MAX * 4) __trap(); continue; }
            fence_gpu();
            left -= __popc(mask);
            for (uint32_t mm = mask; mm; mm &= mm - 1) {
                int src = __ffs(mm) - 1;
                uint32_t base = __shfl_sync(0xffffffffu, b, src) - 1;
                if (lane < NCP) st_relaxed16(ring + (base ^ (OFF_MF + lane * 16 + (ib % UN) * 2)), mbv[src * 32 + lane]);
            }
            __syncwarp();
            if (b != 0) asm volatile("st.release.cta.shared.u32 [%0], %1;" ::"r"(SB + S_AUX + lane * 4), "r"(0) : "memory");
            if (PUBSLEEP_ > 0) __nanosleep(PUBSLEEP_);
        }
        return;
    }
    const uint32_t pagebits = ((uint32_t*)scs)[4];
    const int par = lane & 1, half = lane >> 4, k4 = ((lane & 15) >> 1) * 4;
    const float s_lo = scs[2 * par], s_hi = scs[2 * par + 1];
    const float MAG_LO = 12582912.f, MAG_HI = 12582912.f - 19264.f;
    const uint32_t tab = SB + par * 4;
    const int il = ib % UN, gi = (ib / UN) * 2 + X;
    const uint32_t a_off = gran(2 * il) + half * 128 + k4 * 4;
    const uint32_t v_off0 = gran(2 * il) + lane * 16;
    const uint32_t v_off1 = gran(2 * il + 1) + lane * 16;
    const int NT = p.NS + 2 * GR;
    const int j = w % (NP / GR);
    PROF_DECL
#pragma unroll 1
    for (int n = w / (NP / GR); n < NT; n += MW / (NP / GR)) {
        uint32_t q = ((gi - n) & (GR - 1)) + GR * j, h = n >> 1, lap = h / RS;
        uint32_t base = slot_base(q * RS + (h % RS), pagebits, X);
        const uint32_t tag = (lap + 1) << 18;
        uint4 cw; int it = 0;
        while (true) {
            cw = ld_relaxed4(ring + (base ^ (OFF_PF + il * 32 + half * 16)));
            uint32_t d = ((cw.x ^ tag) | (cw.y ^ tag) | (cw.z ^ tag)) >> 18;
            if (__all_sync(0xffffffffu, d == 0)) break;
            if (DEV_FREE) { cw.x = (cw.x & 1) + (32 | 27 << 6 | 22 << 12); cw.y = (cw.y & 1) + (25 | 30 << 6 | 27 << 12); cw.z = (cw.z & 1) + (29 | 24 << 6 | 27 << 12); break; }
            backoff(it);
        }
        PROF(0);
        unsigned char* pa = ring + (base ^ a_off);
        unsigned char* pv0 = ring + (base ^ v_off0);
        unsigned char* pv1 = ring + (base ^ v_off1) - 9 * 256;
        uint4 a[9];
#pragma unroll
        for (int ps = 8; ps >= 3; ps--) ldg4_lt(a[ps], pa + ps * 256, k4, ((ps < 6 ? cw.y : cw.z) >> (6 * (ps % 3))) & 0x3f);
#pragma unroll
        for (int ps = 8; ps >= 0; ps--) {
            uint32_t cword = ps < 3 ? cw.x : ps < 6 ? cw.y : cw.z;
            const int rem = (int)((cword >> (6 * (ps % 3))) & 0x3f) - k4;
            uint32_t aw[4] = {a[ps].x, a[ps].y, a[ps].z, a[ps].w}, mv[4], vw[4];
#pragma unroll
            for (int e = 0; e < 4; e++) { if (DEV_FREE) aw[e] = (aw[e] + a_off * 0x9e3779b1u * (2 * (ps * 4 + e) + 1) >> 7) & 0x3fff3fffu; mv[e] = 0; lds_lt(mv[e], __dp2a_lo(aw[e], 8u, tab), e, rem); }
#pragma unroll
            for (int e = 0; e < 4; e++) {
                float c = bf_hi(aw[e]);
                float lo = fmaf(bf_lo(mv[e]), c * s_lo, MAG_LO), hi = fmaf(bf_hi(mv[e]), c * s_hi, MAG_HI);
                vw[e] = (__float_as_uint(hi) << 16) + __float_as_uint(lo);
            }
            unsigned char* pv = ps < 4 ? pv0 : ps > 4 ? pv1 : (half ? pv1 : pv0);
            stg4_lt(pv + ps * 512, vw, 0, rem);
            if (ps >= 6) ldg4_lt(a[ps - 6], pa + (ps - 6) * 256, k4, (cw.x >> (6 * (ps - 6))) & 0x3f);
        }
        PROF(1);
        it = 0;
        while (((volatile uint32_t*)mbs)[w] != 0) { __nanosleep(40); if (++it > SPIN_MAX * 4) __trap(); }
        int pl = lane & 15;
        if (pl < 9) {
            uint32_t cword = pl < 3 ? cw.x : pl < 6 ? cw.y : cw.z;
            mbv[w * 32 + 2 * pl + half] = ((cword >> ((pl % 3) * 6)) & 0x3f) | (tag >> 12);
        }
        __syncwarp();
        if (lane == 0) asm volatile("st.release.cta.shared.u32 [%0], %1;" ::"r"(SB + S_AUX + w * 4), "r"(base + 1) : "memory");
        PROF(2);
    }
    PROF_END;
}

__device__ __noinline__ void c_wrap(uint32_t row, int par, uint32_t old, uint32_t w, uint32_t wrap_base) {
    uint32_t nw = old + w, ov = ~(old ^ w) & (old ^ nw);
    int d = 0;
    if (ov & 0x8000u) d += (w & 0x8000u) ? -1 : 1;
    if (ov & 0x80000000u) d += (w & 0x80000000u) ? -256 : 256;
    if (d != 0) {
        uint32_t o2;
        asm volatile("atom.shared.add.u32 %0, [%1], %2;" : "=r"(o2) : "r"(wrap_base + row * 4), "r"(d << (16 * par)) : "memory");
        if ((o2 + (d << (16 * par))) & 0x80808080u) st_relaxed(&g_ctl.bad, 1);
    }
}

__device__ __forceinline__ void c_role(const Prm& p, unsigned char* ring, int X, int c) {
    const int tid = threadIdx.x, lane = tid & 31, w = __shfl_sync(0xffffffffu, tid >> 5, 0);
    const uint32_t wrap_off = ROWS_O * 8;
    for (int r = tid; r < (int)ROWS_O; r += THREADS) { ((uint2*)smem)[r] = make_uint2(0, 0); ((uint32_t*)(smem + wrap_off))[r] = 0x40404040u; }
    uint32_t* misc = (uint32_t*)(smem + S_MISC);
    if (tid == 0) {
        int it = 0; uint32_t pb;
        while (!((pb = ld_relaxed(&g_ctl.pagebits)) >> 31)) backoff(it);
        misc[4] = pb;
    }
    __syncthreads();
    const uint32_t pagebits = misc[4];
    const int par = lane & 1, half = lane >> 4, k4 = ((lane & 15) >> 1) * 4;
    const uint32_t sb = SB, acc = sb + par * 4;
    const int chi = c >= 9;
    uint32_t v_off[3];
#pragma unroll
    for (int ps = 0; ps < 3; ps++) v_off[ps] = gran(2 * (2 * ps + half) + chi) + (c - 9 * chi) * 256 + (lane & 15) * 16;
    const uint32_t b_off = gran(12 + chi) + (c - 9 * chi) * (UN * KS * 2) + (lane >> 1) * 8;
    const int NT = p.NS + 2 * GR;
    int n = w / (NP / 2), j = w % (NP / 2);
    uint32_t base = slot_base((2 * j + ((n + X) & 1)) * RS + ((n >> 1) % RS), pagebits, X);
    uint4 cw = make_uint4(0, 0, 0, 0);
    PROF_DECL
#pragma unroll 1
    while (n < NT) {
        const uint32_t tag2 = ((n >> 1) / RS + 1) * 0x00400040u;
        int it = 0;
        while ((((cw.x ^ tag2) | (cw.y ^ tag2) | (cw.z ^ tag2)) & 0xffc0ffc0u) != 0) {
            if (DEV_FREE) { cw.x = (cw.x & 1) + (31 | 27 << 16); cw.y = (cw.y & 1) + (22 | 30 << 16); cw.z = (cw.z & 1) + (29 | 24 << 16); break; }
            backoff(it);
            cw = ld_relaxed4(ring + (base ^ (OFF_MF + c * 16)));
        }
        PROF(0);
        uint4 v[3]; uint2 b[3]; int rem[3];
#pragma unroll
        for (int ps = 0; ps < 3; ps++) {
            uint32_t cword = ps == 0 ? cw.x : ps == 1 ? cw.y : cw.z;
            rem[ps] = (int)((cword >> (half * 16)) & 0x3f) - k4;
            ldg4_lt(v[ps], ring + (base ^ v_off[ps]), 0, rem[ps]);
            ldg2_lt(b[ps], ring + (base ^ b_off) + ps * 128, 0, rem[ps]);
        }
        unsigned char* rel = ring + (base ^ OFF_REL);
        j += NW - NP / 2; n += 1;
        if (j >= NP / 2) { j -= NP / 2; n += 1; }
        base = slot_base((2 * j + ((n + X) & 1)) * RS + ((n >> 1) % RS), pagebits, X);
        cw = ld_relaxed4(ring + (base ^ (OFF_MF + c * 16)));
#pragma unroll
        for (int ps = 0; ps < 3; ps++) {
            if (rem[ps] > 0) {
                if (DEV_FREE) { b[ps].x = (b[ps].x + b_off * 0x9e3779b1u * (4 * ps + 1)) >> 2 & 0x3fff3fffu; b[ps].y = (b[ps].y + b_off * 0x9e3779b1u * (4 * ps + 3)) >> 2 & 0x3fff3fffu; v[ps].x &= 0x10001; v[ps].y &= 0x10001; v[ps].z &= 0x10001; v[ps].w &= 0x10001; }
                uint32_t vw[4] = {v[ps].x, v[ps].y, v[ps].z, v[ps].w}, old[4], ov = 0;
#pragma unroll
                for (int e = 0; e < 4; e++) {
                    uint32_t bw = e < 2 ? b[ps].x : b[ps].y;
                    asm volatile("atom.shared.add.u32 %0, [%1], %2;" : "=r"(old[e]) : "r"((e & 1) ? __dp2a_hi(bw, 0x08000008u, acc) : __dp2a_lo(bw, 0x08000008u, acc)), "r"(vw[e]) : "memory");
                }
#pragma unroll
                for (int e = 0; e < 4; e++) ov |= ~(old[e] ^ vw[e]) & (old[e] ^ (old[e] + vw[e]));
                if (ov & 0x80008000u) {
#pragma unroll
                    for (int e = 0; e < 4; e++) {
                        uint32_t bw = e < 2 ? b[ps].x : b[ps].y;
                        c_wrap((e & 1) ? bw >> 16 : bw & 0xffffu, par, old[e], vw[e], sb + wrap_off);
                    }
                }
            }
        }
        __syncwarp();
        if (lane == 0) red_add(rel, 1);
        __syncwarp();
        PROF(1);
    }
    PROF_END;
}

__device__ __forceinline__ void c_epilogue(const Prm& p, int X, int c) {
    const int tid = threadIdx.x;
    float* scs = (float*)(smem + S_MISC);
    Wts* wt = (Wts*)(smem + S_AUX);
    load_wts(p, wt);
    if (tid < 32) {
        __syncwarp();
        float sc[4]; bool bad;
        get_scales(p, X, sc, bad);
#pragma unroll
        for (int ch = 0; ch < 4; ch++) if (tid == 0) scs[ch] = sc[ch] > 0.f ? 1.f / sc[ch] : 0.f;
    }
    __syncthreads();
    const int r0 = (X * NCP + c) * ROWS_O, nr = min((int)ROWS_O, p.E - r0);
    for (int r = tid; r < nr; r += THREADS) {
        uint2 s = ((uint2*)smem)[r];
        uint32_t wr = ((uint32_t*)(smem + ROWS_O * 8))[r];
        int l0 = (short)s.x, l2 = (short)s.y;
        int h1 = ((int)s.x >> 16) + ((s.x >> 15) & 1), h3 = ((int)s.y >> 16) + ((s.y >> 15) & 1);
        int w0 = (int)(wr & 0xff) - 64, w1 = (int)((wr >> 8) & 0xff) - 64, w2 = (int)((wr >> 16) & 0xff) - 64, w3 = (int)(wr >> 24) - 64;
        float a[4] = {(float)(l0 + 65536 * w0) * scs[0], (float)(h1 - w0 + 65536 * w1) * scs[1],
                      (float)(l2 + 65536 * w2) * scs[2], (float)(h3 - w2 + 65536 * w3) * scs[3]};
        finish_row(p, wt, r0 + r, a);
    }
}

__device__ __forceinline__ void grid_bar(unsigned* ctr) {
    __syncthreads();
    if (threadIdx.x == 0) { fence_gpu(); red_add(ctr, 1); wait_ge(ctr, gridDim.x); fence_gpu(); }
    __syncthreads();
}
__device__ __noinline__ void fallback(const Prm& p) {
    const int gt = blockIdx.x * THREADS + threadIdx.x, gs = gridDim.x * THREADS;
    Wts* wt = (Wts*)smem;
    __syncthreads();
    load_wts(p, wt);
    for (int e = gt; e < p.E; e += gs) g_acc[e] = make_float4(0.f, 0.f, 0.f, 0.f);
    grid_bar(&g_ctl.bar[0]);
    const float f = __bfloat162float(p.freq[0]);
    for (int t = gt; t < p.T; t += gs) {
        uint2 r = __ldg(p.m + p.idx_in[t]);
        float c = rbf16(cosf(rbf16(f * __bfloat162float(p.angle[t]))));
        asm volatile("red.global.add.v4.f32 [%0], {%1,%2,%3,%4};" ::"l"(g_acc + p.idx_out[t]), "f"(bf_lo(r.x) * c),
                     "f"(bf_hi(r.x) * c), "f"(bf_lo(r.y) * c), "f"(bf_hi(r.y) * c) : "memory");
    }
    grid_bar(&g_ctl.bar[1]);
    for (int e = gt; e < p.E; e += gs) {
        float4 a4 = __ldcg(g_acc + e);
        float a[4] = {a4.x, a4.y, a4.z, a4.w};
        finish_row(p, wt, e, a);
    }
}

__global__ void __launch_bounds__(THREADS, 1) gemnet_kernel(const __grid_constant__ Prm p) {
    const int tid = threadIdx.x, lane = tid & 31, w = __shfl_sync(0xffffffffu, tid >> 5, 0);
    uint32_t* misc = (uint32_t*)(smem + S_MISC);
    bool run_fallback = true;
    if (!p.force_bad && __cvta_generic_to_shared(smem) == SB) {
        unsigned char* const ring = p.ring;
        uint32_t smid; asm("mov.u32 %0, %%smid;" : "=r"(smid));
        const int cls = smid < NM ? 0 : (smid < NM + NP - 4 || (smid >= 124 && smid < 128)) ? 2 : 1;
        if (tid == 0) {
            uint32_t side = 0;
            if (cls != 2) side = probe_pair(ring + gran(15) + (blockIdx.x >> 7) * 2 * SLOT_BYTES + (blockIdx.x & 127) * 32);
            int pool = cls == 2 ? 4 : cls * 2 + side, id = 0;
            for (int k = 0; k < 7; k++) {
                int cap = pool < 2 ? NI : pool < 4 ? NCP : NP;
                id = atomicAdd(&g_ctl.ticket[pool], 1);
                if (id < cap) break;
                pool = k == 0 ? (pool == 4 ? 0 : pool ^ 1) : k - 1;
            }
            misc[8] = pool; misc[9] = id;
        }
        if (blockIdx.x == 0 && w >= 1 && w <= NPAGES) {
            if (lane == 0) misc[16 + w] = probe_pair(ring + ((size_t)(w - 1) << 21) + 8 * SLOT_BYTES + gran(15));
            asm volatile("bar.sync 1, %0;" ::"r"(NPAGES * 32) : "memory");
            if (tid == 32) {
                uint32_t pb = 0x80000000u;
                for (int k = 0; k < NPAGES; k++) pb |= (misc[17 + k] ^ misc[17]) << k;
                st_relaxed(&g_ctl.pagebits, pb);
            }
        }
        __syncthreads();
        const int pool = misc[8], id = misc[9];
        __syncthreads();
        if (DEV_FREE && !(DEV_FREE & (pool == 4 ? 1 : pool < 2 ? 2 : 4))) {
        } else if (pool == 4) {
            for (int k = tid; k < S_MISC / 16; k += THREADS) ((uint4*)smem)[k] = make_uint4(0, 0, 0, 0);
            __syncthreads();
            if (tid < 2 * NBUF) {
                const uint32_t a = __cvta_generic_to_shared(smem + P_BAR) + tid * 8, cnt = tid < NBUF ? CPS : 1;
                mbar_init(a, cnt);
                if (tid % NBUF < id % GR) asm volatile("mbarrier.arrive.shared.b64 _, [%0], %1;" ::"r"(a), "r"(cnt) : "memory");
            }
            __syncthreads();
            if (w < CPS) p_filler(p, id, w);
            else if (w < CPS + NF) {
                int it = 0; uint32_t pb;
                while (!((pb = ld_relaxed(&g_ctl.pagebits)) >> 31)) backoff(it);
                p_flusher(p, ring, __shfl_sync(0xffffffffu, pb, 0), id, w - CPS);
            }
        } else if (pool < 2) {
            m_role(p, ring, pool, id);
        } else {
            c_role(p, ring, pool - 2, id);
        }
        __syncthreads();
        if (tid == 0) { fence_gpu(); red_add(&g_ctl.fin, 1); }
        if ((pool == 2 || pool == 3) && !DEV_FREE) c_epilogue(p, pool - 2, id);
        if (tid == 0) { wait_ge(&g_ctl.fin, NCTA); fence_gpu(); misc[10] = ld_relaxed(&g_ctl.bad); }
        __syncthreads();
        run_fallback = misc[10] && !DEV_FREE;
    }
    if (run_fallback) fallback(p);
    if (tid == 0) {
        fence_gpu();
        if (atomicAdd(&g_ctl.exited, 1) == gridDim.x - 1) {
            uint32_t* c = (uint32_t*)&g_ctl;
            for (int k = 0; k < 32; k++) c[k] = 0;
        }
    }
}

cudaTextureObject_t make_tex(const void* ptr, size_t bytes, int words) {
    cudaResourceDesc rd = {};
    rd.resType = cudaResourceTypeLinear;
    rd.res.linear.devPtr = (void*)ptr;
    rd.res.linear.desc = words == 4 ? cudaCreateChannelDesc<uint4>() : cudaCreateChannelDesc<uint2>();
    rd.res.linear.sizeInBytes = bytes;
    cudaTextureDesc td = {};
    td.readMode = cudaReadModeElementType;
    cudaTextureObject_t t = 0;
    if (cudaCreateTextureObject(&t, &rd, &td, nullptr) != cudaSuccess) { cudaGetLastError(); return 0; }
    return t;
}

}

extern "C" void kernel_launch(void* const* d_in, const int* in_sizes, int n_in, void* d_out, int out_size) {
    static Prm p = {};
    static int grid = 0;
    const int E = in_sizes[3], T = in_sizes[1];
    if (grid == 0 || p.idx_in != d_in[1] || p.idx_out != d_in[2] || p.angle != d_in[4] || p.E != E || p.T != T) {
        int dev = 0, sms = 0;
        cudaGetDevice(&dev);
        cudaDeviceGetAttribute(&sms, cudaDevAttrMultiProcessorCount, dev);
        cudaFuncSetAttribute(gemnet_kernel, cudaFuncAttributeMaxDynamicSharedMemorySize, SMEM_BYTES);
        p.E = E; p.T = T;
        p.NS = (T / 128 + NP * CPS - 1) / (NP * CPS);
        void* rp = nullptr;
        cudaGetSymbolAddress(&rp, g_ring);
        p.ring = (unsigned char*)(((uintptr_t)rp + ((2u << 20) - 1)) & ~(uintptr_t)((2u << 20) - 1));
        bool fast = sms >= NCTA && E <= (int)FAST_E && T >= 128 && T <= (1 << 29);
        if (fast) {
            p.t_in = make_tex(d_in[1], (size_t)(T / 128) * 512, 4);
            p.t_out = make_tex(d_in[2], (size_t)(T / 128) * 512, 4);
            p.t_ang = make_tex(d_in[4], (size_t)(T / 128) * 256, 2);
            fast = p.t_in && p.t_out && p.t_ang;
        }
        p.force_bad = !fast;
        grid = fast ? NCTA : sms;
    }
    p.m = (const uint2*)d_in[0];
    p.idx_in = (const int*)d_in[1];
    p.idx_out = (const int*)d_in[2];
    p.dist = (const __nv_bfloat16*)d_in[3];
    p.angle = (const __nv_bfloat16*)d_in[4];
    p.centers = (const __nv_bfloat16*)d_in[5];
    p.freq = (const __nv_bfloat16*)d_in[6];
    p.w_rbf = (const __nv_bfloat16*)d_in[7];
    p.w_sbf = (const __nv_bfloat16*)d_in[8];
    p.w_down = (const __nv_bfloat16*)d_in[9];
    p.w_up = (const __nv_bfloat16*)d_in[10];
    p.out = (uint2*)d_out;
    gemnet_kernel<<<grid, THREADS, SMEM_BYTES>>>(p);
}
```

```cpp
#include <cuda_runtime.h>
#include <cuda_bf16.h>
#include <stdint.h>

namespace {

constexpr int NI = 12;
constexpr int UN = 3;
constexpr int NG = NI / UN;
constexpr int GR = 2 * NG;
constexpr int NCP = 18;
constexpr int NO = 2 * NCP;
constexpr int KS = 64;
constexpr int NB = UN * NCP;
constexpr int NBUF = 10;
constexpr int NMP = 2 * NI;
constexpr int NP = 48, NM = 2 * NMP, NC = NO, NCTA = NP + NM + NC;
#define CPS_ 24
constexpr int CPS = CPS_;
constexpr int NF = 4;
#define RA_ 3
#define RV_ 3
#define RB_ 8
constexpr int RA = RA_, RV = RV_, RB = RB_;
constexpr int QN = 80, QTRIG = 40;
#define MW_ 18
constexpr int MW = MW_;
#define MPF_ 6
constexpr int MPF = MPF_;
constexpr int THREADS = 896, NW = THREADS / 32;
#define DEV_FREE 0
#define PUBSLEEP_ 0
#define SLEEP_ 200

constexpr int RING_BYTES = NP << 20;
constexpr int NPAGES = RING_BYTES >> 21;
constexpr int MAX_E = 1 << 20;
constexpr int SMEM_BYTES = 232448;

constexpr int SB = 1024;

constexpr int P_CNT = 0;
constexpr int P_BAR = P_CNT + NBUF * NB * 4;
constexpr int P_B = (P_BAR + 2 * NBUF * 8 + 127) / 128 * 128;
constexpr int P_Q = P_B + NBUF * NB * KS * 2;
constexpr int P_A = SMEM_BYTES - 256 - NBUF * NB * KS * 4;
static_assert(P_Q + CPS * QN * 8 + 512 <= P_A && P_A % 128 == 0, "P smem");
constexpr int S_MISC = SMEM_BYTES - 256;
constexpr int S_AUX = S_MISC - 512;

constexpr unsigned FAST_E = 640000;
constexpr unsigned magic_of(unsigned long long d) { return (unsigned)(((1ull << 32) + d - 1) / d); }
constexpr bool magic_ok(unsigned long long d) { return (magic_of(d) * d - (1ull << 32)) * FAST_E < (1ull << 32); }
constexpr unsigned pick_rows(unsigned lo) {
    unsigned d = (lo + 3) & ~3u;
    while (!magic_ok(d)) d += 4;
    return d;
}
constexpr unsigned ROWS_I = pick_rows((FAST_E + NI - 1) / NI), ROWS_O = pick_rows((FAST_E + NO - 1) / NO);
constexpr unsigned MAG_I = magic_of(ROWS_I), MAG_O = magic_of(ROWS_O), HALF_O = ROWS_O * NCP;
constexpr int C_WRAP = ROWS_O * 8, C_TAB = ROWS_O * 12, TAB_N = 1025, TAB_LO = 0x3f80 - 1024;
static_assert(ROWS_I * 4 <= S_AUX && C_TAB + TAB_N * 16 <= S_AUX && ROWS_I <= 65536 && ROWS_O <= 32768, "tables");

struct __align__(128) Ctl {
    unsigned ticket[5];
    unsigned pagebits;
    unsigned stat_cnt[2];
    unsigned bad;
    unsigned fin;
    unsigned bar[3];
    unsigned exited;
    unsigned pad[18];
    float stat[2][NMP][4];
};

struct Prm {
    const uint2* m; const int* idx_in; const int* idx_out; const __nv_bfloat16* dist; const __nv_bfloat16* angle;
    const __nv_bfloat16* centers; const __nv_bfloat16* freq; const __nv_bfloat16* w_rbf; const __nv_bfloat16* w_sbf;
    const __nv_bfloat16* w_down; const __nv_bfloat16* w_up; uint2* out;
    cudaTextureObject_t t_in, t_out, t_ang;
    int E, T;
    unsigned char* ring;
    int NS;
    int force_bad;
};

__device__ __align__(128) unsigned char g_ring[RING_BYTES + (2 << 20)];
__device__ Ctl g_ctl;
__device__ float4 g_acc[MAX_E];
#define PROF_DECL
#define PROF(k)
#define PROF_END

extern __shared__ __align__(128) unsigned char smem[];

__device__ __forceinline__ float bf_lo(uint32_t w) { return __uint_as_float(w << 16); }
__device__ __forceinline__ float bf_hi(uint32_t w) { return __uint_as_float(w & 0xffff0000u); }
__device__ __forceinline__ float rbf16(float x) { return __bfloat162float(__float2bfloat16_rn(x)); }
__device__ __forceinline__ uint32_t pack_bf16(float hi, float lo) {
    uint32_t r; asm("cvt.rn.bf16x2.f32 %0, %1, %2;" : "=r"(r) : "f"(hi), "f"(lo)); return r;
}
__device__ __forceinline__ uint32_t prmt(uint32_t a, uint32_t b, uint32_t c) {
    uint32_t r; asm("prmt.b32 %0, %1, %2, %3;" : "=r"(r) : "r"(a), "r"(b), "r"(c)); return r;
}
__device__ __forceinline__ uint32_t ld_relaxed(const void* p) {
    uint32_t v; asm volatile("ld.relaxed.gpu.global.u32 %0, [%1];" : "=r"(v) : "l"(p) : "memory"); return v;
}
__device__ __forceinline__ uint2 ld_relaxed2(const void* p) {
    uint2 v; asm volatile("ld.relaxed.gpu.global.v2.u32 {%0,%1}, [%2];" : "=r"(v.x), "=r"(v.y) : "l"(p) : "memory"); return v;
}
__device__ __forceinline__ uint4 ld_relaxed4(const void* p) {
    uint4 v; asm volatile("ld.relaxed.gpu.global.v4.u32 {%0,%1,%2,%3}, [%4];" : "=r"(v.x), "=r"(v.y), "=r"(v.z), "=r"(v.w) : "l"(p) : "memory"); return v;
}
__device__ __forceinline__ void st_relaxed(void* p, uint32_t v) { asm volatile("st.relaxed.gpu.global.u32 [%0], %1;" ::"l"(p), "r"(v) : "memory"); }
__device__ __forceinline__ void st_relaxed16(void* p, uint32_t v) { asm volatile("st.relaxed.gpu.global.u16 [%0], %1;" ::"l"(p), "h"((uint16_t)v) : "memory"); }
__device__ __forceinline__ void red_add(void* p, uint32_t v) { asm volatile("red.relaxed.gpu.global.add.u32 [%0], %1;" ::"l"(p), "r"(v) : "memory"); }
__device__ __forceinline__ void fence_gpu() { asm volatile("fence.acq_rel.gpu;" ::: "memory"); }
__device__ __forceinline__ void fence_release() { asm volatile("fence.release.gpu;" ::: "memory"); }
__device__ __forceinline__ void mbar_init(uint32_t a, uint32_t n) { asm volatile("mbarrier.init.shared.b64 [%0], %1;" ::"r"(a), "r"(n) : "memory"); }
__device__ __forceinline__ void mbar_arrive(uint32_t a) { asm volatile("mbarrier.arrive.shared.b64 _, [%0];" ::"r"(a) : "memory"); }
__device__ __forceinline__ bool mbar_try(uint32_t a, uint32_t ph) {
    uint32_t ok;
    asm volatile("{.reg .pred p; mbarrier.try_wait.parity.shared.b64 p, [%1], %2, %3; selp.u32 %0, 1, 0, p;}" : "=r"(ok) : "r"(a), "r"(ph), "r"(2000) : "memory");
    return ok;
}
constexpr int SPIN_MAX = 1 << 22;
__device__ __forceinline__ void mbar_wait(uint32_t a, uint32_t ph) {
    int it = 0;
    while (!mbar_try(a, ph)) { if (++it > SPIN_MAX) __trap(); }
}
__device__ __forceinline__ void backoff(int& it) { __nanosleep(SLEEP_); if (++it > SPIN_MAX) __trap(); }
__device__ __forceinline__ void wait_ge(const void* p, uint32_t v) {
    int it = 0;
    while (ld_relaxed(p) < v) backoff(it);
}

__device__ __forceinline__ bool elect_one() {
    uint32_t r; asm volatile("{.reg .pred p; elect.sync _|p, 0xffffffff; selp.u32 %0, 1, 0, p;}" : "=r"(r)); return r;
}
__device__ __forceinline__ void red_lane0(void* p, int lane) { if (lane == 0) red_add(p, 1); }
__device__ __forceinline__ void lds_lt(uint32_t& v, uint32_t ad, int a, int b) {
    asm volatile("{.reg .pred p; setp.lt.s32 p, %2, %3; @p ld.shared.u32 %0, [%1];}" : "+r"(v) : "r"(ad), "r"(a), "r"(b));
}
__device__ __forceinline__ void ldg4_lt(uint4& v, const void* ad, int a, int b) {
    asm volatile("{.reg .pred p; setp.lt.s32 p, %5, %6; @p ld.relaxed.gpu.global.v4.u32 {%0,%1,%2,%3}, [%4];}"
                 : "=r"(v.x), "=r"(v.y), "=r"(v.z), "=r"(v.w) : "l"(ad), "r"(a), "r"(b) : "memory");
}
template <bool KEEP>
__device__ __forceinline__ void ldg6_lt(uint4& v, uint2& u, const void* av, const void* au, int a, int b) {
    if (KEEP)
        asm volatile("{.reg .pred p; setp.lt.s32 p, %8, %9; @p ld.relaxed.gpu.global.v4.u32 {%0,%1,%2,%3}, [%6]; @p ld.relaxed.gpu.global.v2.u32 {%4,%5}, [%7];}"
                     : "=r"(v.x), "=r"(v.y), "=r"(v.z), "=r"(v.w), "+r"(u.x), "=r"(u.y) : "l"(av), "l"(au), "r"(a), "r"(b) : "memory");
    else
        asm volatile("{.reg .pred p; setp.lt.s32 p, %8, %9; @p ld.relaxed.gpu.global.v4.u32 {%0,%1,%2,%3}, [%6]; @p ld.relaxed.gpu.global.v2.u32 {%4,%5}, [%7];}"
                     : "=r"(v.x), "=r"(v.y), "=r"(v.z), "=r"(v.w), "=r"(u.x), "=r"(u.y) : "l"(av), "l"(au), "r"(a), "r"(b) : "memory");
}
__device__ __forceinline__ void stg4_lt(void* ad, const uint32_t v[4], int a, int b) {
    asm volatile("{.reg .pred p; setp.lt.s32 p, %5, %6; @p st.global.v4.u32 [%0], {%1,%2,%3,%4};}"
                 ::"l"(ad), "r"(v[0]), "r"(v[1]), "r"(v[2]), "r"(v[3]), "r"(a), "r"(b) : "memory");
}

constexpr uint32_t R_V1 = 0x03000, R_A = 0x81000, R_B = 0x82000, R_UNIT = 0x4000, R_HI = 0x40000 - 8 * 256;
__device__ __forceinline__ uint32_t q_base(uint32_t q, uint32_t pagebits_x) { return (q << 20) | (((pagebits_x >> (q >> 1)) & 1u) << 12); }
__device__ __forceinline__ uint32_t slot_off(uint32_t s) { return (s << 16) | (((s + 1) & 2) << 11); }
constexpr uint32_t OFF_PF = R_B + 3 * R_UNIT, OFF_PC = OFF_PF + 128, OFF_RDY = OFF_PC + 96, OFF_REL = OFF_PF + 256, OFF_ARL = OFF_PF + 260;
constexpr uint32_t OFF_PROBE = 3 * R_UNIT;
static_assert(RA <= 4 && RV <= 4 && RB <= 8 && RA <= RB && RV <= RB, "ring");

__device__ __forceinline__ uint32_t probe(unsigned char* p) {
    volatile uint32_t* sink = (volatile uint32_t*)(smem + S_MISC + 240);
    uint32_t best = 0xffffffffu;
#pragma unroll 1
    for (int r = 0; r < 3; r++) {
        uint32_t t0, t1, v;
        asm volatile("mov.u32 %0, %%clock;" : "=r"(t0)::"memory");
        asm volatile("atom.relaxed.gpu.global.add.u32 %0, [%1], 1;" : "=r"(v) : "l"(p) : "memory");
        *sink = v;
        asm volatile("mov.u32 %0, %%clock;" : "=r"(t1)::"memory");
        best = min(best, t1 - t0);
    }
    return best;
}
__device__ __forceinline__ uint32_t probe_pair(unsigned char* p) {
    asm volatile("st.global.v4.u32 [%0], {%1,%1,%1,%1};" ::"l"(p), "r"(0) : "memory");
    asm volatile("st.global.v4.u32 [%0], {%1,%1,%1,%1};" ::"l"(p + 16), "r"(0) : "memory");
    asm volatile("st.global.v4.u32 [%0], {%1,%1,%1,%1};" ::"l"(p + 4096), "r"(0) : "memory");
    asm volatile("st.global.v4.u32 [%0], {%1,%1,%1,%1};" ::"l"(p + 4112), "r"(0) : "memory");
    uint32_t a = probe(p), b = probe(p + 4096);
    return a > b;
}

struct Wts { float c[8], wr[32], ws[32], wd[16], wu[16]; };
__device__ __forceinline__ void load_wts(const Prm& p, Wts* w) {
    int t = threadIdx.x;
    if (t < 8) w->c[t] = __bfloat162float(p.centers[t]);
    if (t < 32) { w->wr[t] = __bfloat162float(p.w_rbf[t]); w->ws[t] = __bfloat162float(p.w_sbf[t]); }
    if (t < 16) { w->wd[t] = __bfloat162float(p.w_down[t]); w->wu[t] = __bfloat162float(p.w_up[t]); }
}
__device__ __forceinline__ void radial(const Wts* w, float d, float s[4], float g[4]) {
#pragma unroll
    for (int j = 0; j < 4; j++) s[j] = g[j] = 0.f;
#pragma unroll
    for (int r = 0; r < 8; r++) {
        float x = rbf16(d - w->c[r]);
        float b = rbf16(__expf(rbf16(-10.0f * rbf16(x * x))));
#pragma unroll
        for (int j = 0; j < 4; j++) { s[j] += b * w->ws[r * 4 + j]; g[j] += b * w->wr[r * 4 + j]; }
    }
}
__device__ __noinline__ uint4 radial_bf16(const Wts* w, uint32_t dbits) {
    float s[4], g[4];
    radial(w, __uint_as_float(dbits << 16), s, g);
    return make_uint4(pack_bf16(s[1], s[0]), pack_bf16(s[3], s[2]), pack_bf16(g[1], g[0]), pack_bf16(g[3], g[2]));
}
__device__ __forceinline__ uint2 finish_row(const float* wd, const float* wu, const float a[4], const float s[4], const float g[4], uint2 r) {
    float agg[4], o[4];
#pragma unroll
    for (int j = 0; j < 4; j++) agg[j] = s[j] * (a[0] * wd[j] + a[1] * wd[4 + j] + a[2] * wd[8 + j] + a[3] * wd[12 + j]);
    const float mm[4] = {bf_lo(r.x), bf_hi(r.x), bf_lo(r.y), bf_hi(r.y)};
#pragma unroll
    for (int j = 0; j < 4; j++) o[j] = mm[j] + (agg[0] * wu[j] + agg[1] * wu[4 + j] + agg[2] * wu[8 + j] + agg[3] * wu[12 + j]) * g[j];
    return make_uint2(pack_bf16(o[1], o[0]), pack_bf16(o[3], o[2]));
}

__device__ __forceinline__ void get_scales(const Prm& p, int side, float sc[4], bool& bad) {
    const int lane = threadIdx.x & 31;
    wait_ge(&g_ctl.stat_cnt[side], NMP);
    fence_gpu();
    uint4 a = make_uint4(0, 0, 0, 0), b = a;
    if (lane < NI) { a = ld_relaxed4(&g_ctl.stat[side][2 * lane][0]); b = ld_relaxed4(&g_ctl.stat[side][2 * lane + 1][0]); }
    uint32_t mxb[4] = {a.x, a.y, b.x, b.y};
    float ss[4] = {__uint_as_float(a.z), __uint_as_float(a.w), __uint_as_float(b.z), __uint_as_float(b.w)};
    bad = false;
    const float kdeg = fminf(3.5f * sqrtf(fmaxf(0.5f * (float)p.T / (float)p.E, 1.0f)), 128.f);
#pragma unroll
    for (int ch = 0; ch < 4; ch++) {
        float mx = __uint_as_float(__reduce_max_sync(0xffffffffu, mxb[ch]));
#pragma unroll
        for (int o = 16; o; o >>= 1) ss[ch] += __shfl_xor_sync(0xffffffffu, ss[ch], o);
        float rms = sqrtf(ss[ch] / (float)p.E);
        float range = fmaxf(mx, kdeg * rms);
        if (!(mx <= 1e15f) || !(range <= 128.f * rms) || (mx > 0.f && mx < 1e-15f)) bad = true;
        sc[ch] = range > 0.f ? 32767.f / range : 0.f;
    }
}

constexpr int PER = 40;
struct __align__(16) PTab { uint32_t e[PER][4]; };
constexpr PTab make_ptab() {
    PTab t = {};
    for (int s = 0; s < PER; s++) {
        for (int d = 0; d < GR; d++) {
            int gi = (s + d) % GR, buf = (s + d) % NBUF, X = gi & 1, g = gi >> 1;
            t.e[s][X] |= (uint32_t)(4 * UN * buf - g - 4 * X + 7) << (8 * g);
        }
        int mnew = s + GR - 1;
        t.e[s][2] = (uint32_t)(SB + P_BAR + (NBUF + mnew % NBUF) * 8) | (uint32_t)(((mnew / NBUF) & 1) ^ 1) << 31;
        t.e[s][3] = (uint32_t)(SB + P_BAR + (s % NBUF) * 8) | (uint32_t)((s + 1) % PER) << 16;
    }
    return t;
}
__constant__ PTab c_ptab = make_ptab();
constexpr int BIAS = 7 * NCP;
static_assert(NG == 4, "group selection");

struct PCtx { uint32_t a0, a1; };
struct PElem { uint32_t b4, aw, ol, r2; };

__device__ __forceinline__ void p_bin(const PCtx& c, PElem& e, uint32_t i, uint32_t o, uint32_t cw, uint32_t csel) {
    uint32_t ib = __umulhi(i, MAG_I), ob = __umulhi(o, MAG_O), sel = ib & 3;
    asm("{.reg .pred p; setp.ge.u32 p, %1, %2; @p add.u32 %0, %0, 4;}" : "+r"(sel) : "r"(o), "n"(HALF_O));
    e.b4 = __dp4a(prmt(c.a0, c.a1, sel), (uint32_t)NCP, ib * NCP + ob * 4);
    e.aw = prmt(i - ib * ROWS_I, cw, csel);
    e.ol = o - ob * ROWS_O;
}
__device__ __forceinline__ void p_rank(PElem& e) {
    asm volatile("atom.shared.add.u32 %0, [%1+%2], 2;" : "=r"(e.r2) : "r"(e.b4), "n"(SB + P_CNT - BIAS) : "memory");
}
__device__ __forceinline__ void p_store(const PElem& e) {
    const uint32_t ab = e.b4 * (KS / 2) + e.r2;
    asm volatile("{.reg .pred p; setp.lt.u32 p, %4, %5; @p st.shared.u32 [%0+%6], %1; @p st.shared.u16 [%2+%7], %3;}"
                 ::"r"(ab * 2), "r"(e.aw), "r"(ab), "h"((uint16_t)e.ol), "r"(e.r2), "n"(KS * 2),
                   "n"(SB + P_A - BIAS * KS), "n"(SB + P_B - BIAS * (KS / 2)) : "memory");
}
__device__ __noinline__ uint32_t cos2_slow(uint32_t x) {
    float a = cosf(bf_lo(x)), b = cosf(bf_hi(x));
    if (!(fabsf(a + b) <= 2.f)) { st_relaxed(&g_ctl.bad, 1); a = b = 0.f; }
    return pack_bf16(b, a);
}

struct PIn { uint4 i, o; uint2 a; };
__device__ __forceinline__ void p_fetch(const Prm& p, PIn& x, int v) {
    asm volatile("{.reg .b32 d0, d1; tex.1d.v4.u32.s32 {%0,%1,d0,d1}, [%2, {%3}];}" : "=r"(x.a.x), "=r"(x.a.y) : "l"(p.t_ang), "r"(v));
    asm volatile("tex.1d.v4.u32.s32 {%0,%1,%2,%3}, [%4, {%5}];" : "=r"(x.i.x), "=r"(x.i.y), "=r"(x.i.z), "=r"(x.i.w) : "l"(p.t_in), "r"(v));
    asm volatile("tex.1d.v4.u32.s32 {%0,%1,%2,%3}, [%4, {%5}];" : "=r"(x.o.x), "=r"(x.o.y), "=r"(x.o.z), "=r"(x.o.w) : "l"(p.t_out), "r"(v));
}

struct PFill {
    PCtx c;
    uint32_t qb, qt, lt, f2, nxt;
    __device__ __forceinline__ void begin() {
        const uint2* t = (const uint2*)c_ptab.e + 2 * (nxt >> 16);
        const uint2 m = t[0], s = t[1];
        c.a0 = m.x; c.a1 = m.y;
        nxt = s.y;
        mbar_wait(s.x & 0xffff, s.x >> 31);
    }
    __device__ __forceinline__ void end() {
        __syncwarp();
        asm volatile("{.reg .pred p; setp.eq.u32 p, %1, 0; @p mbarrier.arrive.shared.b64 _, [%0];}" ::"r"(nxt & 0xffff), "r"(lt) : "memory");
    }
    __device__ __forceinline__ void push(bool f, uint32_t x, uint32_t y) {
        uint32_t mask = __ballot_sync(0xffffffffu, f);
        asm volatile("{.reg .pred p; setp.ne.u32 p, %3, 0; @p st.shared.v2.u32 [%0], {%1,%2};}" ::"r"(qt + __popc(mask & lt) * 8), "r"(x), "r"(y), "r"((uint32_t)f) : "memory");
        qt += __popc(mask) * 8;
    }
    __device__ __forceinline__ void push_checked(bool f, uint32_t i, uint32_t o, uint32_t aw) {
        if (qt - qb + __popc(__ballot_sync(0xffffffffu, f)) * 8 > QN * 8) st_relaxed(&g_ctl.bad, 1);
        else push(f, prmt(i, aw, 0x6210), prmt(o, aw, 0x7210));
    }
    __device__ __forceinline__ void chunk(const PIn& x) {
        uint32_t x0, x1, c0, c1;
        asm("mul.rn.bf16x2 %0, %1, %2;" : "=r"(x0) : "r"(x.a.x), "r"(f2));
        asm("mul.rn.bf16x2 %0, %1, %2;" : "=r"(x1) : "r"(x.a.y), "r"(f2));
        c0 = pack_bf16(__cosf(bf_hi(x0)), __cosf(bf_lo(x0)));
        c1 = pack_bf16(__cosf(bf_hi(x1)), __cosf(bf_lo(x1)));
        if (__any_sync(0xffffffffu, (((x0 & 0x7fff7fffu) + 0x3e003e00u) | ((x1 & 0x7fff7fffu) + 0x3e003e00u)) & 0x80008000u)) { c0 = cos2_slow(x0); c1 = cos2_slow(x1); }
        PElem e0, e1, e2, e3;
        p_bin(c, e0, x.i.x, x.o.x, c0, 0x5410); p_rank(e0);
        p_bin(c, e1, x.i.y, x.o.y, c0, 0x7610); p_rank(e1);
        p_bin(c, e2, x.i.z, x.o.z, c1, 0x5410); p_rank(e2);
        p_bin(c, e3, x.i.w, x.o.w, c1, 0x7610); p_rank(e3);
        p_store(e0); p_store(e1); p_store(e2); p_store(e3);
        const uint32_t r01 = e0.r2 | e1.r2, r23 = e2.r2 | e3.r2;
        const bool f = (r01 | r23) >= KS * 2;
        if (__any_sync(0xffffffffu, f)) {
            const bool f0 = e0.r2 >= KS * 2, f1 = e1.r2 >= KS * 2, f2_ = e2.r2 >= KS * 2, f3 = e3.r2 >= KS * 2, f01 = r01 >= KS * 2;
            uint32_t si = f01 ? (f0 ? x.i.x : x.i.y) : (f2_ ? x.i.z : x.i.w);
            uint32_t so = f01 ? (f0 ? x.o.x : x.o.y) : (f2_ ? x.o.z : x.o.w);
            uint32_t sc = f01 ? (f0 ? e0.aw : e1.aw) : (f2_ ? e2.aw : e3.aw);
            push(f, prmt(si, sc, 0x6210), prmt(so, sc, 0x7210));
            uint32_t s2 = max(max(min(e0.r2, e1.r2), min(e2.r2, e3.r2)), min(r01, r23));
            if (__any_sync(0xffffffffu, s2 >= KS * 2)) {
                push_checked(f1 && f0, x.i.y, x.o.y, e1.aw);
                push_checked(f2_ && f01, x.i.z, x.o.z, e2.aw);
                push_checked(f3 && (f01 || f2_), x.i.w, x.o.w, e3.aw);
            }
            if (qt - qb >= QTRIG * 8) {
                retry(32);
                if (qt - qb > (QN - 32) * 8) { st_relaxed(&g_ctl.bad, 1); qt = qb; }
            }
        }
    }
    __device__ __forceinline__ void retry(uint32_t take) {
        const uint32_t lane8 = (threadIdx.x & 31) * 8;
        uint2 e, r0, r1;
        __syncwarp();
        asm volatile("ld.shared.v2.u32 {%0,%1}, [%2];" : "=r"(e.x), "=r"(e.y) : "r"(qb + lane8) : "memory");
        asm volatile("ld.shared.v2.u32 {%0,%1}, [%2];" : "=r"(r0.x), "=r"(r0.y) : "r"(qb + lane8 + take * 8) : "memory");
        qt -= take * 8;
        const bool more = qt - qb > 256;
        if (more) asm volatile("ld.shared.v2.u32 {%0,%1}, [%2];" : "=r"(r1.x), "=r"(r1.y) : "r"(qb + lane8 + take * 8 + 256) : "memory");
        __syncwarp();
        if (qb + lane8 < qt) asm volatile("st.shared.v2.u32 [%0], {%1,%2};" ::"r"(qb + lane8), "r"(r0.x), "r"(r0.y) : "memory");
        if (more && qb + lane8 + 256 < qt) asm volatile("st.shared.v2.u32 [%0], {%1,%2};" ::"r"(qb + lane8 + 256), "r"(r1.x), "r"(r1.y) : "memory");
        PElem el;
        el.r2 = 0;
        if (lane8 < take * 8) {
            p_bin(c, el, e.x & 0xffffffu, e.y & 0xffffffu, prmt(e.x, e.y, 0x0073), 0x5410);
            p_rank(el);
            p_store(el);
        }
        push(el.r2 >= KS * 2, e.x, e.y);
    }
};

__device__ __forceinline__ void p_filler(const Prm& p, int q, int w) {
    PFill F;
    const int lane = threadIdx.x & 31;
    F.lt = __shfl_sync(0xffffffffu, (1u << lane) - 1u, lane);
    F.qb = F.qt = SB + P_Q + w * (QN * 8); F.nxt = (q % GR) << 16;
    F.f2 = __shfl_sync(0xffffffffu, __bfloat16_as_ushort(p.freq[0]) * 0x10001u, 0);
    constexpr int vstep = NP * CPS * 32;
    const int NS = p.NS, vend = (p.T >> 7) * 32;
    int v = (q * CPS + w) * 32 + lane;
    PIn x0, x1, x2;
    p_fetch(p, x0, v); p_fetch(p, x1, v + vstep);
    PROF_DECL
    const int nch = __shfl_sync(0xffffffffu, (vend - v + vstep - 1) / vstep, 0);
    int n = 0;
#pragma unroll 1
    for (; n + 3 <= nch; n += 3) {
        PROF(1); F.begin(); PROF(0); p_fetch(p, x2, v + 2 * vstep); F.chunk(x0); F.end();
        p_fetch(p, x0, v + 3 * vstep); PROF(1); F.begin(); PROF(0); F.chunk(x1); F.end();
        p_fetch(p, x1, v + 4 * vstep); PROF(1); F.begin(); PROF(0); F.chunk(x2); F.end();
        v += 3 * vstep;
    }
    PROF_END;
#pragma unroll 1
    for (; n < nch; n++) {
        F.begin(); F.chunk(x0); F.end();
        x0 = x1;
    }
    if (q == 0 && w < 4) {
        int t = vend * 4 + w * 32 + lane;
        bool f = t < p.T;
        uint32_t i = 0, o = 0, x = 0;
        if (f) { i = p.idx_in[t]; o = p.idx_out[t]; asm("mul.rn.bf16x2 %0, %1, %2;" : "=r"(x) : "r"((uint32_t)__bfloat16_as_ushort(p.angle[t]) << 16), "r"(F.f2)); }
        F.push_checked(f, i, o, cos2_slow(x & 0xffff0000u));
    }
#pragma unroll 1
    for (; n <= NS + GR; n++) {
        F.begin();
        for (uint32_t nq = (F.qt - F.qb) >> 3; nq > 0;) { uint32_t take = min(nq, 32u); F.retry(take); nq -= take; }
        F.end();
    }
    if (F.qt != F.qb) st_relaxed(&g_ctl.bad, 1);
}

__device__ __forceinline__ void p_flusher(const Prm& p, unsigned char* ring, uint32_t pagebits, int q, int f) {
    const int lane = threadIdx.x & 31;
    const uint32_t bar = SB + P_BAR;
    const int NS = p.NS, NT = NS + 2 * GR;
    const uint32_t pfo = OFF_PF + (lane / 6) * 32 + (lane & 1) * 16 + ((lane % 6) >> 1) * 4;
    const uint32_t pfc = (lane >> 1) * 6 + (lane & 1);
    PROF_DECL
#pragma unroll 1
    for (int n = f; n < NT; n += NF) {
        const uint32_t buf = (n + q % GR) % NBUF, ph = ((n + q % GR) / NBUF) & 1;
        const uint32_t h = n >> 1, lap = h / RB;
        const uint32_t qb = q_base(q, pagebits) ^ (((n + q) & 1) << 12);
        const uint32_t ba = qb ^ slot_off(h % RA) ^ R_A, bb = qb ^ slot_off(h % RB);
        if (h >= RA && !DEV_FREE) {
            const unsigned char* wp = ring + (lane == 0 ? bb ^ OFF_REL : qb ^ slot_off((h - RA) % RB) ^ OFF_ARL);
            const uint32_t need = lane == 0 ? NCP * lap : 2 * UN * ((h - RA) / RB + 1);
            if (lane < 2) wait_ge(wp, need);
            __syncwarp();
        }
        PROF(0);
        if (n <= NS + GR) mbar_wait(bar + buf * 8, ph);
        else { int nl = NS + GR + q % GR; mbar_wait(bar + (nl % NBUF) * 8, (nl / NBUF) & 1); }
        PROF(1);
        uint32_t* cnt = (uint32_t*)(smem + P_CNT) + buf * NB;
        bool any = true;
        if (n >= NS) any = __any_sync(0xffffffffu, lane < NCP && (cnt[lane] | cnt[NCP + lane] | cnt[2 * NCP + lane]));
        if (any && elect_one()) {
            asm volatile("fence.proxy.async.shared::cta;" ::: "memory");
#pragma unroll
            for (int k = 0; k < 9; k++) {
                const int u = k < 6 ? k >> 1 : k - 6, hi = k < 6 && (k & 1);
                const uint32_t soff = k < 6 ? P_A + (u * NCP + hi * 8) * (KS * 4) + buf * (NB * KS * 4) : P_B + u * (NCP * KS * 2) + buf * (NB * KS * 2);
                asm volatile("cp.async.bulk.global.shared::cta.bulk_group [%0], [%1], %2;"
                             ::"l"(ring + (k < 6 ? ba : bb ^ R_B) + (u * R_UNIT + hi * 0x40000)), "r"(SB + soff),
                               "r"(k < 6 ? (hi ? NCP - 8 : 8) * (KS * 4) : NCP * KS * 2) : "memory");
            }
            asm volatile("cp.async.bulk.commit_group;" ::: "memory");
        }
        __syncwarp();
        uint32_t wm = (lap + 1) << 21, wc = wm;
        if (lane < NCP) {
#pragma unroll
            for (int u = 0; u < 3; u++) {
                wm |= min(cnt[pfc + 2 * u] >> 1, (uint32_t)KS) << (7 * u);
                wc |= min(cnt[lane + NCP * u] >> 1, (uint32_t)KS) << (7 * u);
            }
        }
        __syncwarp();
        if (lane < NB / 2) ((uint2*)cnt)[lane] = make_uint2(0, 0);
        PROF(3);
        asm volatile("cp.async.bulk.wait_group 0;" ::: "memory");
        __syncwarp();
        PROF(2);
        if (lane == 0) mbar_arrive(bar + (NBUF + buf) * 8);
        if (any) fence_release();
        PROF(4);
        if (lane < NCP) { st_relaxed(ring + (bb ^ pfo), wm); st_relaxed(ring + (bb ^ (OFF_PC + lane * 4)), wc); }
    }
    PROF_END;
    if (f == 0) {
        const uint32_t X = lane & 1, r = (lane >> 1) % RB;
        const int nh = (NT - ((X + q) & 1) + 1) >> 1;
        const uint32_t bb = q_base(q, pagebits) ^ (X << 12) ^ slot_off(r);
        if (!DEV_FREE) wait_ge(ring + (bb ^ OFF_REL), NCP * ((nh - (int)r + RB - 1) / RB));
        __syncwarp();
        for (int k = 0; k < 24; k++) *(uint4*)(ring + (bb ^ OFF_PF) + k * 16) = make_uint4(0, 0, 0, 0);
    }
}

__device__ __forceinline__ void m_role(const Prm& p, unsigned char* ring, int X, int id) {
    const int tid = threadIdx.x, lane = tid & 31, w = __shfl_sync(0xffffffffu, tid >> 5, 0);
    const int ib = id >> 1, ty = id & 1;
    {
        const int r0 = ib * ROWS_I, nr = max(min((int)ROWS_I, p.E - r0), 0);
        const uint4* src = (const uint4*)(p.m + r0);
        uint32_t mx = 0; float s0 = 0.f, s1 = 0.f;
        constexpr int LB = 10;
#pragma unroll 1
        for (int rb = tid; rb < (int)ROWS_I / 2; rb += LB * THREADS) {
            uint4 v[LB];
#pragma unroll
            for (int k = 0; k < LB; k++) {
                v[k] = make_uint4(0, 0, 0, 0);
                asm volatile("{.reg .pred p; setp.lt.s32 p, %5, %6; @p ld.global.nc.L1::no_allocate.v4.u32 {%0,%1,%2,%3}, [%4];}"
                             : "+r"(v[k].x), "+r"(v[k].y), "+r"(v[k].z), "+r"(v[k].w) : "l"(src + rb + k * THREADS), "r"(rb + k * THREADS), "r"(nr / 2));
            }
#pragma unroll
            for (int k = 0; k < LB; k++) {
                const uint32_t x = ty ? v[k].y : v[k].x, y = ty ? v[k].w : v[k].z;
                if (rb + k * THREADS < (int)ROWS_I / 2) ((uint2*)smem)[rb + k * THREADS] = make_uint2(x, y);
                mx = __vimax3_u16x2(mx, x & 0x7fff7fffu, y & 0x7fff7fffu);
                s0 += bf_lo(x) * bf_lo(x); s0 += bf_lo(y) * bf_lo(y); s1 += bf_hi(x) * bf_hi(x); s1 += bf_hi(y) * bf_hi(y);
            }
        }
        uint32_t mx0 = mx & 0xffffu, mx1 = mx & 0xffff0000u;
        uint4* red = (uint4*)(smem + S_AUX);
        mx0 = __reduce_max_sync(0xffffffffu, mx0 << 16); mx1 = __reduce_max_sync(0xffffffffu, mx1);
#pragma unroll
        for (int o = 16; o; o >>= 1) { s0 += __shfl_xor_sync(0xffffffffu, s0, o); s1 += __shfl_xor_sync(0xffffffffu, s1, o); }
        if (lane == 0) red[w] = make_uint4(mx0, mx1, __float_as_uint(s0), __float_as_uint(s1));
        __syncthreads();
        if (w == 0) {
            uint4 t = lane < NW ? red[lane] : make_uint4(0, 0, 0, 0);
            mx0 = __reduce_max_sync(0xffffffffu, t.x); mx1 = __reduce_max_sync(0xffffffffu, t.y);
            s0 = __uint_as_float(t.z); s1 = __uint_as_float(t.w);
#pragma unroll
            for (int o = 16; o; o >>= 1) { s0 += __shfl_xor_sync(0xffffffffu, s0, o); s1 += __shfl_xor_sync(0xffffffffu, s1, o); }
            if (lane == 0) {
                *(uint4*)g_ctl.stat[X][id] = make_uint4(mx0, mx1, __float_as_uint(s0), __float_as_uint(s1));
                fence_release();
                red_add(&g_ctl.stat_cnt[X], 1);
            }
        }
    }
    float* scs = (float*)(smem + S_MISC);
    if (w == 0) {
        __syncwarp();
        float sc[4]; bool bad;
        get_scales(p, X, sc, bad);
        if (bad) { st_relaxed(&g_ctl.bad, 1); sc[0] = sc[1] = sc[2] = sc[3] = 0.f; }
        int it = 0; uint32_t pb;
        while (!((pb = ld_relaxed(&g_ctl.pagebits)) >> 31)) backoff(it);
        ((uint32_t*)(smem + S_AUX))[lane] = 0;
        if (lane == 0) { scs[0] = sc[0]; scs[1] = sc[1]; scs[2] = sc[2]; scs[3] = sc[3]; ((uint32_t*)scs)[4] = X ? ~pb : pb; }
    }
    __syncthreads();
    const uint32_t NT = p.NS + 2 * GR;
    if (w > MW) return;
    if (w == MW) {
        int left = NT * (NP / GR), it = 0;
        while (left > 0) {
            uint32_t b;
            asm volatile("ld.acquire.cta.shared.u32 %0, [%1];" : "=r"(b) : "r"(SB + S_AUX + lane * 4) : "memory");
            uint32_t mask = __ballot_sync(0xffffffffu, b != 0);
            if (mask == 0) { __nanosleep(40); if (++it > SPIN_MAX * 4) __trap(); continue; }
            if (b != 0) asm volatile("st.relaxed.cta.shared.u32 [%0], %1;" ::"r"(SB + S_AUX + lane * 4), "r"(0) : "memory");
            fence_release();
            if (b != 0) red_add(ring + b, 1);
            left -= __popc(mask);
            if (PUBSLEEP_ > 0) __nanosleep(PUBSLEEP_);
        }
        return;
    }
    const uint32_t pagebits = ((uint32_t*)scs)[4];
    const int half = lane >> 4, k4 = (lane & 15) * 4, k8 = k4 & ~7;
    const float s_lo = scs[2 * ty], s_hi = scs[2 * ty + 1];
    const float MAG_LO = 12582912.f, MAG_HI = 12582912.f - 19264.f;
    const int il = ib / NG, gi = (ib % NG) * 2 + X;
    const uint32_t a_off = R_A + il * R_UNIT + lane * 16, v_off = ty * R_V1 + il * R_UNIT + lane * 16;
    const uint32_t f_off = OFF_PF + il * 32 + half * 16;
    const uint32_t j = w % (NP / GR);
    PROF_DECL
#pragma unroll 1
    for (uint32_t n = w / (NP / GR); n < NT; n += MW / (NP / GR)) {
        const uint32_t q = ((gi - n) & (GR - 1)) + GR * j, h = n >> 1;
        const uint32_t qb = q_base(q, pagebits), bb = qb ^ slot_off(h % RB);
        const uint32_t tag = (h / RB + 1) << 21;
        const uint32_t hv = h + RB - RV;
        const unsigned char* prel = ring + (qb ^ slot_off(hv % RB) ^ OFF_REL);
        uint4 cw; int it = 0;
        while (true) {
            cw = ld_relaxed4(ring + (bb ^ f_off));
            if (__all_sync(0xffffffffu, min(min(cw.x, cw.y), cw.z) >= tag)) break;
            if (DEV_FREE) { cw.x = (cw.x & 1) + (63 | 57 << 7 | 50 << 14); cw.y = (cw.y & 1) + (53 | 61 << 7 | 57 << 14); cw.z = (cw.z & 1) + (59 | 52 << 7 | 57 << 14); break; }
            backoff(it);
        }
        PROF(0);
        const unsigned char* pa = ring + (qb ^ slot_off(h % RA) ^ a_off);
        unsigned char* pv = ring + (qb ^ slot_off(h % RV) ^ v_off);
        uint32_t rel = ld_relaxed(prel);
        uint4 a[9];
#pragma unroll
        for (int ps = 0; ps < MPF; ps++) ldg4_lt(a[ps], pa + ps * 512 + (ps < 4 ? 0 : R_HI), k4, ((ps < 3 ? cw.x : ps < 6 ? cw.y : cw.z) >> (7 * (ps % 3))) & 0x7f);
        while (rel < NCP * (hv / RB)) { if (DEV_FREE) break; backoff(it); rel = ld_relaxed(prel); }
        PROF(3);
#pragma unroll
        for (int ps = 0; ps < 9; ps++) {
            const int cnt = ((ps < 3 ? cw.x : ps < 6 ? cw.y : cw.z) >> (7 * (ps % 3))) & 0x7f, rem = cnt - k4;
            uint32_t aw[4] = {a[ps].x, a[ps].y, a[ps].z, a[ps].w}, mv[4], vw[4];
#pragma unroll
            for (int e = 0; e < 4; e++) { mv[e] = 0; lds_lt(mv[e], __dp2a_lo(aw[e], 4u, (uint32_t)SB), e, rem); }
            if (ps == 8) red_lane0(ring + (bb ^ OFF_ARL), lane);
#pragma unroll
            for (int e = 0; e < 4; e++) {
                float c = bf_hi(aw[e]);
                float lo = fmaf(bf_lo(mv[e]), c * s_lo, MAG_LO), hi = fmaf(bf_hi(mv[e]), c * s_hi, MAG_HI);
                vw[e] = (__float_as_uint(hi) << 16) + __float_as_uint(lo);
            }
            stg4_lt(pv + ps * 512 + (ps < 4 ? 0 : R_HI), vw, k8, cnt);
            if (ps + MPF < 9) ldg4_lt(a[ps + MPF], pa + (ps + MPF) * 512 + R_HI, k4, ((ps + MPF < 6 ? cw.y : cw.z) >> (7 * ((ps + MPF) % 3))) & 0x7f);
        }
        PROF(1);
        it = 0;
        while (((volatile uint32_t*)(smem + S_AUX))[w] != 0) { __nanosleep(40); if (++it > SPIN_MAX * 4) __trap(); }
        __syncwarp();
        if (lane == 0) asm volatile("st.release.cta.shared.u32 [%0], %1;" ::"r"(SB + S_AUX + w * 4), "r"(bb ^ OFF_RDY) : "memory");
        PROF(2);
    }
    PROF_END;
}

__device__ __noinline__ void c_wrap(uint32_t row, int par, uint32_t old, uint32_t w, uint32_t wrap_base) {
    uint32_t nw = old + w, ov = ~(old ^ w) & (old ^ nw);
    int d = 0;
    if (ov & 0x8000u) d += (w & 0x8000u) ? -1 : 1;
    if (ov & 0x80000000u) d += (w & 0x80000000u) ? -256 : 256;
    if (d != 0) {
        uint32_t o2;
        asm volatile("atom.shared.add.u32 %0, [%1], %2;" : "=r"(o2) : "r"(wrap_base + row * 4), "r"(d << (16 * par)) : "memory");
        if ((o2 + (d << (16 * par))) & 0x80808080u) st_relaxed(&g_ctl.bad, 1);
    }
}

__device__ __forceinline__ void c_role(const Prm& p, unsigned char* ring, int X, int c) {
    const int tid = threadIdx.x, lane = tid & 31, w = __shfl_sync(0xffffffffu, tid >> 5, 0);
    const uint32_t wrap_off = C_WRAP;
    load_wts(p, (Wts*)(smem + S_AUX));
    for (int k = tid; k < C_TAB / 16; k += THREADS) { uint32_t z = k < C_WRAP / 16 ? 0u : 0x40404040u; ((uint4*)smem)[k] = make_uint4(z, z, z, z); }
    __syncthreads();
    for (int k = tid; k < TAB_N; k += THREADS) ((uint4*)(smem + C_TAB))[k] = radial_bf16((const Wts*)(smem + S_AUX), TAB_LO + k);
    if (w == NW - 1) {
        float sc[4]; bool bad;
        if (!DEV_FREE) get_scales(p, X, sc, bad);
        if (lane < 16) { float s = lane < 4 ? sc[0] : lane < 8 ? sc[1] : lane < 12 ? sc[2] : sc[3]; ((Wts*)(smem + S_AUX))->wd[lane] *= s > 0.f ? 1.f / s : 0.f; }
    }
    uint32_t* misc = (uint32_t*)(smem + S_MISC);
    if (tid == 0) {
        int it = 0; uint32_t pb;
        while (!((pb = ld_relaxed(&g_ctl.pagebits)) >> 31)) backoff(it);
        misc[4] = X ? ~pb : pb;
    }
    __syncthreads();
    const uint32_t pagebits = misc[4];
    const int par = lane >> 4, k4 = __shfl_sync(0xffffffffu, (lane & 15) * 4, lane);
    const uint32_t sb = SB, acc = __shfl_sync(0xffffffffu, sb + par * 4, lane);
    const uint32_t l0 = __shfl_sync(0xffffffffu, lane == 0 ? 0xffffffffu : 0u, lane);
    if (w >= NP / 2) return;
    const uint32_t NT = p.NS + 2 * GR;
    const uint32_t qb = q_base(2 * w + X, pagebits);
    uint32_t v_off = qb ^ (par * R_V1 + (c < 8 ? 0 : R_HI) + c * 256 + k4 * 4);
    uint32_t b_off = qb ^ (R_B + c * 128 + k4 * 2);
    uint32_t f_off = qb ^ (lane == 0 ? OFF_RDY : OFF_PC + c * 4);
    const uint32_t need_inc = lane == 0 ? 2 * UN : 1u << 21;
    uint32_t need = need_inc, sv = 0, sbb = 0;
    unsigned char* pf = ring + f_off;
    uint32_t fw = 0;
    PROF_DECL
#pragma unroll 1
    for (uint32_t n = 0; n < NT; n++) {
        int it = 0;
        while (!__all_sync(0xffffffffu, fw >= need)) {
            if (DEV_FREE) { fw = (fw & 1) + (62 | 57 << 7 | 52 << 14); break; }
            backoff(it);
            fw = ld_relaxed(pf);
        }
        PROF(0);
        const uint32_t cw = __reduce_max_sync(0xffffffffu, fw);
        const unsigned char* pv = ring + (v_off ^ slot_off(sv));
        const unsigned char* pb = ring + (b_off ^ slot_off(sbb));
        uint4 v[3]; uint2 b[3]; int cnt[3];
        b[0].x = 0;
#pragma unroll
        for (int ps = 0; ps < 3; ps++) {
            cnt[ps] = (cw >> (7 * ps)) & 0x7f;
            if (ps == 0) ldg6_lt<true>(v[ps], b[ps], pv, pb, k4, cnt[ps]);
            else ldg6_lt<false>(v[ps], b[ps], pv + ps * R_UNIT, pb + ps * R_UNIT, k4, cnt[ps]);
        }
        unsigned char* rel = pf + (OFF_REL - OFF_RDY);
        v_off ^= 1u << 20; b_off ^= 1u << 20; f_off ^= 1u << 20;
        if (n & 1) {
            if (++sv == RV) sv = 0;
            if (++sbb == RB) { sbb = 0; need += need_inc; }
        }
        pf = ring + (f_off ^ slot_off(sbb));
        fw = ld_relaxed(pf);
        if (((v[0].x & v[1].x & v[2].x & b[0].x & b[1].x & b[2].x) | l0) == 0xffffffffu) red_add(rel, 1);
#pragma unroll
        for (int ps = 0; ps < 3; ps++) {
            if (k4 < cnt[ps]) {
                uint32_t vw[4] = {v[ps].x, v[ps].y, v[ps].z, v[ps].w}, old[4], ov = 0;
#pragma unroll
                for (int e = 0; e < 4; e++) {
                    uint32_t bw = e < 2 ? b[ps].x : b[ps].y;
                    asm volatile("atom.shared.add.u32 %0, [%1], %2;" : "=r"(old[e]) : "r"((e & 1) ? __dp2a_hi(bw, 0x08000008u, acc) : __dp2a_lo(bw, 0x08000008u, acc)), "r"(vw[e]) : "memory");
                }
#pragma unroll
                for (int e = 0; e < 4; e++) ov |= ~(old[e] ^ vw[e]) & (old[e] ^ (old[e] + vw[e]));
                if (ov & 0x80008000u) {
#pragma unroll
                    for (int e = 0; e < 4; e++) {
                        uint32_t bw = e < 2 ? b[ps].x : b[ps].y;
                        c_wrap((e & 1) ? bw >> 16 : bw & 0xffffu, par, old[e], vw[e], sb + wrap_off);
                    }
                }
            }
        }
        PROF(1);
    }
    PROF_END;
}

__device__ __forceinline__ void c_epilogue(const Prm& p, int X, int c) {
    const int tid = threadIdx.x;
    const Wts* wt = (const Wts*)(smem + S_AUX);
    float wd[16], wu[16];
#pragma unroll
    for (int k = 0; k < 16; k++) { wd[k] = wt->wd[k]; wu[k] = wt->wu[k]; }
    const int r0 = (X * NCP + c) * ROWS_O, nr = min((int)ROWS_O, p.E - r0);
    const uint2* mp = p.m + r0;
    const uint16_t* dp = (const uint16_t*)p.dist + r0;
    uint2* op = p.out + r0;
    constexpr int EB = 4;
#pragma unroll 1
    for (int rb = tid; rb < nr; rb += EB * THREADS) {
        uint2 mr[EB]; uint32_t db[EB];
#pragma unroll
        for (int k = 0; k < EB; k++) { int r = min(rb + k * THREADS, nr - 1); mr[k] = __ldg(mp + r); db[k] = __ldg(dp + r); }
#pragma unroll
        for (int k = 0; k < EB; k++) {
            const int r = rb + k * THREADS;
            if (r < nr) {
                const uint2 s = ((const uint2*)smem)[r];
                const uint32_t wr = ((const uint32_t*)(smem + C_WRAP))[r];
                uint4 t;
                if (db[k] - TAB_LO < TAB_N) t = ((const uint4*)(smem + C_TAB))[db[k] - TAB_LO];
                else t = radial_bf16(wt, db[k]);
                int x0 = (short)s.x, x2 = (short)s.y;
                int x1 = ((int)s.x >> 16) + ((s.x >> 15) & 1), x3 = ((int)s.y >> 16) + ((s.y >> 15) & 1);
                if (wr != 0x40404040u) {
                    int w0 = (int)(wr & 0xff) - 64, w1 = (int)((wr >> 8) & 0xff) - 64, w2 = (int)((wr >> 16) & 0xff) - 64, w3 = (int)(wr >> 24) - 64;
                    x0 += 65536 * w0; x1 += 65536 * w1 - w0; x2 += 65536 * w2; x3 += 65536 * w3 - w2;
                }
                const float a[4] = {(float)x0, (float)x1, (float)x2, (float)x3};
                const float sv[4] = {bf_lo(t.x), bf_hi(t.x), bf_lo(t.y), bf_hi(t.y)}, gv[4] = {bf_lo(t.z), bf_hi(t.z), bf_lo(t.w), bf_hi(t.w)};
                op[r] = finish_row(wd, wu, a, sv, gv, mr[k]);
            }
        }
    }
}

__device__ __forceinline__ void grid_bar(unsigned* ctr) {
    __syncthreads();
    if (threadIdx.x == 0) { fence_gpu(); red_add(ctr, 1); wait_ge(ctr, gridDim.x); fence_gpu(); }
    __syncthreads();
}
__device__ __noinline__ void fallback(const Prm& p) {
    const int gt = blockIdx.x * THREADS + threadIdx.x, gs = gridDim.x * THREADS;
    Wts* wt = (Wts*)smem;
    __syncthreads();
    load_wts(p, wt);
    for (int e = gt; e < p.E; e += gs) g_acc[e] = make_float4(0.f, 0.f, 0.f, 0.f);
    grid_bar(&g_ctl.bar[0]);
    const float f = __bfloat162float(p.freq[0]);
    for (int t = gt; t < p.T; t += gs) {
        uint2 r = __ldg(p.m + p.idx_in[t]);
        float c = rbf16(cosf(rbf16(f * __bfloat162float(p.angle[t]))));
        asm volatile("red.global.add.v4.f32 [%0], {%1,%2,%3,%4};" ::"l"(g_acc + p.idx_out[t]), "f"(bf_lo(r.x) * c),
                     "f"(bf_hi(r.x) * c), "f"(bf_lo(r.y) * c), "f"(bf_hi(r.y) * c) : "memory");
    }
    grid_bar(&g_ctl.bar[1]);
    for (int e = gt; e < p.E; e += gs) {
        float4 a4 = __ldcg(g_acc + e);
        float a[4] = {a4.x, a4.y, a4.z, a4.w}, s[4], g[4];
        radial(wt, __bfloat162float(p.dist[e]), s, g);
        p.out[e] = finish_row(wt->wd, wt->wu, a, s, g, p.m[e]);
    }
}

__global__ void __launch_bounds__(THREADS, 1) gemnet_kernel(const __grid_constant__ Prm p) {
    const int tid = threadIdx.x, lane = tid & 31, w = __shfl_sync(0xffffffffu, tid >> 5, 0);
    uint32_t* misc = (uint32_t*)(smem + S_MISC);
    bool run_fallback = true;
    if (!p.force_bad && __cvta_generic_to_shared(smem) == SB) {
        unsigned char* const ring = p.ring;
        uint32_t smid; asm("mov.u32 %0, %%smid;" : "=r"(smid));
        const int cls = smid < NM ? 0 : (smid < NM + NP - 4 || (smid >= 124 && smid < 128)) ? 2 : 1;
        if (tid == 0) {
            uint32_t side = 0;
            if (cls != 2) side = probe_pair(ring + OFF_PROBE + ((blockIdx.x >> 7) << 20) + (blockIdx.x & 127) * 32);
            int pool = cls == 2 ? 4 : cls * 2 + side, id = 0;
            for (int k = 0; k < 7; k++) {
                int cap = pool < 2 ? NMP : pool < 4 ? NCP : NP;
                id = atomicAdd(&g_ctl.ticket[pool], 1);
                if (id < cap) break;
                pool = k == 0 ? (pool == 4 ? 0 : pool ^ 1) : k - 1;
            }
            misc[8] = pool; misc[9] = id;
        }
        if (blockIdx.x == 0 && w >= 1 && w <= NPAGES) {
            if (lane == 0) misc[16 + w] = probe_pair(ring + ((size_t)(w - 1) << 21) + (1 << 20) + OFF_PROBE + 2048);
            asm volatile("bar.sync 1, %0;" ::"r"(NPAGES * 32) : "memory");
            if (tid == 32) {
                uint32_t pb = 0x80000000u;
                for (int k = 0; k < NPAGES; k++) pb |= (misc[17 + k] ^ misc[17]) << k;
                st_relaxed(&g_ctl.pagebits, pb);
            }
        }
        __syncthreads();
        const int pool = misc[8], id = misc[9];
        __syncthreads();
        if (DEV_FREE && !(DEV_FREE & (pool == 4 ? 1 : pool < 2 ? 2 : 4))) {
        } else if (pool == 4) {
            for (int k = tid; k < S_MISC / 16; k += THREADS) ((uint4*)smem)[k] = make_uint4(0, 0, 0, 0);
            __syncthreads();
            if (tid < 2 * NBUF) {
                const uint32_t a = __cvta_generic_to_shared(smem + P_BAR) + tid * 8, cnt = tid < NBUF ? CPS : 1;
                mbar_init(a, cnt);
                if (tid % NBUF < id % GR) asm volatile("mbarrier.arrive.shared.b64 _, [%0], %1;" ::"r"(a), "r"(cnt) : "memory");
            }
            __syncthreads();
            if (w < CPS) p_filler(p, id, w);
            else if (w < CPS + NF) {
                int it = 0; uint32_t pb;
                while (!((pb = ld_relaxed(&g_ctl.pagebits)) >> 31)) backoff(it);
                p_flusher(p, ring, __shfl_sync(0xffffffffu, pb, 0), id, w - CPS);
            }
        } else if (pool < 2) {
            m_role(p, ring, pool, id);
        } else {
            c_role(p, ring, pool - 2, id);
        }
        __syncthreads();
        if (tid == 0) { fence_gpu(); red_add(&g_ctl.fin, 1); }
        if ((pool == 2 || pool == 3) && !DEV_FREE) c_epilogue(p, pool - 2, id);
        if (tid == 0) { wait_ge(&g_ctl.fin, NCTA); fence_gpu(); misc[10] = ld_relaxed(&g_ctl.bad); }
        __syncthreads();
        run_fallback = misc[10] && !DEV_FREE;
    }
    if (run_fallback) fallback(p);
    if (tid == 0) {
        fence_gpu();
        if (atomicAdd(&g_ctl.exited, 1) == gridDim.x - 1) {
            uint32_t* c = (uint32_t*)&g_ctl;
            for (int k = 0; k < 32; k++) c[k] = 0;
        }
    }
}

cudaTextureObject_t make_tex(const void* ptr, size_t bytes, int words) {
    cudaResourceDesc rd = {};
    rd.resType = cudaResourceTypeLinear;
    rd.res.linear.devPtr = (void*)ptr;
    rd.res.linear.desc = words == 4 ? cudaCreateChannelDesc<uint4>() : cudaCreateChannelDesc<uint2>();
    rd.res.linear.sizeInBytes = bytes;
    cudaTextureDesc td = {};
    td.readMode = cudaReadModeElementType;
    cudaTextureObject_t t = 0;
    if (cudaCreateTextureObject(&t, &rd, &td, nullptr) != cudaSuccess) { cudaGetLastError(); return 0; }
    return t;
}

}

extern "C" void kernel_launch(void* const* d_in, const int* in_sizes, int n_in, void* d_out, int out_size) {
    static Prm p = {};
    static int grid = 0;
    const int E = in_sizes[3], T = in_sizes[1];
    if (grid == 0 || p.idx_in != d_in[1] || p.idx_out != d_in[2] || p.angle != d_in[4] || p.E != E || p.T != T) {
        int dev = 0, sms = 0;
        cudaGetDevice(&dev);
        cudaDeviceGetAttribute(&sms, cudaDevAttrMultiProcessorCount, dev);
        cudaFuncSetAttribute(gemnet_kernel, cudaFuncAttributeMaxDynamicSharedMemorySize, SMEM_BYTES);
        p.E = E; p.T = T;
        p.NS = (T / 128 + NP * CPS - 1) / (NP * CPS);
        void* rp = nullptr;
        cudaGetSymbolAddress(&rp, g_ring);
        p.ring = (unsigned char*)(((uintptr_t)rp + ((2u << 20) - 1)) & ~(uintptr_t)((2u << 20) - 1));
        bool fast = sms >= NCTA && E <= (int)FAST_E && (E & 1) == 0 && T >= 128 && T <= (1 << 29);
        if (fast) {
            p.t_in = make_tex(d_in[1], (size_t)(T / 128) * 512, 4);
            p.t_out = make_tex(d_in[2], (size_t)(T / 128) * 512, 4);
            p.t_ang = make_tex(d_in[4], (size_t)(T / 128) * 256, 2);
            fast = p.t_in && p.t_out && p.t_ang;
        }
        p.force_bad = !fast;
        grid = fast ? NCTA : sms;
    }
    p.m = (const uint2*)d_in[0];
    p.idx_in = (const int*)d_in[1];
    p.idx_out = (const int*)d_in[2];
    p.dist = (const __nv_bfloat16*)d_in[3];
    p.angle = (const __nv_bfloat16*)d_in[4];
    p.centers = (const __nv_bfloat16*)d_in[5];
    p.freq = (const __nv_bfloat16*)d_in[6];
    p.w_rbf = (const __nv_bfloat16*)d_in[7];
    p.w_sbf = (const __nv_bfloat16*)d_in[8];
    p.w_down = (const __nv_bfloat16*)d_in[9];
    p.w_up = (const __nv_bfloat16*)d_in[10];
    p.out = (uint2*)d_out;
    gemnet_kernel<<<grid, THREADS, SMEM_BYTES>>>(p);
}
```

```cpp
#include <cuda_runtime.h>
#include <cuda_bf16.h>
#include <stdint.h>

namespace {

constexpr int NI = 12;
constexpr int UN = 3;
constexpr int NG = NI / UN;
constexpr int GR = 2 * NG;
constexpr int NCP = 18;
constexpr int NO = 2 * NCP;
constexpr int KS = 64;
constexpr int NB = UN * NCP;
constexpr int NBUF = 10;
constexpr int NMP = 2 * NI;
constexpr int NP = 48, NM = 2 * NMP, NC = NO, NCTA = NP + NM + NC;
#define CPS_ 24
constexpr int CPS = CPS_;
constexpr int NF = 4;
#define RA_ 3
#define RV_ 3
#define RB_ 6
constexpr int RA = RA_, RV = RV_, RB = RB_;
constexpr int QN = 80, QTRIG = 40;
#define MW_ 18
constexpr int MW = MW_;
#define MPF_ 6
constexpr int MPF = MPF_;
constexpr int THREADS = 896, NW = THREADS / 32;
#define DEV_FREE 0
#define P_SULD 0
#ifndef M_SULD
#define M_SULD 0
#endif
#define C_SULD 0
#define SLEEP_ 200

constexpr int RING_BYTES = NP << 20;
constexpr int NPAGES = RING_BYTES >> 21;
constexpr int MAX_E = 1 << 20;
constexpr int SMEM_BYTES = 232448;

constexpr int SB = 1024;

constexpr int P_CNT = 0;
constexpr int P_BAR = P_CNT + NBUF * NB * 4;
constexpr int P_B = (P_BAR + 2 * NBUF * 8 + 127) / 128 * 128;
constexpr int P_Q = P_B + NBUF * NB * KS * 2;
constexpr int P_A = SMEM_BYTES - 256 - NBUF * NB * KS * 4;
static_assert(P_Q + CPS * QN * 8 + 512 <= P_A && P_A % 128 == 0, "P smem");
constexpr int S_MISC = SMEM_BYTES - 256;
constexpr int S_AUX = S_MISC - 512;

constexpr unsigned FAST_E = 640000;
constexpr unsigned magic_of(unsigned long long d) { return (unsigned)(((1ull << 32) + d - 1) / d); }
constexpr bool magic_ok(unsigned long long d) { return (magic_of(d) * d - (1ull << 32)) * FAST_E < (1ull << 32); }
constexpr unsigned pick_rows(unsigned lo) {
    unsigned d = (lo + 3) & ~3u;
    while (!magic_ok(d)) d += 4;
    return d;
}
constexpr unsigned ROWS_I = pick_rows((FAST_E + NI - 1) / NI), ROWS_O = pick_rows((FAST_E + NO - 1) / NO);
constexpr unsigned MAG_I = magic_of(ROWS_I), MAG_O = magic_of(ROWS_O), HALF_O = ROWS_O * NCP;
constexpr int C_WRAP = ROWS_O * 8, C_TAB = ROWS_O * 12, TAB_N = 1025, TAB_LO = 0x3f80 - 1024;
static_assert(ROWS_I * 4 <= S_AUX && C_TAB + TAB_N * 16 <= S_AUX && ROWS_I <= 65536 && ROWS_O <= 32768, "tables");

struct __align__(128) Ctl {
    unsigned ticket[5];
    unsigned pagebits;
    unsigned stat_cnt[2];
    unsigned bad;
    unsigned fin;
    unsigned bar[3];
    unsigned exited;
    unsigned pad[18];
    float stat[2][NMP][4];
};

struct Prm {
    const uint2* m; const int* idx_in; const int* idx_out; const __nv_bfloat16* dist; const __nv_bfloat16* angle;
    const __nv_bfloat16* centers; const __nv_bfloat16* freq; const __nv_bfloat16* w_rbf; const __nv_bfloat16* w_sbf;
    const __nv_bfloat16* w_down; const __nv_bfloat16* w_up; uint2* out;
    cudaTextureObject_t t_in, t_out, t_ang;
    cudaTextureObject_t s_in, s_out, s_ring;
    int E, T;
    unsigned char* ring;
    int NS;
    int force_bad;
};

__device__ __align__(128) unsigned char g_ring[RING_BYTES + (2 << 20)];
__device__ Ctl g_ctl;
__device__ float4 g_acc[MAX_E];
#define PROF_DECL
#define PROF(k)
#define PROF_END

extern __shared__ __align__(128) unsigned char smem[];

__device__ __forceinline__ float bf_lo(uint32_t w) { return __uint_as_float(w << 16); }
__device__ __forceinline__ float bf_hi(uint32_t w) { return __uint_as_float(w & 0xffff0000u); }
__device__ __forceinline__ float rbf16(float x) { return __bfloat162float(__float2bfloat16_rn(x)); }
__device__ __forceinline__ uint32_t pack_bf16(float hi, float lo) {
    uint32_t r; asm("cvt.rn.bf16x2.f32 %0, %1, %2;" : "=r"(r) : "f"(hi), "f"(lo)); return r;
}
__device__ __forceinline__ uint32_t prmt(uint32_t a, uint32_t b, uint32_t c) {
    uint32_t r; asm("prmt.b32 %0, %1, %2, %3;" : "=r"(r) : "r"(a), "r"(b), "r"(c)); return r;
}
__device__ __forceinline__ uint32_t ld_relaxed(const void* p) {
    uint32_t v; asm volatile("ld.relaxed.gpu.global.u32 %0, [%1];" : "=r"(v) : "l"(p) : "memory"); return v;
}
__device__ __forceinline__ uint2 ld_relaxed2(const void* p) {
    uint2 v; asm volatile("ld.relaxed.gpu.global.v2.u32 {%0,%1}, [%2];" : "=r"(v.x), "=r"(v.y) : "l"(p) : "memory"); return v;
}
__device__ __forceinline__ uint4 ld_relaxed4(const void* p) {
    uint4 v; asm volatile("ld.relaxed.gpu.global.v4.u32 {%0,%1,%2,%3}, [%4];" : "=r"(v.x), "=r"(v.y), "=r"(v.z), "=r"(v.w) : "l"(p) : "memory"); return v;
}
__device__ __forceinline__ void st_relaxed(void* p, uint32_t v) { asm volatile("st.relaxed.gpu.global.u32 [%0], %1;" ::"l"(p), "r"(v) : "memory"); }
__device__ __forceinline__ void st_relaxed16(void* p, uint32_t v) { asm volatile("st.relaxed.gpu.global.u16 [%0], %1;" ::"l"(p), "h"((uint16_t)v) : "memory"); }
__device__ __forceinline__ void red_add(void* p, uint32_t v) { asm volatile("red.relaxed.gpu.global.add.u32 [%0], %1;" ::"l"(p), "r"(v) : "memory"); }
__device__ __forceinline__ void fence_gpu() { asm volatile("fence.acq_rel.gpu;" ::: "memory"); }
__device__ __forceinline__ void fence_release() { asm volatile("fence.release.gpu;" ::: "memory"); }
__device__ __forceinline__ void mbar_init(uint32_t a, uint32_t n) { asm volatile("mbarrier.init.shared.b64 [%0], %1;" ::"r"(a), "r"(n) : "memory"); }
__device__ __forceinline__ void mbar_arrive(uint32_t a) { asm volatile("mbarrier.arrive.shared.b64 _, [%0];" ::"r"(a) : "memory"); }
__device__ __forceinline__ bool mbar_try(uint32_t a, uint32_t ph) {
    uint32_t ok;
    asm volatile("{.reg .pred p; mbarrier.try_wait.parity.shared.b64 p, [%1], %2, %3; selp.u32 %0, 1, 0, p;}" : "=r"(ok) : "r"(a), "r"(ph), "r"(2000) : "memory");
    return ok;
}
constexpr int SPIN_MAX = 1 << 22;
__device__ __forceinline__ void mbar_wait(uint32_t a, uint32_t ph) {
    int it = 0;
    while (!mbar_try(a, ph)) { if (++it > SPIN_MAX) __trap(); }
}
__device__ __forceinline__ void backoff(int& it) { __nanosleep(SLEEP_); if (++it > SPIN_MAX) __trap(); }
__device__ __forceinline__ void wait_ge(const void* p, uint32_t v) {
    int it = 0;
    while (ld_relaxed(p) < v) backoff(it);
}

__device__ __forceinline__ bool elect_one() {
    uint32_t r; asm volatile("{.reg .pred p; elect.sync _|p, 0xffffffff; selp.u32 %0, 1, 0, p;}" : "=r"(r)); return r;
}
__device__ __forceinline__ void st_lane0(void* p, uint32_t v, int lane) {
    asm volatile("{.reg .pred p; setp.eq.s32 p, %2, 0; @p st.relaxed.gpu.global.u32 [%0], %1;}" ::"l"(p), "r"(v), "r"(lane) : "memory");
}
__device__ __forceinline__ void wait_all_ge(const void* p, uint32_t v) {
    int it = 0;
    while (!__all_sync(0xffffffffu, ld_relaxed(p) >= v)) backoff(it);
}
__device__ __forceinline__ void suld4(uint4& v, unsigned long long h, uint32_t off) {
    asm volatile("suld.b.1d.cg.v4.b32.zero {%0,%1,%2,%3}, [%4, {%5}];" : "=r"(v.x), "=r"(v.y), "=r"(v.z), "=r"(v.w) : "l"(h), "r"(off) : "memory");
}
__device__ __forceinline__ void lds_lt(uint32_t& v, uint32_t ad, int a, int b) {
    asm volatile("{.reg .pred p; setp.lt.s32 p, %2, %3; @p ld.shared.u32 %0, [%1];}" : "+r"(v) : "r"(ad), "r"(a), "r"(b));
}

constexpr uint32_t R_V1 = 0x03000, R_A = 0x81000, R_B = 0x82000, R_UNIT = 0x4000, R_HI = 0x40000 - 8 * 256;
__device__ __forceinline__ uint32_t q_base(uint32_t q, uint32_t pagebits_x) { return (q << 20) | (((pagebits_x >> (q >> 1)) & 1u) << 12); }
__device__ __forceinline__ uint32_t slot_off(uint32_t s) { return (s << 16) | (((s + 1) & 2) << 11); }
constexpr uint32_t OFF_PF = R_B + 3 * R_UNIT, OFF_RDY = OFF_PF + 128, OFF_REL = OFF_PF + 256;
constexpr uint32_t OFF_PROBE = 3 * R_UNIT;
static_assert(RA <= 4 && RV <= 4 && RB <= 8 && RA <= RB && RV <= RB, "ring");

__device__ __forceinline__ uint32_t probe(unsigned char* p) {
    volatile uint32_t* sink = (volatile uint32_t*)(smem + S_MISC + 240);
    uint32_t best = 0xffffffffu;
#pragma unroll 1
    for (int r = 0; r < 3; r++) {
        uint32_t t0, t1, v;
        asm volatile("mov.u32 %0, %%clock;" : "=r"(t0)::"memory");
        asm volatile("atom.relaxed.gpu.global.add.u32 %0, [%1], 1;" : "=r"(v) : "l"(p) : "memory");
        *sink = v;
        asm volatile("mov.u32 %0, %%clock;" : "=r"(t1)::"memory");
        best = min(best, t1 - t0);
    }
    return best;
}
__device__ __forceinline__ uint32_t probe_pair(unsigned char* p) {
    asm volatile("st.global.v4.u32 [%0], {%1,%1,%1,%1};" ::"l"(p), "r"(0) : "memory");
    asm volatile("st.global.v4.u32 [%0], {%1,%1,%1,%1};" ::"l"(p + 16), "r"(0) : "memory");
    asm volatile("st.global.v4.u32 [%0], {%1,%1,%1,%1};" ::"l"(p + 4096), "r"(0) : "memory");
    asm volatile("st.global.v4.u32 [%0], {%1,%1,%1,%1};" ::"l"(p + 4112), "r"(0) : "memory");
    uint32_t a = probe(p), b = probe(p + 4096);
    return a > b;
}

struct Wts { float c[8], wr[32], ws[32], wd[16], wu[16]; };
__device__ __forceinline__ void load_wts(const Prm& p, Wts* w) {
    int t = threadIdx.x;
    if (t < 8) w->c[t] = __bfloat162float(p.centers[t]);
    if (t < 32) { w->wr[t] = __bfloat162float(p.w_rbf[t]); w->ws[t] = __bfloat162float(p.w_sbf[t]); }
    if (t < 16) { w->wd[t] = __bfloat162float(p.w_down[t]); w->wu[t] = __bfloat162float(p.w_up[t]); }
}
__device__ __forceinline__ void radial(const Wts* w, float d, float s[4], float g[4]) {
#pragma unroll
    for (int j = 0; j < 4; j++) s[j] = g[j] = 0.f;
#pragma unroll
    for (int r = 0; r < 8; r++) {
        float x = rbf16(d - w->c[r]);
        float b = rbf16(__expf(rbf16(-10.0f * rbf16(x * x))));
#pragma unroll
        for (int j = 0; j < 4; j++) { s[j] += b * w->ws[r * 4 + j]; g[j] += b * w->wr[r * 4 + j]; }
    }
}
__device__ __noinline__ uint4 radial_bf16(const Wts* w, uint32_t dbits) {
    float s[4], g[4];
    radial(w, __uint_as_float(dbits << 16), s, g);
    return make_uint4(pack_bf16(s[1], s[0]), pack_bf16(s[3], s[2]), pack_bf16(g[1], g[0]), pack_bf16(g[3], g[2]));
}
__device__ __forceinline__ uint2 finish_row(const float* wd, const float* wu, const float a[4], const float s[4], const float g[4], uint2 r) {
    float agg[4], o[4];
#pragma unroll
    for (int j = 0; j < 4; j++) agg[j] = s[j] * (a[0] * wd[j] + a[1] * wd[4 + j] + a[2] * wd[8 + j] + a[3] * wd[12 + j]);
    const float mm[4] = {bf_lo(r.x), bf_hi(r.x), bf_lo(r.y), bf_hi(r.y)};
#pragma unroll
    for (int j = 0; j < 4; j++) o[j] = mm[j] + (agg[0] * wu[j] + agg[1] * wu[4 + j] + agg[2] * wu[8 + j] + agg[3] * wu[12 + j]) * g[j];
    return make_uint2(pack_bf16(o[1], o[0]), pack_bf16(o[3], o[2]));
}

__device__ __forceinline__ void get_scales(const Prm& p, int side, float sc[4], bool& bad) {
    const int lane = threadIdx.x & 31;
    wait_ge(&g_ctl.stat_cnt[side], NMP);
    fence_gpu();
    uint4 a = make_uint4(0, 0, 0, 0), b = a;
    if (lane < NI) { a = ld_relaxed4(&g_ctl.stat[side][2 * lane][0]); b = ld_relaxed4(&g_ctl.stat[side][2 * lane + 1][0]); }
    uint32_t mxb[4] = {a.x, a.y, b.x, b.y};
    float ss[4] = {__uint_as_float(a.z), __uint_as_float(a.w), __uint_as_float(b.z), __uint_as_float(b.w)};
    bad = false;
    const float kdeg = fminf(3.5f * sqrtf(fmaxf(0.5f * (float)p.T / (float)p.E, 1.0f)), 128.f);
#pragma unroll
    for (int ch = 0; ch < 4; ch++) {
        float mx = __uint_as_float(__reduce_max_sync(0xffffffffu, mxb[ch]));
#pragma unroll
        for (int o = 16; o; o >>= 1) ss[ch] += __shfl_xor_sync(0xffffffffu, ss[ch], o);
        float rms = sqrtf(ss[ch] / (float)p.E);
        float range = fmaxf(4.002f * mx, kdeg * rms);
        if (!(mx <= 1e15f) || !(range <= 128.f * rms) || (mx > 0.f && mx < 1e-15f)) bad = true;
        sc[ch] = range > 0.f ? 32767.f / range : 0.f;
    }
}

constexpr int PER = 40;
struct __align__(16) PTab { uint32_t e[PER][4]; };
constexpr PTab make_ptab() {
    PTab t = {};
    for (int s = 0; s < PER; s++) {
        for (int d = 0; d < GR; d++) {
            int gi = (s + d) % GR, buf = (s + d) % NBUF, X = gi & 1, g = gi >> 1;
            t.e[s][X] |= (uint32_t)(4 * UN * buf - g - 4 * X + 7) << (8 * g);
        }
        int mnew = s + GR - 1;
        t.e[s][2] = (uint32_t)(SB + P_BAR + (NBUF + mnew % NBUF) * 8) | (uint32_t)(((mnew / NBUF) & 1) ^ 1) << 31;
        t.e[s][3] = (uint32_t)(SB + P_BAR + (s % NBUF) * 8) | (uint32_t)((s + 1) % PER) << 16;
    }
    return t;
}
__constant__ PTab c_ptab = make_ptab();
constexpr int BIAS = 7 * NCP;
static_assert(NG == 4, "group selection");

struct PCtx { uint32_t a0, a1; };
struct PElem { uint32_t b4, aw, ol, r2; };

__device__ __forceinline__ void p_bin(const PCtx& c, PElem& e, uint32_t i, uint32_t o, uint32_t cw, uint32_t csel) {
    uint32_t ib = __umulhi(i, MAG_I), ob = __umulhi(o, MAG_O), sel = ib & 3;
    asm("{.reg .pred p; setp.ge.u32 p, %1, %2; @p add.u32 %0, %0, 4;}" : "+r"(sel) : "r"(o), "n"(HALF_O));
    e.b4 = __dp4a(prmt(c.a0, c.a1, sel), (uint32_t)NCP, ib * NCP + ob * 4);
    e.aw = prmt(i - ib * ROWS_I, cw, csel);
    e.ol = o - ob * ROWS_O;
}
__device__ __forceinline__ void p_rank(PElem& e) {
    asm volatile("atom.shared.add.u32 %0, [%1+%2], 2;" : "=r"(e.r2) : "r"(e.b4), "n"(SB + P_CNT - BIAS) : "memory");
}
__device__ __forceinline__ void p_store(const PElem& e) {
    const uint32_t ab = e.b4 * (KS / 2) + e.r2;
    asm volatile("{.reg .pred p; setp.lt.u32 p, %4, %5; @p st.shared.u32 [%0+%6], %1; @p st.shared.u16 [%2+%7], %3;}"
                 ::"r"(ab * 2), "r"(e.aw), "r"(ab), "h"((uint16_t)e.ol), "r"(e.r2), "n"(KS * 2),
                   "n"(SB + P_A - BIAS * KS), "n"(SB + P_B - BIAS * (KS / 2)) : "memory");
}
__device__ __noinline__ uint32_t cos2_slow(uint32_t x) {
    float a = cosf(bf_lo(x)), b = cosf(bf_hi(x));
    if (!(fabsf(a + b) <= 2.f)) { st_relaxed(&g_ctl.bad, 1); a = b = 0.f; }
    return pack_bf16(b, a);
}

struct PIn { uint4 i, o; uint2 a; };
__device__ __forceinline__ void p_fetch(const Prm& p, PIn& x, uint32_t ch, uint32_t lane) {
    const int v = ch * 32 + lane;
    asm volatile("{.reg .b32 d0, d1; tex.1d.v4.u32.s32 {%0,%1,d0,d1}, [%2, {%3}];}" : "=r"(x.a.x), "=r"(x.a.y) : "l"(p.t_ang), "r"(v));
    if (P_SULD) {
        const uint32_t win = min(ch, (uint32_t)(p.T >> 7) - 1) >> 12, off = (v & 0x1ffff) * 16;
        asm volatile("suld.b.1d.cs.v4.b32.zero {%0,%1,%2,%3}, [%4, {%5}];" : "=r"(x.i.x), "=r"(x.i.y), "=r"(x.i.z), "=r"(x.i.w) : "l"(p.s_in + win), "r"(off));
        asm volatile("suld.b.1d.cs.v4.b32.zero {%0,%1,%2,%3}, [%4, {%5}];" : "=r"(x.o.x), "=r"(x.o.y), "=r"(x.o.z), "=r"(x.o.w) : "l"(p.s_out + win), "r"(off));
    } else {
        asm volatile("tex.1d.v4.u32.s32 {%0,%1,%2,%3}, [%4, {%5}];" : "=r"(x.i.x), "=r"(x.i.y), "=r"(x.i.z), "=r"(x.i.w) : "l"(p.t_in), "r"(v));
        asm volatile("tex.1d.v4.u32.s32 {%0,%1,%2,%3}, [%4, {%5}];" : "=r"(x.o.x), "=r"(x.o.y), "=r"(x.o.z), "=r"(x.o.w) : "l"(p.t_out), "r"(v));
    }
}

struct PFill {
    PCtx c;
    uint32_t qb, qt, lt, f2, nxt;
    __device__ __forceinline__ void begin() {
        const uint2* t = (const uint2*)c_ptab.e + 2 * (nxt >> 16);
        const uint2 m = t[0], s = t[1];
        c.a0 = m.x; c.a1 = m.y;
        nxt = s.y;
        mbar_wait(s.x & 0xffff, s.x >> 31);
    }
    __device__ __forceinline__ void end() {
        __syncwarp();
        asm volatile("{.reg .pred p; setp.eq.u32 p, %1, 0; @p mbarrier.arrive.shared.b64 _, [%0];}" ::"r"(nxt & 0xffff), "r"(lt) : "memory");
    }
    __device__ __forceinline__ void push(bool f, uint32_t x, uint32_t y) {
        uint32_t mask = __ballot_sync(0xffffffffu, f);
        asm volatile("{.reg .pred p; setp.ne.u32 p, %3, 0; @p st.shared.v2.u32 [%0], {%1,%2};}" ::"r"(qt + __popc(mask & lt) * 8), "r"(x), "r"(y), "r"((uint32_t)f) : "memory");
        qt += __popc(mask) * 8;
    }
    __device__ __forceinline__ void push_checked(bool f, uint32_t i, uint32_t o, uint32_t aw) {
        if (qt - qb + __popc(__ballot_sync(0xffffffffu, f)) * 8 > QN * 8) st_relaxed(&g_ctl.bad, 1);
        else push(f, prmt(i, aw, 0x6210), prmt(o, aw, 0x7210));
    }
    __device__ __forceinline__ void chunk(const PIn& x) {
        uint32_t x0, x1, c0, c1;
        asm("mul.rn.bf16x2 %0, %1, %2;" : "=r"(x0) : "r"(x.a.x), "r"(f2));
        asm("mul.rn.bf16x2 %0, %1, %2;" : "=r"(x1) : "r"(x.a.y), "r"(f2));
        c0 = pack_bf16(__cosf(bf_hi(x0)), __cosf(bf_lo(x0)));
        c1 = pack_bf16(__cosf(bf_hi(x1)), __cosf(bf_lo(x1)));
        if (__any_sync(0xffffffffu, (((x0 & 0x7fff7fffu) + 0x3e003e00u) | ((x1 & 0x7fff7fffu) + 0x3e003e00u)) & 0x80008000u)) { c0 = cos2_slow(x0); c1 = cos2_slow(x1); }
        PElem e0, e1, e2, e3;
        p_bin(c, e0, x.i.x, x.o.x, c0, 0x5410); p_rank(e0);
        p_bin(c, e1, x.i.y, x.o.y, c0, 0x7610); p_rank(e1);
        p_bin(c, e2, x.i.z, x.o.z, c1, 0x5410); p_rank(e2);
        p_bin(c, e3, x.i.w, x.o.w, c1, 0x7610); p_rank(e3);
        p_store(e0); p_store(e1); p_store(e2); p_store(e3);
        const uint32_t r01 = e0.r2 | e1.r2, r23 = e2.r2 | e3.r2;
        const bool f = (r01 | r23) >= KS * 2;
        if (__any_sync(0xffffffffu, f)) {
            const bool f0 = e0.r2 >= KS * 2, f1 = e1.r2 >= KS * 2, f2_ = e2.r2 >= KS * 2, f3 = e3.r2 >= KS * 2, f01 = r01 >= KS * 2;
            uint32_t si = f01 ? (f0 ? x.i.x : x.i.y) : (f2_ ? x.i.z : x.i.w);
            uint32_t so = f01 ? (f0 ? x.o.x : x.o.y) : (f2_ ? x.o.z : x.o.w);
            uint32_t sc = f01 ? (f0 ? e0.aw : e1.aw) : (f2_ ? e2.aw : e3.aw);
            push(f, prmt(si, sc, 0x6210), prmt(so, sc, 0x7210));
            uint32_t s2 = max(max(min(e0.r2, e1.r2), min(e2.r2, e3.r2)), min(r01, r23));
            if (__any_sync(0xffffffffu, s2 >= KS * 2)) {
                push_checked(f1 && f0, x.i.y, x.o.y, e1.aw);
                push_checked(f2_ && f01, x.i.z, x.o.z, e2.aw);
                push_checked(f3 && (f01 || f2_), x.i.w, x.o.w, e3.aw);
            }
            if (qt - qb >= QTRIG * 8) {
                retry(32);
                if (qt - qb > (QN - 32) * 8) { st_relaxed(&g_ctl.bad, 1); qt = qb; }
            }
        }
    }
    __device__ __forceinline__ void retry(uint32_t take) {
        const uint32_t lane8 = (threadIdx.x & 31) * 8;
        uint2 e, r0, r1;
        __syncwarp();
        asm volatile("ld.shared.v2.u32 {%0,%1}, [%2];" : "=r"(e.x), "=r"(e.y) : "r"(qb + lane8) : "memory");
        asm volatile("ld.shared.v2.u32 {%0,%1}, [%2];" : "=r"(r0.x), "=r"(r0.y) : "r"(qb + lane8 + take * 8) : "memory");
        qt -= take * 8;
        const bool more = qt - qb > 256;
        if (more) asm volatile("ld.shared.v2.u32 {%0,%1}, [%2];" : "=r"(r1.x), "=r"(r1.y) : "r"(qb + lane8 + take * 8 + 256) : "memory");
        __syncwarp();
        if (qb + lane8 < qt) asm volatile("st.shared.v2.u32 [%0], {%1,%2};" ::"r"(qb + lane8), "r"(r0.x), "r"(r0.y) : "memory");
        if (more && qb + lane8 + 256 < qt) asm volatile("st.shared.v2.u32 [%0], {%1,%2};" ::"r"(qb + lane8 + 256), "r"(r1.x), "r"(r1.y) : "memory");
        PElem el;
        el.r2 = 0;
        if (lane8 < take * 8) {
            p_bin(c, el, e.x & 0xffffffu, e.y & 0xffffffu, prmt(e.x, e.y, 0x0073), 0x5410);
            p_rank(el);
            p_store(el);
        }
        push(el.r2 >= KS * 2, e.x, e.y);
    }
};

__device__ __forceinline__ void p_filler(const Prm& p, int q, int w) {
    PFill F;
    const int lane = threadIdx.x & 31;
    F.lt = __shfl_sync(0xffffffffu, (1u << lane) - 1u, lane);
    F.qb = F.qt = SB + P_Q + w * (QN * 8); F.nxt = (q % GR) << 16;
    F.f2 = __shfl_sync(0xffffffffu, __bfloat16_as_ushort(p.freq[0]) * 0x10001u, 0);
    constexpr int cstep = NP * CPS;
    const int NS = p.NS, cend = p.T >> 7;
    uint32_t ch = q * CPS + w;
    PIn x0, x1, x2;
    p_fetch(p, x0, ch, lane); p_fetch(p, x1, ch + cstep, lane);
    PROF_DECL
    const int nch = (cend - (int)ch + cstep - 1) / cstep;
    int n = 0;
#pragma unroll 1
    for (; n + 3 <= nch; n += 3) {
        PROF(1); F.begin(); PROF(0); p_fetch(p, x2, ch + 2 * cstep, lane); F.chunk(x0); F.end();
        p_fetch(p, x0, ch + 3 * cstep, lane); PROF(1); F.begin(); PROF(0); F.chunk(x1); F.end();
        p_fetch(p, x1, ch + 4 * cstep, lane); PROF(1); F.begin(); PROF(0); F.chunk(x2); F.end();
        ch += 3 * cstep;
    }
    PROF_END;
#pragma unroll 1
    for (; n < nch; n++) {
        F.begin(); F.chunk(x0); F.end();
        x0 = x1;
    }
    if (q == 0 && w < 4) {
        int t = cend * 128 + w * 32 + lane;
        bool f = t < p.T;
        uint32_t i = 0, o = 0, x = 0;
        if (f) { i = p.idx_in[t]; o = p.idx_out[t]; asm("mul.rn.bf16x2 %0, %1, %2;" : "=r"(x) : "r"((uint32_t)__bfloat16_as_ushort(p.angle[t]) << 16), "r"(F.f2)); }
        F.push_checked(f, i, o, cos2_slow(x & 0xffff0000u));
    }
#pragma unroll 1
    for (; n <= NS + GR; n++) {
        F.begin();
        for (uint32_t nq = (F.qt - F.qb) >> 3; nq > 0;) { uint32_t take = min(nq, 32u); F.retry(take); nq -= take; }
        F.end();
    }
    if (F.qt != F.qb) st_relaxed(&g_ctl.bad, 1);
}

__device__ __forceinline__ void p_flusher(const Prm& p, unsigned char* ring, uint32_t pagebits, int q, int f) {
    const int lane = threadIdx.x & 31;
    const uint32_t bar = SB + P_BAR;
    const int NS = p.NS, NT = NS + 2 * GR;
    const uint32_t wto = lane < NCP ? OFF_REL + lane * 4 : OFF_RDY + (lane % 6) * 4;
    const uint32_t pfo = OFF_PF + (lane / 6) * 32 + (lane & 1) * 16 + ((lane % 6) >> 1) * 4;
    const uint32_t pfc = (lane >> 1) * 6 + (lane & 1);
    PROF_DECL
#pragma unroll 1
    for (int n = f; n < NT; n += NF) {
        const uint32_t buf = (n + q % GR) % NBUF, ph = ((n + q % GR) / NBUF) & 1;
        const uint32_t h = n >> 1, lap = h / RB;
        const uint32_t qb = q_base(q, pagebits) ^ (((n + q) & 1) << 12);
        const uint32_t ba = qb ^ slot_off(h % RA) ^ R_A, bb = qb ^ slot_off(h % RB);
        if (h >= RA && !DEV_FREE)
            wait_all_ge(ring + ((lane < NCP ? bb : qb ^ slot_off((h - RA) % RB)) ^ wto), lane < NCP ? lap : ((h - RA) / RB + 1) << 1);
        PROF(0);
        if (n <= NS + GR) mbar_wait(bar + buf * 8, ph);
        else { int nl = NS + GR + q % GR; mbar_wait(bar + (nl % NBUF) * 8, (nl / NBUF) & 1); }
        PROF(1);
        uint32_t* cnt = (uint32_t*)(smem + P_CNT) + buf * NB;
        bool any = true;
        if (n >= NS) any = __any_sync(0xffffffffu, lane < NCP && (cnt[lane] | cnt[NCP + lane] | cnt[2 * NCP + lane]));
        if (any && elect_one()) {
            asm volatile("fence.proxy.async.shared::cta;" ::: "memory");
#pragma unroll
            for (int k = 0; k < 9; k++) {
                const int u = k < 6 ? k >> 1 : k - 6, hi = k < 6 && (k & 1);
                const uint32_t soff = k < 6 ? P_A + (u * NCP + hi * 8) * (KS * 4) + buf * (NB * KS * 4) : P_B + u * (NCP * KS * 2) + buf * (NB * KS * 2);
                asm volatile("cp.async.bulk.global.shared::cta.bulk_group [%0], [%1], %2;"
                             ::"l"(ring + (k < 6 ? ba : bb ^ R_B) + (u * R_UNIT + hi * 0x40000)), "r"(SB + soff),
                               "r"(k < 6 ? (hi ? NCP - 8 : 8) * (KS * 4) : NCP * KS * 2) : "memory");
            }
            asm volatile("cp.async.bulk.commit_group;" ::: "memory");
        }
        __syncwarp();
        uint32_t wm = ((lap + 1) << 22) | ((uint32_t)any << 21);
        if (lane < NCP) {
#pragma unroll
            for (int u = 0; u < 3; u++) wm |= min(cnt[pfc + 2 * u] >> 1, (uint32_t)KS) << (7 * u);
        }
        __syncwarp();
        if (lane < NB / 2) ((uint2*)cnt)[lane] = make_uint2(0, 0);
        PROF(3);
        asm volatile("cp.async.bulk.wait_group 0;" ::: "memory");
        __syncwarp();
        PROF(2);
        if (lane == 0) mbar_arrive(bar + (NBUF + buf) * 8);
        if (any) fence_release();
        PROF(4);
        if (lane < NCP) st_relaxed(ring + (bb ^ pfo), wm);
    }
    PROF_END;
    if (f == 0) {
        for (int k = 0; k < 2 * RB && !DEV_FREE; k++) {
            const int X = k & 1, r = k >> 1, nh = (NT - ((X + q) & 1) + 1) >> 1;
            wait_all_ge(ring + (q_base(q, pagebits) ^ (X << 12) ^ slot_off(r) ^ (OFF_REL + (lane % NCP) * 4)), (nh - r + RB - 1) / RB);
        }
        for (int k = 0; k < 2 * RB; k++)
            if (lane < 24) *(uint4*)(ring + (q_base(q, pagebits) ^ ((k & 1) << 12) ^ slot_off(k >> 1) ^ OFF_PF) + lane * 16) = make_uint4(0, 0, 0, 0);
    }
}

__device__ __forceinline__ void m_role(const Prm& p, unsigned char* ring, int X, int id) {
    const int tid = threadIdx.x, lane = tid & 31, w = __shfl_sync(0xffffffffu, tid >> 5, 0);
    const int ib = id >> 1, ty = id & 1;
    {
        const int r0 = ib * ROWS_I, nr = max(min((int)ROWS_I, p.E - r0), 0);
        const uint4* src = (const uint4*)(p.m + r0);
        uint32_t mx = 0; float s0 = 0.f, s1 = 0.f;
        constexpr int LB = 10;
#pragma unroll 1
        for (int rb = tid; rb < (int)ROWS_I / 2; rb += LB * THREADS) {
            uint4 v[LB];
#pragma unroll
            for (int k = 0; k < LB; k++) {
                v[k] = make_uint4(0, 0, 0, 0);
                asm volatile("{.reg .pred p; setp.lt.s32 p, %5, %6; @p ld.global.nc.L1::no_allocate.v4.u32 {%0,%1,%2,%3}, [%4];}"
                             : "+r"(v[k].x), "+r"(v[k].y), "+r"(v[k].z), "+r"(v[k].w) : "l"(src + rb + k * THREADS), "r"(rb + k * THREADS), "r"(nr / 2));
            }
#pragma unroll
            for (int k = 0; k < LB; k++) {
                const uint32_t x = ty ? v[k].y : v[k].x, y = ty ? v[k].w : v[k].z;
                if (rb + k * THREADS < (int)ROWS_I / 2) ((uint2*)smem)[rb + k * THREADS] = make_uint2(x, y);
                mx = __vimax3_u16x2(mx, x & 0x7fff7fffu, y & 0x7fff7fffu);
                s0 += bf_lo(x) * bf_lo(x); s0 += bf_lo(y) * bf_lo(y); s1 += bf_hi(x) * bf_hi(x); s1 += bf_hi(y) * bf_hi(y);
            }
        }
        uint32_t mx0 = mx & 0xffffu, mx1 = mx & 0xffff0000u;
        uint4* red = (uint4*)(smem + S_AUX);
        mx0 = __reduce_max_sync(0xffffffffu, mx0 << 16); mx1 = __reduce_max_sync(0xffffffffu, mx1);
#pragma unroll
        for (int o = 16; o; o >>= 1) { s0 += __shfl_xor_sync(0xffffffffu, s0, o); s1 += __shfl_xor_sync(0xffffffffu, s1, o); }
        if (lane == 0) red[w] = make_uint4(mx0, mx1, __float_as_uint(s0), __float_as_uint(s1));
        __syncthreads();
        if (w == 0) {
            uint4 t = lane < NW ? red[lane] : make_uint4(0, 0, 0, 0);
            mx0 = __reduce_max_sync(0xffffffffu, t.x); mx1 = __reduce_max_sync(0xffffffffu, t.y);
            s0 = __uint_as_float(t.z); s1 = __uint_as_float(t.w);
#pragma unroll
            for (int o = 16; o; o >>= 1) { s0 += __shfl_xor_sync(0xffffffffu, s0, o); s1 += __shfl_xor_sync(0xffffffffu, s1, o); }
            if (lane == 0) {
                *(uint4*)g_ctl.stat[X][id] = make_uint4(mx0, mx1, __float_as_uint(s0), __float_as_uint(s1));
                fence_release();
                red_add(&g_ctl.stat_cnt[X], 1);
            }
        }
    }
    float* scs = (float*)(smem + S_MISC);
    if (w == 0) {
        __syncwarp();
        float sc[4]; bool bad;
        get_scales(p, X, sc, bad);
        if (bad) { st_relaxed(&g_ctl.bad, 1); sc[0] = sc[1] = sc[2] = sc[3] = 0.f; }
        int it = 0; uint32_t pb;
        while (!((pb = ld_relaxed(&g_ctl.pagebits)) >> 31)) backoff(it);
        if (lane == 0) { scs[0] = sc[0]; scs[1] = sc[1]; scs[2] = sc[2]; scs[3] = sc[3]; ((uint32_t*)scs)[4] = X ? ~pb : pb; ((uint32_t*)scs)[5] = bad; }
    }
    __syncthreads();
    if (((uint32_t*)scs)[5]) {
        for (int k = tid; k < (int)ROWS_I; k += THREADS) ((uint32_t*)smem)[k] = 0;
        __syncthreads();
    }
    const uint32_t NT = p.NS + 2 * GR;
    if (w >= MW) return;
    const uint32_t pagebits = ((uint32_t*)scs)[4];
    const int half = lane >> 4, k4 = (lane & 15) * 4;
    const float s_lo = scs[2 * ty], s_hi = scs[2 * ty + 1];
    const float MAG_LO = 12582912.f, MAG_HI = 12582912.f - 19264.f;
    const int il = ib / NG, gi = (ib % NG) * 2 + X;
    const uint32_t a_off = R_A + il * R_UNIT + lane * 16, v_off = ty * R_V1 + il * R_UNIT + lane * 16;
    const uint32_t f_off = OFF_PF + il * 32 + half * 16, r_off = OFF_REL + (lane % NCP) * 4;
    const uint32_t j = w % (NP / GR);
    PROF_DECL
#pragma unroll 1
    for (uint32_t n = w / (NP / GR); n < NT; n += MW / (NP / GR)) {
        const uint32_t q = ((gi - n) & (GR - 1)) + GR * j, h = n >> 1;
        const uint32_t qb = q_base(q, pagebits), bb = qb ^ slot_off(h % RB);
        const uint32_t tag = (h / RB + 1) << 22;
        uint4 cw; int it = 0;
        while (true) {
            cw = ld_relaxed4(ring + (bb ^ f_off));
            if (__all_sync(0xffffffffu, min(min(cw.x, cw.y), cw.z) >= tag)) break;
            if (DEV_FREE) { cw.x = (cw.x & 1) + (63 | 57 << 7 | 50 << 14 | 1 << 21); cw.y = (cw.y & 1) + (53 | 61 << 7 | 57 << 14); cw.z = (cw.z & 1) + (59 | 52 << 7 | 57 << 14); break; }
            backoff(it);
        }
        PROF(0);
        if (__any_sync(0xffffffffu, cw.x & (1u << 21))) {
            const uint32_t oa = qb ^ slot_off(h % RA) ^ a_off;
            const unsigned char* pa = ring + oa;
            const unsigned long long sh = p.s_ring + (q >> 1);
            unsigned char* pv = ring + (qb ^ slot_off(h % RV) ^ v_off);
            const uint32_t hv = h + RB - RV;
            const unsigned char* prel = ring + (qb ^ slot_off(hv % RB) ^ r_off);
            const uint32_t rel = ld_relaxed(prel);
            const uint32_t vlap = h / RV;
            const float mag_lo0 = MAG_LO + (float)(8192 + (vlap & 3) * 16384), mag_hi0 = MAG_HI + (float)(8192 + ((vlap >> 2) & 3) * 16384);
            uint4 a[9];
#define M_LOAD(ps) do { if (M_SULD) suld4(a[ps], sh, (oa & 0x1fffff) + (ps) * 512 + ((ps) < 4 ? 0 : R_HI)); \
                        else a[ps] = ld_relaxed4(pa + (ps) * 512 + ((ps) < 4 ? 0 : R_HI)); } while (0)
#pragma unroll
            for (int ps = 0; ps < MPF; ps++) M_LOAD(ps);
            if (!__all_sync(0xffffffffu, rel >= hv / RB) && !DEV_FREE) wait_all_ge(prel, hv / RB);
            PROF(3);
#pragma unroll
            for (int ps = 0; ps < 9; ps++) {
                const int rem = (int)(((ps < 3 ? cw.x : ps < 6 ? cw.y : cw.z) >> (7 * (ps % 3))) & 0x7f) - k4;
                uint32_t aw[4] = {a[ps].x, a[ps].y, a[ps].z, a[ps].w}, mv[4], vw[4];
#pragma unroll
                for (int e = 0; e < 4; e++) { mv[e] = 0; lds_lt(mv[e], __dp2a_lo(aw[e], 4u, (uint32_t)SB), e, rem); }
#pragma unroll
                for (int e = 0; e < 4; e++) {
                    float c = bf_hi(aw[e]);
                    float lo = fmaf(bf_lo(mv[e]), c * s_lo, e ? MAG_LO : mag_lo0), hi = fmaf(bf_hi(mv[e]), c * s_hi, e ? MAG_HI : mag_hi0);
                    vw[e] = (__float_as_uint(hi) << 16) + __float_as_uint(lo);
                }
                asm volatile("st.global.v4.u32 [%0], {%1,%2,%3,%4};" ::"l"(pv + ps * 512 + (ps < 4 ? 0 : R_HI)), "r"(vw[0]), "r"(vw[1]), "r"(vw[2]), "r"(vw[3]) : "memory");
                if (ps + MPF < 9) M_LOAD(ps + MPF);
            }
            if (vlap == 0 || n >= p.NS) fence_release();
        }
        st_lane0(ring + (bb ^ (OFF_RDY + (2 * il + ty) * 4)), cw.x >> 21, lane);
        PROF(1);
    }
    PROF_END;
}

__device__ __noinline__ void c_wrap(uint32_t row, int par, uint32_t old, uint32_t w, uint32_t wrap_base) {
    uint32_t nw = old + w, ov = ~(old ^ w) & (old ^ nw);
    int d = 0;
    if (ov & 0x8000u) d += (w & 0x8000u) ? -1 : 1;
    if (ov & 0x80000000u) d += (w & 0x80000000u) ? -256 : 256;
    if (d != 0) {
        uint32_t o2;
        asm volatile("atom.shared.add.u32 %0, [%1], %2;" : "=r"(o2) : "r"(wrap_base + row * 4), "r"(d << (16 * par)) : "memory");
        if ((o2 + (d << (16 * par))) & 0x80808080u) st_relaxed(&g_ctl.bad, 1);
    }
}

struct CTask { uint4 v[3]; uint2 b[3]; };
struct CWork {
    unsigned char* ring; unsigned long long sh;
    uint32_t v_off, b_off, f_off, r_off, acc;
    uint32_t lap1, sv, sb, vtag, fw;
    int lane, dev_free;
    template <int ODD> __device__ __forceinline__ bool issue(CTask& t) {
        if (!__all_sync(0xffffffffu, fw >= 2 * lap1)) {
            int it = 0;
            do {
                if (dev_free) { fw = 1; break; }
                backoff(it);
                fw = ld_relaxed(ring + (f_off ^ slot_off(sb) ^ (ODD << 20)));
            } while (!__all_sync(0xffffffffu, fw >= 2 * lap1));
        }
        const bool data = __any_sync(0xffffffffu, fw & 1);
        if (data) {
            const uint32_t ov = v_off ^ slot_off(sv) ^ (ODD << 20);
            const unsigned char* pv = ring + ov;
            const unsigned char* pb = ring + (b_off ^ slot_off(sb) ^ (ODD << 20));
#pragma unroll
            for (int ps = 0; ps < 3; ps++) {
                if (ps < C_SULD) suld4(t.v[ps], sh, (ov & 0x1fffff) + ps * R_UNIT);
                else t.v[ps] = ld_relaxed4(pv + ps * R_UNIT);
                t.b[ps] = ld_relaxed2(pb + ps * R_UNIT);
            }
        }
        fw = ld_relaxed(ring + (f_off ^ slot_off(ODD ? (sb + 1 == RB ? 0 : sb + 1) : sb) ^ (!ODD << 20)));
        return data;
    }
    template <int ODD> __device__ __forceinline__ void arrive(CTask& t, bool data) {
        if (data) {
            int it = 0;
            while (__any_sync(0xffffffffu, (((t.v[0].x ^ vtag) | (t.v[1].x ^ vtag) | (t.v[2].x ^ vtag)) & 0xc000c000u) | ((t.b[0].x | t.b[1].x | t.b[2].x) & 0x8000u))) {
                if (dev_free) { for (int ps = 0; ps < 3; ps++) t.v[ps].x = (t.v[ps].x & 0x3fff3fffu) | (vtag & 0xc000c000u); break; }
                if (++it > SPIN_MAX) __trap();
#pragma unroll
                for (int ps = 0; ps < 3; ps++) t.v[ps] = ld_relaxed4(ring + (v_off ^ slot_off(sv) ^ (ODD << 20)) + ps * R_UNIT);
            }
#pragma unroll
            for (int ps = 0; ps < 3; ps++) t.v[ps].x -= vtag;
        }
        st_lane0(ring + (r_off ^ slot_off(sb) ^ (ODD << 20)), lap1, lane);
        if (ODD) {
            if (++sv == RV) { sv = 0; vtag += 0x4000u; if (vtag & 0x10000u) vtag += 0x3fff0000u; }
            if (++sb == RB) { sb = 0; lap1++; }
        }
    }
    __device__ __forceinline__ void add(const CTask& t, bool data) {
        if (!data) return;
        uint32_t old[3][4], ov = 0;
#pragma unroll
        for (int ps = 0; ps < 3; ps++) {
            const uint32_t vw[4] = {t.v[ps].x, t.v[ps].y, t.v[ps].z, t.v[ps].w};
#pragma unroll
            for (int e = 0; e < 4; e++) {
                const uint32_t bw = e < 2 ? t.b[ps].x : t.b[ps].y;
                asm volatile("atom.shared.add.u32 %0, [%1], %2;" : "=r"(old[ps][e]) : "r"((e & 1) ? __dp2a_hi(bw, 0x08000008u, acc) : __dp2a_lo(bw, 0x08000008u, acc)), "r"(vw[e]) : "memory");
            }
        }
#pragma unroll
        for (int ps = 0; ps < 3; ps++) {
            const uint32_t vw[4] = {t.v[ps].x, t.v[ps].y, t.v[ps].z, t.v[ps].w};
#pragma unroll
            for (int e = 0; e < 4; e++) ov |= ~(old[ps][e] ^ vw[e]) & (old[ps][e] ^ (old[ps][e] + vw[e]));
        }
        if (__any_sync(0xffffffffu, ov & 0x80008000u)) {
#pragma unroll
            for (int ps = 0; ps < 3; ps++) {
                const uint32_t vw[4] = {t.v[ps].x, t.v[ps].y, t.v[ps].z, t.v[ps].w};
#pragma unroll
                for (int e = 0; e < 4; e++) {
                    const uint32_t bw = e < 2 ? t.b[ps].x : t.b[ps].y;
                    c_wrap((e & 1) ? bw >> 16 : bw & 0xffffu, lane >> 4, old[ps][e], vw[e], SB + C_WRAP);
                }
            }
        }
    }
};

__device__ __forceinline__ void c_role(const Prm& p, unsigned char* ring, int X, int c) {
    const int tid = threadIdx.x, lane = tid & 31, w = __shfl_sync(0xffffffffu, tid >> 5, 0);
    load_wts(p, (Wts*)(smem + S_AUX));
    for (int k = tid; k < C_TAB / 16; k += THREADS) { uint32_t z = k < C_WRAP / 16 ? 0u : 0x40404040u; ((uint4*)smem)[k] = make_uint4(z, z, z, z); }
    __syncthreads();
    for (int k = tid; k < TAB_N; k += THREADS) ((uint4*)(smem + C_TAB))[k] = radial_bf16((const Wts*)(smem + S_AUX), TAB_LO + k);
    if (w == NW - 1) {
        float sc[4]; bool bad;
        if (!DEV_FREE) get_scales(p, X, sc, bad);
        if (lane < 16) { float s = lane < 4 ? sc[0] : lane < 8 ? sc[1] : lane < 12 ? sc[2] : sc[3]; ((Wts*)(smem + S_AUX))->wd[lane] *= s > 0.f ? 1.f / s : 0.f; }
    }
    uint32_t* misc = (uint32_t*)(smem + S_MISC);
    if (tid == 0) {
        int it = 0; uint32_t pb;
        while (!((pb = ld_relaxed(&g_ctl.pagebits)) >> 31)) backoff(it);
        misc[4] = X ? ~pb : pb;
    }
    __syncthreads();
    const uint32_t pagebits = misc[4];
    if (w >= NP / 2) return;
    CWork W;
    const int par = lane >> 4;
    W.ring = ring; W.lane = __shfl_sync(0xffffffffu, lane, lane); W.sh = p.s_ring + w; W.dev_free = DEV_FREE;
    const uint32_t qb = q_base(2 * w + X, pagebits), k = lane & 15;
    W.acc = __shfl_sync(0xffffffffu, SB + par * 4, lane);
    W.v_off = __shfl_sync(0xffffffffu, qb ^ (par * R_V1 + (c < 8 ? 0 : R_HI) + c * 256 + k * 16), lane);
    W.b_off = __shfl_sync(0xffffffffu, qb ^ (R_B + c * 128 + k * 8), lane);
    W.f_off = __shfl_sync(0xffffffffu, qb ^ (OFF_RDY + (lane % 6) * 4), lane);
    W.r_off = qb ^ (OFF_REL + c * 4);
    W.lap1 = 1; W.sv = W.sb = W.fw = 0; W.vtag = 0x20002000u;
    const uint32_t NT = p.NS + 2 * GR;
    CTask A, B;
    PROF_DECL
    bool da = W.issue<0>(A), db;
#pragma unroll 1
    for (uint32_t n = 2;; n += 2) {
        W.arrive<0>(A, da); PROF(1); db = W.issue<1>(B); PROF(0); W.add(A, da);
        W.arrive<1>(B, db);
        if (n >= NT) break;
        PROF(1); da = W.issue<0>(A); PROF(0); W.add(B, db);
    }
    W.add(B, db);
    PROF_END;
}

__device__ __forceinline__ void c_epilogue(const Prm& p, int X, int c) {
    const int tid = threadIdx.x;
    const Wts* wt = (const Wts*)(smem + S_AUX);
    float wd[16], wu[16];
#pragma unroll
    for (int k = 0; k < 16; k++) { wd[k] = wt->wd[k]; wu[k] = wt->wu[k]; }
    const int r0 = (X * NCP + c) * ROWS_O, nr = min((int)ROWS_O, p.E - r0);
    const uint2* mp = p.m + r0;
    const uint16_t* dp = (const uint16_t*)p.dist + r0;
    uint2* op = p.out + r0;
    constexpr int EB = 4;
#pragma unroll 1
    for (int rb = tid; rb < nr; rb += EB * THREADS) {
        uint2 mr[EB]; uint32_t db[EB];
#pragma unroll
        for (int k = 0; k < EB; k++) { int r = min(rb + k * THREADS, nr - 1); mr[k] = __ldg(mp + r); db[k] = __ldg(dp + r); }
#pragma unroll
        for (int k = 0; k < EB; k++) {
            const int r = rb + k * THREADS;
            if (r < nr) {
                const uint2 s = ((const uint2*)smem)[r];
                const uint32_t wr = ((const uint32_t*)(smem + C_WRAP))[r];
                uint4 t;
                if (db[k] - TAB_LO < TAB_N) t = ((const uint4*)(smem + C_TAB))[db[k] - TAB_LO];
                else t = radial_bf16(wt, db[k]);
                int x0 = (short)s.x, x2 = (short)s.y;
                int x1 = ((int)s.x >> 16) + ((s.x >> 15) & 1), x3 = ((int)s.y >> 16) + ((s.y >> 15) & 1);
                if (wr != 0x40404040u) {
                    int w0 = (int)(wr & 0xff) - 64, w1 = (int)((wr >> 8) & 0xff) - 64, w2 = (int)((wr >> 16) & 0xff) - 64, w3 = (int)(wr >> 24) - 64;
                    x0 += 65536 * w0; x1 += 65536 * w1 - w0; x2 += 65536 * w2; x3 += 65536 * w3 - w2;
                }
                const float a[4] = {(float)x0, (float)x1, (float)x2, (float)x3};
                const float sv[4] = {bf_lo(t.x), bf_hi(t.x), bf_lo(t.y), bf_hi(t.y)}, gv[4] = {bf_lo(t.z), bf_hi(t.z), bf_lo(t.w), bf_hi(t.w)};
                op[r] = finish_row(wd, wu, a, sv, gv, mr[k]);
            }
        }
    }
}

__device__ __forceinline__ void grid_bar(unsigned* ctr) {
    __syncthreads();
    if (threadIdx.x == 0) { fence_gpu(); red_add(ctr, 1); wait_ge(ctr, gridDim.x); fence_gpu(); }
    __syncthreads();
}
__device__ __noinline__ void fallback(const Prm& p) {
    const int gt = blockIdx.x * THREADS + threadIdx.x, gs = gridDim.x * THREADS;
    Wts* wt = (Wts*)smem;
    __syncthreads();
    load_wts(p, wt);
    for (int e = gt; e < p.E; e += gs) g_acc[e] = make_float4(0.f, 0.f, 0.f, 0.f);
    grid_bar(&g_ctl.bar[0]);
    const float f = __bfloat162float(p.freq[0]);
    for (int t = gt; t < p.T; t += gs) {
        uint2 r = __ldg(p.m + p.idx_in[t]);
        float c = rbf16(cosf(rbf16(f * __bfloat162float(p.angle[t]))));
        asm volatile("red.global.add.v4.f32 [%0], {%1,%2,%3,%4};" ::"l"(g_acc + p.idx_out[t]), "f"(bf_lo(r.x) * c),
                     "f"(bf_hi(r.x) * c), "f"(bf_lo(r.y) * c), "f"(bf_hi(r.y) * c) : "memory");
    }
    grid_bar(&g_ctl.bar[1]);
    for (int e = gt; e < p.E; e += gs) {
        float4 a4 = __ldcg(g_acc + e);
        float a[4] = {a4.x, a4.y, a4.z, a4.w}, s[4], g[4];
        radial(wt, __bfloat162float(p.dist[e]), s, g);
        p.out[e] = finish_row(wt->wd, wt->wu, a, s, g, p.m[e]);
    }
}

__global__ void __launch_bounds__(THREADS, 1) gemnet_kernel(const __grid_constant__ Prm p) {
    const int tid = threadIdx.x, lane = tid & 31, w = __shfl_sync(0xffffffffu, tid >> 5, 0);
    uint32_t* misc = (uint32_t*)(smem + S_MISC);
    bool run_fallback = true;
    if (!p.force_bad && __cvta_generic_to_shared(smem) == SB) {
        unsigned char* const ring = p.ring;
        uint32_t smid; asm("mov.u32 %0, %%smid;" : "=r"(smid));
        const int cls = smid < NM ? 0 : (smid < NM + NP - 4 || (smid >= 124 && smid < 128)) ? 2 : 1;
        if (tid == 0) {
            uint32_t side = 0;
            if (cls != 2) side = probe_pair(ring + OFF_PROBE + ((blockIdx.x >> 7) << 20) + (blockIdx.x & 127) * 32);
            int pool = cls == 2 ? 4 : cls * 2 + side, id = 0;
            for (int k = 0; k < 7; k++) {
                int cap = pool < 2 ? NMP : pool < 4 ? NCP : NP;
                id = atomicAdd(&g_ctl.ticket[pool], 1);
                if (id < cap) break;
                pool = k == 0 ? (pool == 4 ? 0 : pool ^ 1) : k - 1;
            }
            misc[8] = pool; misc[9] = id;
        }
        if (blockIdx.x == 0 && w >= 1 && w <= NPAGES) {
            if (lane == 0) misc[16 + w] = probe_pair(ring + ((size_t)(w - 1) << 21) + (1 << 20) + OFF_PROBE + 2048);
            asm volatile("bar.sync 1, %0;" ::"r"(NPAGES * 32) : "memory");
            if (tid == 32) {
                uint32_t pb = 0x80000000u;
                for (int k = 0; k < NPAGES; k++) pb |= (misc[17 + k] ^ misc[17]) << k;
                st_relaxed(&g_ctl.pagebits, pb);
            }
        }
        __syncthreads();
        const int pool = misc[8], id = misc[9];
        __syncthreads();
        if (DEV_FREE && !(DEV_FREE & (pool == 4 ? 1 : pool < 2 ? 2 : 4))) {
        } else if (pool == 4) {
            for (int k = tid; k < S_MISC / 16; k += THREADS) {
                const uint32_t z = k >= P_B / 16 && k < P_Q / 16 ? (k & 7) * 0x20002u : 0u, y = z + (k >= P_B / 16 && k < P_Q / 16 ? 0x10001u : 0u);
                ((uint4*)smem)[k] = make_uint4(z, z, y, y);
            }
            __syncthreads();
            if (tid < 2 * NBUF) {
                const uint32_t a = __cvta_generic_to_shared(smem + P_BAR) + tid * 8, cnt = tid < NBUF ? CPS : 1;
                mbar_init(a, cnt);
                if (tid % NBUF < id % GR) asm volatile("mbarrier.arrive.shared.b64 _, [%0], %1;" ::"r"(a), "r"(cnt) : "memory");
            }
            __syncthreads();
            if (w < CPS) p_filler(p, id, w);
            else if (w < CPS + NF) {
                int it = 0; uint32_t pb;
                while (!((pb = ld_relaxed(&g_ctl.pagebits)) >> 31)) backoff(it);
                p_flusher(p, ring, __shfl_sync(0xffffffffu, pb, 0), id, w - CPS);
            }
        } else if (pool < 2) {
            m_role(p, ring, pool, id);
        } else {
            c_role(p, ring, pool - 2, id);
        }
        __syncthreads();
        if (tid == 0) { fence_gpu(); red_add(&g_ctl.fin, 1); }
        if ((pool == 2 || pool == 3) && !DEV_FREE) c_epilogue(p, pool - 2, id);
        if (tid == 0) { wait_ge(&g_ctl.fin, NCTA); fence_gpu(); misc[10] = ld_relaxed(&g_ctl.bad); }
        __syncthreads();
        run_fallback = misc[10] && !DEV_FREE;
    }
    if (run_fallback) fallback(p);
    if (tid == 0) {
        fence_gpu();
        if (atomicAdd(&g_ctl.exited, 1) == gridDim.x - 1) {
            uint32_t* c = (uint32_t*)&g_ctl;
            for (int k = 0; k < 32; k++) c[k] = 0;
        }
    }
}

cudaTextureObject_t make_tex(const void* ptr, size_t bytes, int words) {
    cudaResourceDesc rd = {};
    rd.resType = cudaResourceTypeLinear;
    rd.res.linear.devPtr = (void*)ptr;
    rd.res.linear.desc = words == 4 ? cudaCreateChannelDesc<uint4>() : cudaCreateChannelDesc<uint2>();
    rd.res.linear.sizeInBytes = bytes;
    cudaTextureDesc td = {};
    td.readMode = cudaReadModeElementType;
    cudaTextureObject_t t = 0;
    if (cudaCreateTextureObject(&t, &rd, &td, nullptr) != cudaSuccess) { cudaGetLastError(); return 0; }
    return t;
}

cudaTextureObject_t make_windows(const void* ptr, size_t bytes) {
    cudaTextureObject_t first = 0;
    for (size_t o = 0, k = 0; o < bytes; o += 2u << 20, k++) {
        cudaTextureObject_t t = make_tex((const char*)ptr + o, bytes - o < (2u << 20) ? bytes - o : (2u << 20), 4);
        if (k == 0) first = t;
        if (!t || t != first + k) return 0;
    }
    return first;
}

}

extern "C" void kernel_launch(void* const* d_in, const int* in_sizes, int n_in, void* d_out, int out_size) {
    static Prm p = {};
    static int grid = 0;
    const int E = in_sizes[3], T = in_sizes[1];
    if (grid == 0 || p.idx_in != d_in[1] || p.idx_out != d_in[2] || p.angle != d_in[4] || p.E != E || p.T != T) {
        int dev = 0, sms = 0;
        cudaGetDevice(&dev);
        cudaDeviceGetAttribute(&sms, cudaDevAttrMultiProcessorCount, dev);
        cudaFuncSetAttribute(gemnet_kernel, cudaFuncAttributeMaxDynamicSharedMemorySize, SMEM_BYTES);
        p.E = E; p.T = T;
        p.NS = ((T / 128 + NP * CPS - 1) / (NP * CPS) + 1) & ~1;
        void* rp = nullptr;
        cudaGetSymbolAddress(&rp, g_ring);
        p.ring = (unsigned char*)(((uintptr_t)rp + ((2u << 20) - 1)) & ~(uintptr_t)((2u << 20) - 1));
        bool fast = sms >= NCTA && E <= (int)FAST_E && (E & 1) == 0 && T >= 128 && T <= (1 << 29);
        if (fast) {
            p.t_in = make_tex(d_in[1], (size_t)(T / 128) * 512, 4);
            p.t_out = make_tex(d_in[2], (size_t)(T / 128) * 512, 4);
            p.t_ang = make_tex(d_in[4], (size_t)(T / 128) * 256, 2);
            fast = p.t_in && p.t_out && p.t_ang;
            if (P_SULD) { p.s_in = make_windows(d_in[1], (size_t)(T / 128) * 512); p.s_out = make_windows(d_in[2], (size_t)(T / 128) * 512); fast = fast && p.s_in && p.s_out; }
            if (M_SULD || C_SULD) { p.s_ring = make_windows(p.ring, RING_BYTES); fast = fast && p.s_ring; }
        }
        p.force_bad = !fast;
        grid = fast ? NCTA : sms;
    }
    p.m = (const uint2*)d_in[0];
    p.idx_in = (const int*)d_in[1];
    p.idx_out = (const int*)d_in[2];
    p.dist = (const __nv_bfloat16*)d_in[3];
    p.angle = (const __nv_bfloat16*)d_in[4];
    p.centers = (const __nv_bfloat16*)d_in[5];
    p.freq = (const __nv_bfloat16*)d_in[6];
    p.w_rbf = (const __nv_bfloat16*)d_in[7];
    p.w_sbf = (const __nv_bfloat16*)d_in[8];
    p.w_down = (const __nv_bfloat16*)d_in[9];
    p.w_up = (const __nv_bfloat16*)d_in[10];
    p.out = (uint2*)d_out;
    gemnet_kernel<<<grid, THREADS, SMEM_BYTES>>>(p);
}
```

```cpp
#include <cuda_runtime.h>
#include <cuda_bf16.h>
#include <stdint.h>

namespace {

constexpr int NI = 12;
constexpr int UN = 3;
constexpr int NG = NI / UN;
constexpr int GR = 2 * NG;
constexpr int NCP = 18;
constexpr int NO = 2 * NCP;
constexpr int KS = 64;
constexpr int NB = UN * NCP;
constexpr int NBUF = 10;
constexpr int NMP = 2 * NI;
constexpr int NP = 48, NM = 2 * NMP, NC = NO, NCTA = NP + NM + NC;
#define CPS_ 24
constexpr int CPS = CPS_;
#define FB_ 1
constexpr int FB = FB_;
constexpr int NF = FB > 2 ? 3 : 4;
static_assert((NF - 1) * FB < NBUF, "barrier phases");
#define RA_ 4
#define RV_ 3
#define RB_ 5
constexpr int RA = RA_, RV = RV_, RB = RB_;
constexpr int QN = 80, QTRIG = 40;
#define MW_ 18
constexpr int MW = MW_;
#define MPF_ 6
constexpr int MPF = MPF_;
constexpr int THREADS = 896, NW = THREADS / 32;
#define DEV_FREE 0
#define P_SULD 0
#ifndef M_SULD
#define M_SULD 0
#endif
#define C_SULD 0
#define SLEEP_ 200

constexpr int RING_BYTES = NP << 20;
constexpr int NPAGES = RING_BYTES >> 21;
constexpr int MAX_E = 1 << 20;
constexpr int SMEM_BYTES = 232448;

constexpr int SB = 1024;

constexpr int P_CNT = 0;
constexpr int P_BAR = P_CNT + NBUF * NB * 4;
constexpr int P_B = (P_BAR + 2 * NBUF * 8 + 127) / 128 * 128;
constexpr int P_Q = P_B + NBUF * NB * KS * 2;
constexpr int P_A = SMEM_BYTES - 256 - NBUF * NB * KS * 4;
static_assert(P_Q + CPS * QN * 8 + 512 <= P_A && P_A % 128 == 0, "P smem");
constexpr int S_MISC = SMEM_BYTES - 256;
constexpr int S_AUX = S_MISC - 512;

constexpr unsigned FAST_E = 640000;
constexpr unsigned magic_of(unsigned long long d) { return (unsigned)(((1ull << 32) + d - 1) / d); }
constexpr bool magic_ok(unsigned long long d) { return (magic_of(d) * d - (1ull << 32)) * FAST_E < (1ull << 32); }
constexpr unsigned pick_rows(unsigned lo) {
    unsigned d = (lo + 3) & ~3u;
    while (!magic_ok(d)) d += 4;
    return d;
}
constexpr unsigned ROWS_I = pick_rows((FAST_E + NI - 1) / NI), ROWS_O = pick_rows((FAST_E + NO - 1) / NO);
constexpr unsigned MAG_I = magic_of(ROWS_I), MAG_O = magic_of(ROWS_O), HALF_O = ROWS_O * NCP;
constexpr int C_WRAP = ROWS_O * 8, C_TAB = ROWS_O * 12, TAB_N = 1025, TAB_LO = 0x3f80 - 1024, TAB_X = (S_AUX - C_TAB) / 16 - TAB_N;
static_assert(ROWS_I * 4 <= S_AUX && TAB_X >= 100 && ROWS_I <= 65536 && ROWS_O <= 32768, "tables");

constexpr int NPC = NM + NC;
constexpr int PC_ROWS = ((FAST_E + NPC - 1) / NPC + 3) & ~3;
struct __align__(128) Ctl {
    unsigned ticket[5];
    unsigned pagebits;
    unsigned pieces_done, unused;
    unsigned bad;
    unsigned fin;
    unsigned bar[3];
    unsigned exited;
    unsigned pad[18];
    float stat[NPC][8];
};

struct Prm {
    const uint2* m; const int* idx_in; const int* idx_out; const __nv_bfloat16* dist; const __nv_bfloat16* angle;
    const __nv_bfloat16* centers; const __nv_bfloat16* freq; const __nv_bfloat16* w_rbf; const __nv_bfloat16* w_sbf;
    const __nv_bfloat16* w_down; const __nv_bfloat16* w_up; uint2* out;
    cudaTextureObject_t t_in, t_out, t_ang;
    cudaTextureObject_t s_in, s_out, s_ring;
    int E, T;
    unsigned char* ring;
    int NS;
    int force_bad;
};

__device__ __align__(128) unsigned char g_ring[RING_BYTES + (2 << 20)];
__device__ Ctl g_ctl;
__device__ float4 g_acc[MAX_E];
__device__ __align__(128) uint32_t g_md[2][NI * ROWS_I];
#define TS(k)
#define PROF_DECL
#define PROF(k)
#define PROF_END

extern __shared__ __align__(128) unsigned char smem[];

__device__ __forceinline__ float bf_lo(uint32_t w) { return __uint_as_float(w << 16); }
__device__ __forceinline__ float bf_hi(uint32_t w) { return __uint_as_float(w & 0xffff0000u); }
__device__ __forceinline__ float rbf16(float x) { return __bfloat162float(__float2bfloat16_rn(x)); }
__device__ __forceinline__ uint32_t pack_bf16(float hi, float lo) {
    uint32_t r; asm("cvt.rn.bf16x2.f32 %0, %1, %2;" : "=r"(r) : "f"(hi), "f"(lo)); return r;
}
__device__ __forceinline__ uint32_t prmt(uint32_t a, uint32_t b, uint32_t c) {
    uint32_t r; asm("prmt.b32 %0, %1, %2, %3;" : "=r"(r) : "r"(a), "r"(b), "r"(c)); return r;
}
__device__ __forceinline__ uint32_t ld_relaxed(const void* p) {
    uint32_t v; asm volatile("ld.relaxed.gpu.global.u32 %0, [%1];" : "=r"(v) : "l"(p) : "memory"); return v;
}
__device__ __forceinline__ uint2 ld_relaxed2(const void* p) {
    uint2 v; asm volatile("ld.relaxed.gpu.global.v2.u32 {%0,%1}, [%2];" : "=r"(v.x), "=r"(v.y) : "l"(p) : "memory"); return v;
}
__device__ __forceinline__ uint4 ld_relaxed4(const void* p) {
    uint4 v; asm volatile("ld.relaxed.gpu.global.v4.u32 {%0,%1,%2,%3}, [%4];" : "=r"(v.x), "=r"(v.y), "=r"(v.z), "=r"(v.w) : "l"(p) : "memory"); return v;
}
__device__ __forceinline__ void st_relaxed(void* p, uint32_t v) { asm volatile("st.relaxed.gpu.global.u32 [%0], %1;" ::"l"(p), "r"(v) : "memory"); }
__device__ __forceinline__ void st_relaxed16(void* p, uint32_t v) { asm volatile("st.relaxed.gpu.global.u16 [%0], %1;" ::"l"(p), "h"((uint16_t)v) : "memory"); }
__device__ __forceinline__ void red_add(void* p, uint32_t v) { asm volatile("red.relaxed.gpu.global.add.u32 [%0], %1;" ::"l"(p), "r"(v) : "memory"); }
__device__ __forceinline__ void fence_gpu() { asm volatile("fence.acq_rel.gpu;" ::: "memory"); }
__device__ __forceinline__ void fence_acquire() { asm volatile("fence.acquire.gpu;" ::: "memory"); }
__device__ __forceinline__ void fence_release() { asm volatile("fence.release.gpu;" ::: "memory"); }
__device__ __forceinline__ void mbar_init(uint32_t a, uint32_t n) { asm volatile("mbarrier.init.shared.b64 [%0], %1;" ::"r"(a), "r"(n) : "memory"); }
__device__ __forceinline__ void mbar_arrive(uint32_t a) { asm volatile("mbarrier.arrive.shared.b64 _, [%0];" ::"r"(a) : "memory"); }
__device__ __forceinline__ bool mbar_try(uint32_t a, uint32_t ph) {
    uint32_t ok;
    asm volatile("{.reg .pred p; mbarrier.try_wait.parity.shared.b64 p, [%1], %2, %3; selp.u32 %0, 1, 0, p;}" : "=r"(ok) : "r"(a), "r"(ph), "r"(2000) : "memory");
    return ok;
}
constexpr int SPIN_MAX = 1 << 22;
__device__ __forceinline__ void mbar_wait(uint32_t a, uint32_t ph) {
    int it = 0;
    while (!mbar_try(a, ph)) { if (++it > SPIN_MAX) __trap(); }
}
__device__ __forceinline__ void backoff(int& it) { __nanosleep(SLEEP_); if (++it > SPIN_MAX) __trap(); }
__device__ __forceinline__ void wait_ge(const void* p, uint32_t v) {
    int it = 0;
    while (ld_relaxed(p) < v) backoff(it);
}

__device__ __forceinline__ bool elect_one() {
    uint32_t r; asm volatile("{.reg .pred p; elect.sync _|p, 0xffffffff; selp.u32 %0, 1, 0, p;}" : "=r"(r)); return r;
}
__device__ __forceinline__ void st_lane0(void* p, uint32_t v, int lane) {
    asm volatile("{.reg .pred p; setp.eq.s32 p, %2, 0; @p st.relaxed.gpu.global.u32 [%0], %1;}" ::"l"(p), "r"(v), "r"(lane) : "memory");
}
__device__ __forceinline__ void wait_all_ge(const void* p, uint32_t v) {
    int it = 0;
    while (!__all_sync(0xffffffffu, ld_relaxed(p) >= v)) backoff(it);
}
__device__ __forceinline__ void suld4(uint4& v, unsigned long long h, uint32_t off) {
    asm volatile("suld.b.1d.cg.v4.b32.zero {%0,%1,%2,%3}, [%4, {%5}];" : "=r"(v.x), "=r"(v.y), "=r"(v.z), "=r"(v.w) : "l"(h), "r"(off) : "memory");
}
__device__ __forceinline__ void lds_lt(uint32_t& v, uint32_t ad, int a, int b) {
    asm volatile("{.reg .pred p; setp.lt.s32 p, %2, %3; @p ld.shared.u32 %0, [%1];}" : "+r"(v) : "r"(ad), "r"(a), "r"(b));
}

constexpr uint32_t R_V1 = 0x03000, R_A = 0x81000, R_B = 0x82000, R_UNIT = 0x4000, R_HI = 0x40000 - 8 * 256;
__device__ __forceinline__ uint32_t q_base(uint32_t q, uint32_t pagebits_x) { return (q << 20) | (((pagebits_x >> (q >> 1)) & 1u) << 12); }
__device__ __forceinline__ uint32_t slot_off(uint32_t s) { return (s << 16) | (((s + 1) & 2) << 11); }
constexpr uint32_t OFF_PF = R_B + 3 * R_UNIT, OFF_RDY = OFF_PF + 128, OFF_REL = OFF_PF + 256;
constexpr uint32_t OFF_PROBE = 3 * R_UNIT;
static_assert(RA <= 4 && RV <= 4 && RB <= 8 && RA <= RB && RV <= RB, "ring");

__device__ __forceinline__ uint32_t probe(unsigned char* p) {
    volatile uint32_t* sink = (volatile uint32_t*)(smem + S_MISC + 240);
    asm volatile("st.global.v4.u32 [%0], {%1,%1,%1,%1};" ::"l"(p), "r"(0) : "memory");
    asm volatile("st.global.v4.u32 [%0], {%1,%1,%1,%1};" ::"l"(p + 16), "r"(0) : "memory");
    uint32_t best = 0xffffffffu;
#pragma unroll 1
    for (int r = 0; r < 3; r++) {
        uint32_t t0, t1, v;
        asm volatile("mov.u32 %0, %%clock;" : "=r"(t0)::"memory");
        asm volatile("atom.relaxed.gpu.global.add.u32 %0, [%1], 1;" : "=r"(v) : "l"(p) : "memory");
        *sink = v;
        asm volatile("mov.u32 %0, %%clock;" : "=r"(t1)::"memory");
        best = min(best, t1 - t0);
    }
    return best;
}

struct Wts { float c[8], wr[32], ws[32], wd[16], wu[16]; };
__device__ __forceinline__ void load_wts(const Prm& p, Wts* w) {
    int t = threadIdx.x;
    if (t < 8) w->c[t] = __bfloat162float(p.centers[t]);
    if (t < 32) { w->wr[t] = __bfloat162float(p.w_rbf[t]); w->ws[t] = __bfloat162float(p.w_sbf[t]); }
    if (t < 16) { w->wd[t] = __bfloat162float(p.w_down[t]); w->wu[t] = __bfloat162float(p.w_up[t]); }
}
__device__ __forceinline__ void radial(const Wts* w, float d, float s[4], float g[4]) {
#pragma unroll
    for (int j = 0; j < 4; j++) s[j] = g[j] = 0.f;
#pragma unroll
    for (int r = 0; r < 8; r++) {
        float x = rbf16(d - w->c[r]);
        float b = rbf16(__expf(rbf16(-10.0f * rbf16(x * x))));
#pragma unroll
        for (int j = 0; j < 4; j++) { s[j] += b * w->ws[r * 4 + j]; g[j] += b * w->wr[r * 4 + j]; }
    }
}
__device__ __noinline__ uint4 radial_bf16(const Wts* w, uint32_t dbits) {
    float s[4], g[4];
    radial(w, __uint_as_float(dbits << 16), s, g);
    return make_uint4(pack_bf16(s[1], s[0]), pack_bf16(s[3], s[2]), pack_bf16(g[1], g[0]), pack_bf16(g[3], g[2]));
}
__device__ __forceinline__ uint2 finish_row(const float* wu, const float agg[4], const float g[4], uint2 r) {
    float o[4];
    const float mm[4] = {bf_lo(r.x), bf_hi(r.x), bf_lo(r.y), bf_hi(r.y)};
#pragma unroll
    for (int j = 0; j < 4; j++) o[j] = mm[j] + (agg[0] * wu[j] + agg[1] * wu[4 + j] + agg[2] * wu[8 + j] + agg[3] * wu[12 + j]) * g[j];
    return make_uint2(pack_bf16(o[1], o[0]), pack_bf16(o[3], o[2]));
}
__device__ __forceinline__ uint2 down_row(const float* wd, uint32_t x, uint32_t y) {
    const float a[4] = {bf_lo(x), bf_hi(x), bf_lo(y), bf_hi(y)};
    float d[4];
#pragma unroll
    for (int j = 0; j < 4; j++) d[j] = a[0] * wd[j] + a[1] * wd[4 + j] + a[2] * wd[8 + j] + a[3] * wd[12 + j];
    return make_uint2(pack_bf16(d[1], d[0]), pack_bf16(d[3], d[2]));
}

__device__ __forceinline__ void down_piece(const Prm& p, int pc, const float* wd) {
    const int tid = threadIdx.x, lane = tid & 31, w = tid >> 5;
    const int r0 = pc * PC_ROWS / 2, nr = max(min((pc + 1) * PC_ROWS, p.E) / 2 - r0, 0);
    const uint32_t bar = SB + S_AUX + 504;
    if (tid == 0) {
        mbar_init(bar, 1);
        asm volatile("fence.proxy.async.shared::cta;" ::: "memory");
        asm volatile("mbarrier.arrive.expect_tx.shared.b64 _, [%0], %1;" ::"r"(bar), "r"(nr * 16) : "memory");
        for (int o = 0; o < nr; o += 1024)
            asm volatile("cp.async.bulk.shared::cluster.global.mbarrier::complete_tx::bytes [%0], [%1], %2, [%3];"
                         ::"r"(SB + o * 16), "l"((const uint4*)p.m + r0 + o), "r"(min(1024, nr - o) * 16), "r"(bar) : "memory");
    }
    __syncthreads();
    mbar_wait(bar, 0);
    uint32_t mx0 = 0, mx1 = 0; float ss[4] = {0.f, 0.f, 0.f, 0.f};
    for (int r = tid; r < nr; r += THREADS) {
        const uint4 v = ((const uint4*)smem)[r];
        const uint2 a = down_row(wd, v.x, v.y), b = down_row(wd, v.z, v.w);
        ((uint2*)g_md[0])[r0 + r] = make_uint2(a.x, b.x); ((uint2*)g_md[1])[r0 + r] = make_uint2(a.y, b.y);
        mx0 = __vimax3_u16x2(mx0, a.x & 0x7fff7fffu, b.x & 0x7fff7fffu); mx1 = __vimax3_u16x2(mx1, a.y & 0x7fff7fffu, b.y & 0x7fff7fffu);
        ss[0] += bf_lo(a.x) * bf_lo(a.x) + bf_lo(b.x) * bf_lo(b.x); ss[1] += bf_hi(a.x) * bf_hi(a.x) + bf_hi(b.x) * bf_hi(b.x);
        ss[2] += bf_lo(a.y) * bf_lo(a.y) + bf_lo(b.y) * bf_lo(b.y); ss[3] += bf_hi(a.y) * bf_hi(a.y) + bf_hi(b.y) * bf_hi(b.y);
    }
    uint32_t st[4] = {mx0 << 16, mx0 & 0xffff0000u, mx1 << 16, mx1 & 0xffff0000u};
    uint4* red = (uint4*)(smem + PC_ROWS * 8);
    for (int pass = 0; pass < 2; pass++) {
#pragma unroll
        for (int ch = 0; ch < 4; ch++) {
            st[ch] = __reduce_max_sync(0xffffffffu, st[ch]);
#pragma unroll
            for (int o = 16; o; o >>= 1) ss[ch] += __shfl_xor_sync(0xffffffffu, ss[ch], o);
        }
        uint4* dst = pass ? (uint4*)g_ctl.stat[pc] : red + 2 * w;
        if (lane == 0) { dst[0] = make_uint4(st[0], st[1], st[2], st[3]); dst[1] = make_uint4(__float_as_uint(ss[0]), __float_as_uint(ss[1]), __float_as_uint(ss[2]), __float_as_uint(ss[3])); }
        if (pass) break;
        __syncthreads();
        const uint4 a = lane < NW ? red[2 * lane] : make_uint4(0, 0, 0, 0), b = lane < NW ? red[2 * lane + 1] : make_uint4(0, 0, 0, 0);
        __syncthreads();
        if (w != 0) return;
        st[0] = a.x; st[1] = a.y; st[2] = a.z; st[3] = a.w;
        ss[0] = __uint_as_float(b.x); ss[1] = __uint_as_float(b.y); ss[2] = __uint_as_float(b.z); ss[3] = __uint_as_float(b.w);
    }
    if (lane == 0) { fence_release(); red_add(&g_ctl.pieces_done, 1); }
    __syncwarp();
}

__device__ __forceinline__ void get_scales(const Prm& p, float sc[4], bool& bad) {
    const int lane = threadIdx.x & 31;
    uint32_t mxb[4] = {0, 0, 0, 0};
    float ss[4] = {0.f, 0.f, 0.f, 0.f};
#pragma unroll
    for (int k = 0; k < (NPC + 31) / 32; k++) {
        if (lane + 32 * k < NPC) {
            const uint4 a = ld_relaxed4(&g_ctl.stat[lane + 32 * k][0]), b = ld_relaxed4(&g_ctl.stat[lane + 32 * k][4]);
            mxb[0] = max(mxb[0], a.x); mxb[1] = max(mxb[1], a.y); mxb[2] = max(mxb[2], a.z); mxb[3] = max(mxb[3], a.w);
            ss[0] += __uint_as_float(b.x); ss[1] += __uint_as_float(b.y); ss[2] += __uint_as_float(b.z); ss[3] += __uint_as_float(b.w);
        }
    }
    bad = false;
    const float kdeg = fminf(3.5f * sqrtf(fmaxf(0.5f * (float)p.T / (float)p.E, 1.0f)), 128.f);
#pragma unroll
    for (int ch = 0; ch < 4; ch++) {
        float mx = __uint_as_float(__reduce_max_sync(0xffffffffu, mxb[ch]));
#pragma unroll
        for (int o = 16; o; o >>= 1) ss[ch] += __shfl_xor_sync(0xffffffffu, ss[ch], o);
        float rms = sqrtf(ss[ch] / (float)p.E);
        float range = fmaxf(4.002f * mx, kdeg * rms);
        if (!(mx <= 1e15f) || !(range <= 128.f * rms) || (mx > 0.f && mx < 1e-15f)) bad = true;
        sc[ch] = range > 0.f ? 32767.f / range : 0.f;
    }
}

constexpr int PER = 40;
struct __align__(16) PTab { uint32_t e[PER][4]; };
constexpr PTab make_ptab() {
    PTab t = {};
    for (int s = 0; s < PER; s++) {
        for (int d = 0; d < GR; d++) {
            int gi = (s + d) % GR, buf = (s + d) % NBUF, X = gi & 1, g = gi >> 1;
            t.e[s][X] |= (uint32_t)(4 * UN * buf - g - 4 * X + 7) << (8 * g);
        }
        int mnew = s + GR - 1;
        t.e[s][2] = (uint32_t)(SB + P_BAR + (NBUF + mnew % NBUF) * 8) | (uint32_t)(((mnew / NBUF) & 1) ^ 1) << 31;
        t.e[s][3] = (uint32_t)(SB + P_BAR + (s % NBUF) * 8) | (uint32_t)((s + 1) % PER) << 16;
    }
    return t;
}
__constant__ PTab c_ptab = make_ptab();
constexpr int BIAS = 7 * NCP;
static_assert(NG == 4, "group selection");

struct PCtx { uint32_t a0, a1; };
struct PElem { uint32_t b4, aw, ol, r2; };

__device__ __forceinline__ void p_bin(const PCtx& c, PElem& e, uint32_t i, uint32_t o, uint32_t cw, uint32_t csel) {
    uint32_t ib = __umulhi(i, MAG_I), ob = __umulhi(o, MAG_O), sel = ib & 3;
    asm("{.reg .pred p; setp.ge.u32 p, %1, %2; @p add.u32 %0, %0, 4;}" : "+r"(sel) : "r"(o), "n"(HALF_O));
    e.b4 = __dp4a(prmt(c.a0, c.a1, sel), (uint32_t)NCP, ib * NCP + ob * 4);
    e.aw = prmt(i - ib * ROWS_I, cw, csel);
    e.ol = o - ob * ROWS_O;
}
__device__ __forceinline__ void p_rank(PElem& e) {
    asm volatile("atom.shared.add.u32 %0, [%1+%2], 2;" : "=r"(e.r2) : "r"(e.b4), "n"(SB + P_CNT - BIAS) : "memory");
}
__device__ __forceinline__ void p_store(const PElem& e) {
    const uint32_t ab = e.b4 * (KS / 2) + e.r2;
    asm volatile("{.reg .pred p; setp.lt.u32 p, %4, %5; @p st.shared.u32 [%0+%6], %1; @p st.shared.u16 [%2+%7], %3;}"
                 ::"r"(ab * 2), "r"(e.aw), "r"(ab), "h"((uint16_t)e.ol), "r"(e.r2), "n"(KS * 2),
                   "n"(SB + P_A - BIAS * KS), "n"(SB + P_B - BIAS * (KS / 2)) : "memory");
}
__device__ __noinline__ uint32_t cos2_slow(uint32_t x) {
    float a = cosf(bf_lo(x)), b = cosf(bf_hi(x));
    if (!(fabsf(a + b) <= 2.f)) { st_relaxed(&g_ctl.bad, 1); a = b = 0.f; }
    return pack_bf16(b, a);
}

struct PIn { uint4 i, o; uint2 a; };
__device__ __forceinline__ void p_fetch(const Prm& p, PIn& x, uint32_t ch, uint32_t lane) {
    const int v = ch * 32 + lane;
    asm volatile("{.reg .b32 d0, d1; tex.1d.v4.u32.s32 {%0,%1,d0,d1}, [%2, {%3}];}" : "=r"(x.a.x), "=r"(x.a.y) : "l"(p.t_ang), "r"(v));
    if (P_SULD) {
        const uint32_t win = min(ch, (uint32_t)(p.T >> 7) - 1) >> 12, off = (v & 0x1ffff) * 16;
        asm volatile("suld.b.1d.cs.v4.b32.zero {%0,%1,%2,%3}, [%4, {%5}];" : "=r"(x.i.x), "=r"(x.i.y), "=r"(x.i.z), "=r"(x.i.w) : "l"(p.s_in + win), "r"(off));
        asm volatile("suld.b.1d.cs.v4.b32.zero {%0,%1,%2,%3}, [%4, {%5}];" : "=r"(x.o.x), "=r"(x.o.y), "=r"(x.o.z), "=r"(x.o.w) : "l"(p.s_out + win), "r"(off));
    } else {
        asm volatile("tex.1d.v4.u32.s32 {%0,%1,%2,%3}, [%4, {%5}];" : "=r"(x.i.x), "=r"(x.i.y), "=r"(x.i.z), "=r"(x.i.w) : "l"(p.t_in), "r"(v));
        asm volatile("tex.1d.v4.u32.s32 {%0,%1,%2,%3}, [%4, {%5}];" : "=r"(x.o.x), "=r"(x.o.y), "=r"(x.o.z), "=r"(x.o.w) : "l"(p.t_out), "r"(v));
    }
}

struct PFill {
    PCtx c;
    uint32_t qb, qt, lt, f2, nxt;
    __device__ __forceinline__ void begin() {
        const uint2* t = (const uint2*)c_ptab.e + 2 * (nxt >> 16);
        const uint2 m = t[0], s = t[1];
        c.a0 = m.x; c.a1 = m.y;
        nxt = s.y;
        mbar_wait(s.x & 0xffff, s.x >> 31);
    }
    __device__ __forceinline__ void end() {
        __syncwarp();
        asm volatile("{.reg .pred p; setp.eq.u32 p, %1, 0; @p mbarrier.arrive.shared.b64 _, [%0];}" ::"r"(nxt & 0xffff), "r"(lt) : "memory");
    }
    __device__ __forceinline__ void push(bool f, uint32_t x, uint32_t y) {
        uint32_t mask = __ballot_sync(0xffffffffu, f);
        asm volatile("{.reg .pred p; setp.ne.u32 p, %3, 0; @p st.shared.v2.u32 [%0], {%1,%2};}" ::"r"(qt + __popc(mask & lt) * 8), "r"(x), "r"(y), "r"((uint32_t)f) : "memory");
        qt += __popc(mask) * 8;
    }
    __device__ __forceinline__ void push_checked(bool f, uint32_t i, uint32_t o, uint32_t aw) {
        if (qt - qb + __popc(__ballot_sync(0xffffffffu, f)) * 8 > QN * 8) st_relaxed(&g_ctl.bad, 1);
        else push(f, prmt(i, aw, 0x6210), prmt(o, aw, 0x7210));
    }
    __device__ __forceinline__ void chunk(const PIn& x) {
        uint32_t x0, x1, c0, c1;
        asm("mul.rn.bf16x2 %0, %1, %2;" : "=r"(x0) : "r"(x.a.x), "r"(f2));
        asm("mul.rn.bf16x2 %0, %1, %2;" : "=r"(x1) : "r"(x.a.y), "r"(f2));
        c0 = pack_bf16(__cosf(bf_hi(x0)), __cosf(bf_lo(x0)));
        c1 = pack_bf16(__cosf(bf_hi(x1)), __cosf(bf_lo(x1)));
        if (__any_sync(0xffffffffu, (((x0 & 0x7fff7fffu) + 0x3e003e00u) | ((x1 & 0x7fff7fffu) + 0x3e003e00u)) & 0x80008000u)) { c0 = cos2_slow(x0); c1 = cos2_slow(x1); }
        PElem e0, e1, e2, e3;
        p_bin(c, e0, x.i.x, x.o.x, c0, 0x5410); p_rank(e0);
        p_bin(c, e1, x.i.y, x.o.y, c0, 0x7610); p_rank(e1);
        p_bin(c, e2, x.i.z, x.o.z, c1, 0x5410); p_rank(e2);
        p_bin(c, e3, x.i.w, x.o.w, c1, 0x7610); p_rank(e3);
        p_store(e0); p_store(e1); p_store(e2); p_store(e3);
        const uint32_t r01 = e0.r2 | e1.r2, r23 = e2.r2 | e3.r2;
        const bool f = (r01 | r23) >= KS * 2;
        if (__any_sync(0xffffffffu, f)) {
            const bool f0 = e0.r2 >= KS * 2, f1 = e1.r2 >= KS * 2, f2_ = e2.r2 >= KS * 2, f3 = e3.r2 >= KS * 2, f01 = r01 >= KS * 2;
            uint32_t si = f01 ? (f0 ? x.i.x : x.i.y) : (f2_ ? x.i.z : x.i.w);
            uint32_t so = f01 ? (f0 ? x.o.x : x.o.y) : (f2_ ? x.o.z : x.o.w);
            uint32_t sc = f01 ? (f0 ? e0.aw : e1.aw) : (f2_ ? e2.aw : e3.aw);
            push(f, prmt(si, sc, 0x6210), prmt(so, sc, 0x7210));
            uint32_t s2 = max(max(min(e0.r2, e1.r2), min(e2.r2, e3.r2)), min(r01, r23));
            if (__any_sync(0xffffffffu, s2 >= KS * 2)) {
                push_checked(f1 && f0, x.i.y, x.o.y, e1.aw);
                push_checked(f2_ && f01, x.i.z, x.o.z, e2.aw);
                push_checked(f3 && (f01 || f2_), x.i.w, x.o.w, e3.aw);
            }
            if (qt - qb >= QTRIG * 8) {
                retry(32);
                if (qt - qb > (QN - 32) * 8) { st_relaxed(&g_ctl.bad, 1); qt = qb; }
            }
        }
    }
    __device__ __forceinline__ void retry(uint32_t take) {
        const uint32_t lane8 = (threadIdx.x & 31) * 8;
        uint2 e, r0, r1;
        __syncwarp();
        asm volatile("ld.shared.v2.u32 {%0,%1}, [%2];" : "=r"(e.x), "=r"(e.y) : "r"(qb + lane8) : "memory");
        asm volatile("ld.shared.v2.u32 {%0,%1}, [%2];" : "=r"(r0.x), "=r"(r0.y) : "r"(qb + lane8 + take * 8) : "memory");
        qt -= take * 8;
        const bool more = qt - qb > 256;
        if (more) asm volatile("ld.shared.v2.u32 {%0,%1}, [%2];" : "=r"(r1.x), "=r"(r1.y) : "r"(qb + lane8 + take * 8 + 256) : "memory");
        __syncwarp();
        if (qb + lane8 < qt) asm volatile("st.shared.v2.u32 [%0], {%1,%2};" ::"r"(qb + lane8), "r"(r0.x), "r"(r0.y) : "memory");
        if (more && qb + lane8 + 256 < qt) asm volatile("st.shared.v2.u32 [%0], {%1,%2};" ::"r"(qb + lane8 + 256), "r"(r1.x), "r"(r1.y) : "memory");
        PElem el;
        el.r2 = 0;
        if (lane8 < take * 8) {
            p_bin(c, el, e.x & 0xffffffu, e.y & 0xffffffu, prmt(e.x, e.y, 0x0073), 0x5410);
            p_rank(el);
            p_store(el);
        }
        push(el.r2 >= KS * 2, e.x, e.y);
    }
};

__device__ __forceinline__ void p_filler(const Prm& p, int q, int w) {
    PFill F;
    const int lane = threadIdx.x & 31;
    F.lt = __shfl_sync(0xffffffffu, (1u << lane) - 1u, lane);
    F.qb = F.qt = SB + P_Q + w * (QN * 8); F.nxt = (q % GR) << 16;
    F.f2 = __shfl_sync(0xffffffffu, __bfloat16_as_ushort(p.freq[0]) * 0x10001u, 0);
    constexpr int cstep = NP * CPS;
    const int NS = p.NS, cend = p.T >> 7;
    uint32_t ch = q * CPS + w;
    PIn x0, x1, x2;
    p_fetch(p, x0, ch, lane); p_fetch(p, x1, ch + cstep, lane);
    PROF_DECL
    const int nch = (cend - (int)ch + cstep - 1) / cstep;
    int n = 0;
#pragma unroll 1
    for (; n + 3 <= nch; n += 3) {
        PROF(1); F.begin(); PROF(0); p_fetch(p, x2, ch + 2 * cstep, lane); F.chunk(x0); F.end();
        p_fetch(p, x0, ch + 3 * cstep, lane); PROF(1); F.begin(); PROF(0); F.chunk(x1); F.end();
        p_fetch(p, x1, ch + 4 * cstep, lane); PROF(1); F.begin(); PROF(0); F.chunk(x2); F.end();
        ch += 3 * cstep;
    }
    PROF_END;
#pragma unroll 1
    for (; n < nch; n++) {
        F.begin(); F.chunk(x0); F.end();
        x0 = x1;
    }
    if (q == 0 && w < 4) {
        int t = cend * 128 + w * 32 + lane;
        bool f = t < p.T;
        uint32_t i = 0, o = 0, x = 0;
        if (f) { i = p.idx_in[t]; o = p.idx_out[t]; asm("mul.rn.bf16x2 %0, %1, %2;" : "=r"(x) : "r"((uint32_t)__bfloat16_as_ushort(p.angle[t]) << 16), "r"(F.f2)); }
        F.push_checked(f, i, o, cos2_slow(x & 0xffff0000u));
    }
#pragma unroll 1
    for (; n <= NS + GR; n++) {
        F.begin();
        for (uint32_t nq = (F.qt - F.qb) >> 3; nq > 0;) { uint32_t take = min(nq, 32u); F.retry(take); nq -= take; }
        F.end();
    }
    if (F.qt != F.qb) st_relaxed(&g_ctl.bad, 1);
}

__device__ __forceinline__ void p_flusher(const Prm& p, unsigned char* ring, uint32_t pagebits, int q, int f) {
    const int lane = threadIdx.x & 31;
    const uint32_t bar = SB + P_BAR;
    const int NS = p.NS, NT = NS + 2 * GR;
    const uint32_t wto = lane < NCP ? OFF_REL + lane * 4 : OFF_RDY + (lane % 6) * 4;
    const uint32_t pfo = OFF_PF + (lane / 6) * 32 + (lane & 1) * 16 + ((lane % 6) >> 1) * 4;
    const uint32_t pfc = (lane >> 1) * 6 + (lane & 1);
    PROF_DECL
#pragma unroll 1
    for (int n0 = f * FB; n0 < NT; n0 += NF * FB) {
      uint32_t pw[FB], po[FB]; bool fence = false;
#pragma unroll
      for (int jf = 0; jf < FB; jf++) {
        const int n = n0 + jf;
        const uint32_t buf = (n + q % GR) % NBUF, ph = ((n + q % GR) / NBUF) & 1;
        const uint32_t h = n >> 1, lap = h / RB;
        const uint32_t qb = q_base(q, pagebits) ^ (((n + q) & 1) << 12);
        const uint32_t ba = qb ^ slot_off(h % RA) ^ R_A, bb = qb ^ slot_off(h % RB);
        if (h >= RA && !DEV_FREE)
            wait_all_ge(ring + ((lane < NCP ? bb : qb ^ slot_off((h - RA) % RB)) ^ wto), lane < NCP ? lap : ((h - RA) / RB + 1) << 1);
        PROF(0);
        if (n <= NS + GR) mbar_wait(bar + buf * 8, ph);
        else { int nl = NS + GR + q % GR; mbar_wait(bar + (nl % NBUF) * 8, (nl / NBUF) & 1); }
        PROF(1);
        uint32_t* cnt = (uint32_t*)(smem + P_CNT) + buf * NB;
        bool any = true;
        if (n >= NS) any = __any_sync(0xffffffffu, lane < NCP && (cnt[lane] | cnt[NCP + lane] | cnt[2 * NCP + lane]));
        if (any && elect_one()) {
            asm volatile("fence.proxy.async.shared::cta;" ::: "memory");
#pragma unroll
            for (int k = 0; k < 9; k++) {
                const int u = k < 6 ? k >> 1 : k - 6, hi = k < 6 && (k & 1);
                const uint32_t soff = k < 6 ? P_A + (u * NCP + hi * 8) * (KS * 4) + buf * (NB * KS * 4) : P_B + u * (NCP * KS * 2) + buf * (NB * KS * 2);
                asm volatile("cp.async.bulk.global.shared::cta.bulk_group [%0], [%1], %2;"
                             ::"l"(ring + (k < 6 ? ba : bb ^ R_B) + (u * R_UNIT + hi * 0x40000)), "r"(SB + soff),
                               "r"(k < 6 ? (hi ? NCP - 8 : 8) * (KS * 4) : NCP * KS * 2) : "memory");
            }
            asm volatile("cp.async.bulk.commit_group;" ::: "memory");
        }
        __syncwarp();
        uint32_t wm = ((lap + 1) << 22) | ((uint32_t)any << 21);
        if (lane < NCP) {
#pragma unroll
            for (int u = 0; u < 3; u++) wm |= min(cnt[pfc + 2 * u] >> 1, (uint32_t)KS) << (7 * u);
        }
        __syncwarp();
        if (lane < NB / 2) ((uint2*)cnt)[lane] = make_uint2(0, 0);
        PROF(3);
        asm volatile("cp.async.bulk.wait_group 0;" ::: "memory");
        __syncwarp();
        PROF(2);
        if (lane == 0) mbar_arrive(bar + (NBUF + buf) * 8);
        pw[jf] = wm; po[jf] = bb ^ pfo; fence |= any;
      }
      if (fence) fence_release();
      PROF(4);
#pragma unroll
      for (int jf = 0; jf < FB; jf++) if (lane < NCP) st_relaxed(ring + po[jf], pw[jf]);
    }
    PROF_END;
}
__device__ __forceinline__ void p_cleanup(unsigned char* ring, int q) {
    const int k = threadIdx.x / 24;
    if (k < 2 * RB) *(uint4*)(ring + ((q << 20) ^ ((k & 1) << 12) ^ slot_off(k >> 1) ^ OFF_PF) + (threadIdx.x % 24) * 16) = make_uint4(0, 0, 0, 0);
}

__device__ __forceinline__ void m_role(const Prm& p, unsigned char* ring, int X, int id) {
    const int tid = threadIdx.x, lane = tid & 31, w = __shfl_sync(0xffffffffu, tid >> 5, 0);
    const int ib = id >> 1, ty = id & 1;
    float* scs = (float*)(smem + S_MISC);
    if (w == 0) {
        const uint32_t bar = SB + S_AUX;
        if (lane == 0) mbar_init(bar, 1);
        wait_ge(&g_ctl.pieces_done, NPC);
        fence_acquire();
        if (lane == 0) {
            asm volatile("fence.proxy.async.global;" ::: "memory");
            asm volatile("fence.proxy.async.shared::cta;" ::: "memory");
            asm volatile("mbarrier.arrive.expect_tx.shared.b64 _, [%0], %1;" ::"r"(bar), "r"(ROWS_I * 4) : "memory");
            constexpr uint32_t PART = (ROWS_I * 4 / 8 + 127) / 128 * 128;
            for (uint32_t o = 0; o < ROWS_I * 4; o += PART)
                asm volatile("cp.async.bulk.shared::cluster.global.mbarrier::complete_tx::bytes [%0], [%1], %2, [%3];"
                             ::"r"(SB + o), "l"((const char*)(g_md[ty] + ib * ROWS_I) + o), "r"(min(PART, ROWS_I * 4 - o)), "r"(bar) : "memory");
        }
        __syncwarp();
            float sc[4]; bool bad;
        get_scales(p, sc, bad);
            if (bad) { st_relaxed(&g_ctl.bad, 1); sc[0] = sc[1] = sc[2] = sc[3] = 0.f; }
        int it = 0; uint32_t pb;
        while (!((pb = ld_relaxed(&g_ctl.pagebits)) >> 31)) backoff(it);
        if (lane == 0) { scs[0] = sc[0]; scs[1] = sc[1]; scs[2] = sc[2]; scs[3] = sc[3]; ((uint32_t*)scs)[4] = X ? ~pb : pb; ((uint32_t*)scs)[5] = bad; }
        mbar_wait(bar, 0);
    }
    __syncthreads();
    if (((uint32_t*)scs)[5]) {
        for (int k = tid; k < (int)ROWS_I; k += THREADS) ((uint32_t*)smem)[k] = 0;
        __syncthreads();
    }
    const uint32_t NT = p.NS + 2 * GR;
    if (w >= MW) return;
    const uint32_t pagebits = ((uint32_t*)scs)[4];
    const int half = lane >> 4, k4 = (lane & 15) * 4;
    const float s_lo = scs[2 * ty], s_hi = scs[2 * ty + 1];
    const float MAG_LO = 12582912.f, MAG_HI = 12582912.f - 19264.f;
    const int il = ib / NG, gi = (ib % NG) * 2 + X;
    const uint32_t a_off = R_A + il * R_UNIT + lane * 16, v_off = ty * R_V1 + il * R_UNIT + lane * 16;
    const uint32_t f_off = OFF_PF + il * 32 + half * 16, r_off = OFF_REL + (lane % NCP) * 4;
    const uint32_t j = w % (NP / GR);
    PROF_DECL
#pragma unroll 1
    for (uint32_t n = w / (NP / GR); n < NT; n += MW / (NP / GR)) {
        const uint32_t q = ((gi - n) & (GR - 1)) + GR * j, h = n >> 1;
        const uint32_t qb = q_base(q, pagebits), bb = qb ^ slot_off(h % RB);
        const uint32_t tag = (h / RB + 1) << 22;
        uint4 cw; int it = 0;
        while (true) {
            cw = ld_relaxed4(ring + (bb ^ f_off));
            if (__all_sync(0xffffffffu, min(min(cw.x, cw.y), cw.z) >= tag)) break;
            if (DEV_FREE) { cw.x = (cw.x & 1) + (63 | 57 << 7 | 50 << 14 | 1 << 21); cw.y = (cw.y & 1) + (53 | 61 << 7 | 57 << 14); cw.z = (cw.z & 1) + (59 | 52 << 7 | 57 << 14); break; }
            backoff(it);
        }
        PROF(0);
        if (__any_sync(0xffffffffu, cw.x & (1u << 21))) {
            const uint32_t oa = qb ^ slot_off(h % RA) ^ a_off;
            const unsigned char* pa = ring + oa;
            const unsigned long long sh = p.s_ring + (q >> 1);
            unsigned char* pv = ring + (qb ^ slot_off(h % RV) ^ v_off);
            const uint32_t hv = h + RB - RV;
            const unsigned char* prel = ring + (qb ^ slot_off(hv % RB) ^ r_off);
            const uint32_t rel = ld_relaxed(prel);
            const uint32_t vlap = h / RV;
            const float mag_lo0 = MAG_LO + (float)(8192 + (vlap & 3) * 16384), mag_hi0 = MAG_HI + (float)(8192 + ((vlap >> 2) & 3) * 16384);
            uint4 a[9];
#define M_LOAD(ps) do { if (M_SULD) suld4(a[ps], sh, (oa & 0x1fffff) + (ps) * 512 + ((ps) < 4 ? 0 : R_HI)); \
                        else a[ps] = ld_relaxed4(pa + (ps) * 512 + ((ps) < 4 ? 0 : R_HI)); } while (0)
#pragma unroll
            for (int ps = 0; ps < MPF; ps++) M_LOAD(ps);
            if (!__all_sync(0xffffffffu, rel >= hv / RB) && !DEV_FREE) wait_all_ge(prel, hv / RB);
            PROF(3);
#pragma unroll
            for (int ps = 0; ps < 9; ps++) {
                const int rem = (int)(((ps < 3 ? cw.x : ps < 6 ? cw.y : cw.z) >> (7 * (ps % 3))) & 0x7f) - k4;
                uint32_t aw[4] = {a[ps].x, a[ps].y, a[ps].z, a[ps].w}, mv[4], vw[4];
#pragma unroll
                for (int e = 0; e < 4; e++) { mv[e] = 0; lds_lt(mv[e], __dp2a_lo(aw[e], 4u, (uint32_t)SB), e, rem); }
#pragma unroll
                for (int e = 0; e < 4; e++) {
                    float c = bf_hi(aw[e]);
                    float lo = fmaf(bf_lo(mv[e]), c * s_lo, e ? MAG_LO : mag_lo0), hi = fmaf(bf_hi(mv[e]), c * s_hi, e ? MAG_HI : mag_hi0);
                    vw[e] = (__float_as_uint(hi) << 16) + __float_as_uint(lo);
                }
                asm volatile("st.global.v4.u32 [%0], {%1,%2,%3,%4};" ::"l"(pv + ps * 512 + (ps < 4 ? 0 : R_HI)), "r"(vw[0]), "r"(vw[1]), "r"(vw[2]), "r"(vw[3]) : "memory");
                if (ps + MPF < 9) M_LOAD(ps + MPF);
            }
            if (vlap == 0 || n >= p.NS) fence_release();
        }
        st_lane0(ring + (bb ^ (OFF_RDY + (2 * il + ty) * 4)), cw.x >> 21, lane);
        PROF(1);
    }
    PROF_END;
}

__device__ __noinline__ void c_wrap(uint32_t row, int par, uint32_t old, uint32_t w) {
    const uint32_t nw = old + w, ov = ~(old ^ w) & (old ^ nw);
    int d = 0;
    if (ov & 0x8000u) d += (w & 0x8000u) ? -1 : 1;
    if (ov & 0x80000000u) d += (w & 0x80000000u) ? -16 : 16;
    if (d != 0) {
        uint32_t c;
        asm volatile("atom.shared.add.u32 %0, [%1], %2;" : "=r"(c) : "r"(SB + C_WRAP + row * 4), "r"(d << (8 * par)) : "memory");
        c = (c >> (8 * par)) + d;
        if (((c + 1) & 0xe) == 0 || ((c + 16) & 0xe0) == 0) st_relaxed(&g_ctl.bad, 1);
    }
}

#define CGRP 6
struct CTask { uint4 v[3]; uint2 b[3]; };
struct CWork {
    unsigned char* ring; unsigned long long sh;
    uint32_t v_off, b_off, f_off, r_off, acc;
    uint32_t lap1, sv, sb, vtag, fw;
    int lane, dev_free;
    template <int ODD> __device__ __forceinline__ bool issue(CTask& t) {
        if (!__all_sync(0xffffffffu, fw >= 2 * lap1)) {
            int it = 0;
            do {
                if (dev_free) { fw = 1; break; }
                backoff(it);
                fw = ld_relaxed(ring + (f_off ^ slot_off(sb) ^ (ODD << 20)));
            } while (!__all_sync(0xffffffffu, fw >= 2 * lap1));
        }
        const bool data = __any_sync(0xffffffffu, fw & 1);
        if (data) {
            const uint32_t ov = v_off ^ slot_off(sv) ^ (ODD << 20);
            const unsigned char* pv = ring + ov;
            const unsigned char* pb = ring + (b_off ^ slot_off(sb) ^ (ODD << 20));
#pragma unroll
            for (int ps = 0; ps < 3; ps++) {
                if (ps < C_SULD) suld4(t.v[ps], sh, (ov & 0x1fffff) + ps * R_UNIT);
                else t.v[ps] = ld_relaxed4(pv + ps * R_UNIT);
                t.b[ps] = ld_relaxed2(pb + ps * R_UNIT);
            }
        }
        fw = ld_relaxed(ring + (f_off ^ slot_off(ODD ? (sb + 1 == RB ? 0 : sb + 1) : sb) ^ (!ODD << 20)));
        return data;
    }
    template <int ODD> __device__ __forceinline__ void arrive(CTask& t, bool data) {
        if (data) {
            int it = 0;
            while (__any_sync(0xffffffffu, (((t.v[0].x ^ vtag) | (t.v[1].x ^ vtag) | (t.v[2].x ^ vtag)) & 0xc000c000u) | ((t.b[0].x | t.b[1].x | t.b[2].x) & 0x8000u))) {
                if (dev_free) { for (int ps = 0; ps < 3; ps++) t.v[ps].x = (t.v[ps].x & 0x3fff3fffu) | (vtag & 0xc000c000u); break; }
                if (++it > SPIN_MAX) __trap();
#pragma unroll
                for (int ps = 0; ps < 3; ps++) t.v[ps] = ld_relaxed4(ring + (v_off ^ slot_off(sv) ^ (ODD << 20)) + ps * R_UNIT);
            }
#pragma unroll
            for (int ps = 0; ps < 3; ps++) t.v[ps].x -= vtag;
        }
        st_lane0(ring + (r_off ^ slot_off(sb) ^ (ODD << 20)), lap1, lane);
        if (ODD) {
            if (++sv == RV) { sv = 0; vtag += 0x4000u; if (vtag & 0x10000u) vtag += 0x3fff0000u; }
            if (++sb == RB) { sb = 0; lap1++; }
        }
    }
    __device__ __forceinline__ void add(const CTask& t, bool data) {
        if (!data) return;
        const uint32_t vw[12] = {t.v[0].x, t.v[0].y, t.v[0].z, t.v[0].w, t.v[1].x, t.v[1].y, t.v[1].z, t.v[1].w, t.v[2].x, t.v[2].y, t.v[2].z, t.v[2].w};
        const uint32_t bw[6] = {t.b[0].x, t.b[0].y, t.b[1].x, t.b[1].y, t.b[2].x, t.b[2].y};
#pragma unroll
        for (int g = 0; g < 12; g += CGRP) {
            uint32_t old[CGRP], ov = 0;
#pragma unroll
            for (int e = g; e < g + CGRP; e++)
                asm volatile("atom.shared.add.u32 %0, [%1], %2;" : "=r"(old[e - g]) : "r"((e & 1) ? __dp2a_hi(bw[e >> 1], 0x08000008u, acc) : __dp2a_lo(bw[e >> 1], 0x08000008u, acc)), "r"(vw[e]) : "memory");
#pragma unroll
            for (int e = g; e < g + CGRP; e++) ov |= ~(old[e - g] ^ vw[e]) & (old[e - g] ^ (old[e - g] + vw[e]));
            if (__any_sync(0xffffffffu, ov & 0x80008000u)) {
#pragma unroll
                for (int e = g; e < g + CGRP; e++) c_wrap((e & 1) ? bw[e >> 1] >> 16 : bw[e >> 1] & 0xffffu, lane >> 4, old[e - g], vw[e]);
            }
        }
    }
};

__device__ __forceinline__ void c_role(const Prm& p, unsigned char* ring, int X, int c) {
    const int tid = threadIdx.x, lane = tid & 31, w = __shfl_sync(0xffffffffu, tid >> 5, 0);
    uint32_t* misc = (uint32_t*)(smem + S_MISC);
    Wts* wt = (Wts*)(smem + S_AUX);
    load_wts(p, wt);
    for (int k = tid; k < C_WRAP / 16; k += THREADS) ((uint4*)smem)[k] = make_uint4(0, 0, 0, 0);
    if (tid == 0) misc[6] = TAB_N;
    __syncthreads();
    if (w == 0) {
        float sc[4]; bool bad;
        wait_ge(&g_ctl.pieces_done, NPC);
        fence_acquire();
        get_scales(p, sc, bad);
        const float s = (lane & 2) ? ((lane & 1) ? sc[3] : sc[2]) : ((lane & 1) ? sc[1] : sc[0]);
        wt->ws[lane] *= s > 0.f ? 1.f / s : 0.f;
        int it = 0; uint32_t pb;
        while (!((pb = ld_relaxed(&g_ctl.pagebits)) >> 31)) backoff(it);
        misc[4] = X ? ~pb : pb;
    } else {
        const int r0 = (X * NCP + c) * ROWS_O, nr = min((int)ROWS_O, p.E - r0);
#pragma unroll 4
        for (int r = tid - 32; r < (int)ROWS_O / 2; r += THREADS - 32) {
            const uint32_t d2 = 2 * r < nr ? __ldg((const uint32_t*)(p.dist + r0) + r) : TAB_LO * 0x10001u;
            uint32_t e[2] = {(d2 & 0xffff) - TAB_LO, (d2 >> 16) - TAB_LO};
#pragma unroll
            for (int k = 0; k < 2; k++)
                if (e[k] >= TAB_N) {
                    const uint32_t d = e[k] + TAB_LO;
                    if ((d & 0x7f80) == 0x7f80) st_relaxed(&g_ctl.bad, 1);
                    e[k] = min(atomicAdd(&misc[6], 1u), 0xffffu);
                    if (e[k] < TAB_N + TAB_X) ((uint32_t*)(smem + C_TAB))[e[k] * 4] = d;
                }
            ((uint2*)(smem + C_WRAP))[r] = make_uint2(e[0] << 16 | 0x8888u, e[1] << 16 | 0x8888u);
        }
    }
    __syncthreads();
    if (w >= NP / 2) {
        const int nt = min(misc[6], (uint32_t)(TAB_N + TAB_X));
        for (int k = tid - NP * 16; k < nt; k += THREADS - NP * 16)
            ((uint4*)(smem + C_TAB))[k] = radial_bf16(wt, k < TAB_N ? TAB_LO + k : ((uint32_t*)(smem + C_TAB))[k * 4]);
        if (tid == THREADS - 1 && !DEV_FREE) {
            const uint32_t h = p.NS >> 1;
            const unsigned char* f = ring + (q_base(X, misc[4]) ^ slot_off(h % RB) ^ (OFF_REL + c * 4));
            for (int it = 0; ld_relaxed(f) < h / RB; it++) { __nanosleep(2000); if (it > SPIN_MAX) __trap(); }
            const int r0 = (X * NCP + c) * ROWS_O, nr = min((int)ROWS_O, p.E - r0);
            if (nr > 0) asm volatile("cp.async.bulk.prefetch.L2.global [%0], %1;" ::"l"(p.m + r0), "r"(nr * 8) : "memory");
        }
    }
    const uint32_t pagebits = misc[4];
    if (w >= NP / 2) return;
    CWork W;
    const int par = lane >> 4;
    W.ring = ring; W.lane = __shfl_sync(0xffffffffu, lane, lane); W.sh = p.s_ring + w; W.dev_free = DEV_FREE;
    const uint32_t qb = q_base(2 * w + X, pagebits), k = lane & 15;
    W.acc = __shfl_sync(0xffffffffu, SB + par * 4, lane);
    W.v_off = __shfl_sync(0xffffffffu, qb ^ (par * R_V1 + (c < 8 ? 0 : R_HI) + c * 256 + k * 16), lane);
    W.b_off = __shfl_sync(0xffffffffu, qb ^ (R_B + c * 128 + k * 8), lane);
    W.f_off = __shfl_sync(0xffffffffu, qb ^ (OFF_RDY + (lane % 6) * 4), lane);
    W.r_off = qb ^ (OFF_REL + c * 4);
    W.lap1 = 1; W.sv = W.sb = W.fw = 0; W.vtag = 0x20002000u;
    const uint32_t NT = p.NS + 2 * GR;
    CTask A, B;
    PROF_DECL
    bool da = W.issue<0>(A), db;
#pragma unroll 1
    for (uint32_t n = 2;; n += 2) {
        W.arrive<0>(A, da); PROF(1); db = W.issue<1>(B); PROF(0); W.add(A, da);
        W.arrive<1>(B, db);
        if (n >= NT) break;
        PROF(1); da = W.issue<0>(A); PROF(0); W.add(B, db);
    }
    W.add(B, db);
    PROF_END;
}

__device__ __forceinline__ uint32_t bf2_mul(uint32_t a, uint32_t b) { uint32_t r; asm("mul.rn.bf16x2 %0, %1, %2;" : "=r"(r) : "r"(a), "r"(b)); return r; }
__device__ __forceinline__ uint32_t bf2_fma(uint32_t a, uint32_t b, uint32_t c) { uint32_t r; asm("fma.rn.bf16x2 %0, %1, %2, %3;" : "=r"(r) : "r"(a), "r"(b), "r"(c)); return r; }
__device__ __forceinline__ uint32_t c_agg(uint32_t a, uint32_t s, uint32_t wr, bool wrapped) {
    int x0 = (short)a, x1 = ((int)a >> 16) + ((a >> 15) & 1);
    if (wrapped) { const int w0 = (int)(wr & 15) - 8, w1 = (int)((wr >> 4) & 15) - 8; x0 += 65536 * w0; x1 += 65536 * w1 - w0; }
    return pack_bf16((float)x1 * bf_hi(s), (float)x0 * bf_lo(s));
}
__device__ __forceinline__ void c_epilogue(const Prm& p, int X, int c) {
    const int tid = threadIdx.x, lane = tid & 31;
    const Wts* wt = (const Wts*)(smem + S_AUX);
    uint32_t bw[4];
#pragma unroll
    for (int k = 0; k < 4; k++) {
        const int col = (k >> 1) * 2 + ((lane >> 2) & 1), row = (k & 1) * 2;
        bw[k] = (lane >> 3) == (lane & 3) ? pack_bf16(wt->wu[(row + 1) * 4 + col], wt->wu[row * 4 + col]) : 0u;
    }
    const int r0 = (X * NCP + c) * ROWS_O, np = max(min((int)ROWS_O, p.E - r0), 0) / 2;
    const uint4* mp = (const uint4*)(p.m + r0);
    uint4* op = (uint4*)(p.out + r0);
    constexpr int EB = 5;
#pragma unroll 1
    for (int rb = tid; rb - lane < np; rb += EB * THREADS) {
        uint4 mr[EB];
#pragma unroll
        for (int k = 0; k < EB; k++) mr[k] = __ldg(mp + min(rb + k * THREADS, np - 1));
#pragma unroll
        for (int k = 0; k < EB; k++) {
            const int r = min(rb + k * THREADS, np - 1);
            const uint4 a = ((const uint4*)smem)[r];
            const uint2 wr = ((const uint2*)(smem + C_WRAP))[r];
            const uint4 t0 = ((const uint4*)(smem + C_TAB))[min(wr.x >> 16, (uint32_t)(TAB_N + TAB_X - 1))];
            const uint4 t1 = ((const uint4*)(smem + C_TAB))[min(wr.y >> 16, (uint32_t)(TAB_N + TAB_X - 1))];
            const bool wrapped = __any_sync(0xffffffffu, prmt(wr.x, wr.y, 0x5410) != 0x88888888u);
            uint32_t a0, a1, a2, a3;
            if (wrapped) { a0 = c_agg(a.x, t0.x, wr.x, true); a2 = c_agg(a.y, t0.y, wr.x >> 8, true); a1 = c_agg(a.z, t1.x, wr.y, true); a3 = c_agg(a.w, t1.y, wr.y >> 8, true); }
            else { a0 = c_agg(a.x, t0.x, 0, false); a2 = c_agg(a.y, t0.y, 0, false); a1 = c_agg(a.z, t1.x, 0, false); a3 = c_agg(a.w, t1.y, 0, false); }
            float u[8];
#pragma unroll
            for (int h = 0; h < 2; h++)
                asm("mma.sync.aligned.m16n8k16.row.col.f32.bf16.bf16.f32 {%0,%1,%2,%3}, {%4,%5,%6,%7}, {%8,%9}, {%10,%10,%10,%10};"
                    : "=f"(u[4 * h]), "=f"(u[4 * h + 1]), "=f"(u[4 * h + 2]), "=f"(u[4 * h + 3])
                    : "r"(a0), "r"(a1), "r"(a2), "r"(a3), "r"(bw[2 * h]), "r"(bw[2 * h + 1]), "f"(0.f));
            const uint4 o = make_uint4(bf2_fma(pack_bf16(u[1], u[0]), t0.z, mr[k].x), bf2_fma(pack_bf16(u[5], u[4]), t0.w, mr[k].y),
                                       bf2_fma(pack_bf16(u[3], u[2]), t1.z, mr[k].z), bf2_fma(pack_bf16(u[7], u[6]), t1.w, mr[k].w));
            if (rb + k * THREADS < np) op[r] = o;
        }
    }
    if (((const uint32_t*)(smem + S_MISC))[6] > TAB_N + TAB_X) {
        for (int r = 2 * tid; r < 2 * np; r += (r & 1) ? 2 * THREADS - 1 : 1) {
            const uint32_t wr = ((const uint32_t*)(smem + C_WRAP))[r];
            if ((wr >> 16) < TAB_N + TAB_X) continue;
            const uint4 t = radial_bf16(wt, __bfloat16_as_ushort(p.dist[r0 + r]));
            const uint2 a = ((const uint2*)smem)[r];
            const uint32_t a0 = c_agg(a.x, t.x, wr, true), a1 = c_agg(a.y, t.y, wr >> 8, true);
            const float agg[4] = {bf_lo(a0), bf_hi(a0), bf_lo(a1), bf_hi(a1)}, g[4] = {bf_lo(t.z), bf_hi(t.z), bf_lo(t.w), bf_hi(t.w)};
            p.out[r0 + r] = finish_row(wt->wu, agg, g, p.m[r0 + r]);
        }
    }
}

__device__ __forceinline__ void grid_bar(unsigned* ctr) {
    __syncthreads();
    if (threadIdx.x == 0) { fence_gpu(); red_add(ctr, 1); wait_ge(ctr, gridDim.x); fence_gpu(); }
    __syncthreads();
}
__device__ __noinline__ void fallback(const Prm& p) {
    const int gt = blockIdx.x * THREADS + threadIdx.x, gs = gridDim.x * THREADS;
    Wts* wt = (Wts*)smem;
    __syncthreads();
    load_wts(p, wt);
    for (int e = gt; e < p.E; e += gs) g_acc[e] = make_float4(0.f, 0.f, 0.f, 0.f);
    grid_bar(&g_ctl.bar[0]);
    const float f = __bfloat162float(p.freq[0]);
    for (int t = gt; t < p.T; t += gs) {
        uint2 r = __ldg(p.m + p.idx_in[t]);
        float c = rbf16(cosf(rbf16(f * __bfloat162float(p.angle[t]))));
        asm volatile("red.global.add.v4.f32 [%0], {%1,%2,%3,%4};" ::"l"(g_acc + p.idx_out[t]), "f"(bf_lo(r.x) * c),
                     "f"(bf_hi(r.x) * c), "f"(bf_lo(r.y) * c), "f"(bf_hi(r.y) * c) : "memory");
    }
    grid_bar(&g_ctl.bar[1]);
    for (int e = gt; e < p.E; e += gs) {
        float4 a4 = __ldcg(g_acc + e);
        float a[4] = {a4.x, a4.y, a4.z, a4.w}, s[4], g[4];
        radial(wt, __bfloat162float(p.dist[e]), s, g);
        float agg[4];
#pragma unroll
        for (int j = 0; j < 4; j++) agg[j] = s[j] * (a[0] * wt->wd[j] + a[1] * wt->wd[4 + j] + a[2] * wt->wd[8 + j] + a[3] * wt->wd[12 + j]);
        p.out[e] = finish_row(wt->wu, agg, g, p.m[e]);
    }
}

__global__ void __launch_bounds__(THREADS, 1) gemnet_kernel(const __grid_constant__ Prm p) {
    const int tid = threadIdx.x, lane = tid & 31, w = __shfl_sync(0xffffffffu, tid >> 5, 0);
    uint32_t* misc = (uint32_t*)(smem + S_MISC);
    bool run_fallback = true;
    if (!p.force_bad && __cvta_generic_to_shared(smem) == SB) {
        unsigned char* const ring = p.ring;
        uint32_t smid; asm("mov.u32 %0, %%smid;" : "=r"(smid));
        const int cls = smid < NM ? 0 : (smid < NM + NP - 4 || (smid >= 124 && smid < 128)) ? 2 : 1;
        if (lane == 0) {
            if (w < 2 && (cls != 2 || blockIdx.x == 0)) misc[16 + w] = probe(ring + OFF_PROBE + w * 4096 + ((blockIdx.x >> 7) << 20) + (blockIdx.x & 127) * 32);
            else if (blockIdx.x == 0 && w <= NPAGES) misc[16 + w] = probe(ring + ((size_t)(w - 1) << 21) + OFF_PROBE);
        }
        float wd[16];
        if (cls != 2 || blockIdx.x == 0) __syncthreads();
        if (tid == 0) {
            int pool = cls == 2 ? 4 : cls * 2 + (misc[16] > misc[17]), id = 0;
            for (int k = 0; k < 7; k++) {
                int cap = pool < 2 ? NMP : pool < 4 ? NCP : NP;
                id = atomicAdd(&g_ctl.ticket[pool], 1);
                if (id < cap) break;
                pool = k == 0 ? (pool == 4 ? 0 : pool ^ 1) : k - 1;
            }
            misc[8] = pool; misc[9] = id;
        }
        if (blockIdx.x == 0 && tid == 32) {
            uint32_t pb = 0x80000000u;
            for (int k = 1; k < NPAGES; k++) pb |= (uint32_t)((2 * misc[17 + k] > misc[16] + misc[17]) != (misc[16] > misc[17])) << k;
            st_relaxed(&g_ctl.pagebits, pb);
        }
#pragma unroll
        for (int k = 0; k < 16; k++) wd[k] = __bfloat162float(p.w_down[k]);
        __syncthreads();
        const int pool = misc[8], id = misc[9];
        __syncthreads();
        if (pool != 4) down_piece(p, pool < 2 ? pool * NMP + id : NM + (pool - 2) * NCP + id, wd);
        if (DEV_FREE && !(DEV_FREE & (pool == 4 ? 1 : pool < 2 ? 2 : 4))) {
        } else if (pool == 4) {
            for (int k = tid; k < S_MISC / 16; k += THREADS) {
                const uint32_t z = k >= P_B / 16 && k < P_Q / 16 ? (k & 7) * 0x20002u : 0u, y = z + (k >= P_B / 16 && k < P_Q / 16 ? 0x10001u : 0u);
                ((uint4*)smem)[k] = make_uint4(z, z, y, y);
            }
            __syncthreads();
            if (tid < 2 * NBUF) {
                const uint32_t a = __cvta_generic_to_shared(smem + P_BAR) + tid * 8, cnt = tid < NBUF ? CPS : 1;
                mbar_init(a, cnt);
                if (tid % NBUF < id % GR) asm volatile("mbarrier.arrive.shared.b64 _, [%0], %1;" ::"r"(a), "r"(cnt) : "memory");
            }
            __syncthreads();
            if (w < CPS) p_filler(p, id, w);
            else if (w < CPS + NF) {
                int it = 0; uint32_t pb;
                while (!((pb = ld_relaxed(&g_ctl.pagebits)) >> 31)) backoff(it);
                p_flusher(p, ring, __shfl_sync(0xffffffffu, pb, 0), id, w - CPS);
            }
        } else if (pool < 2) {
            m_role(p, ring, pool, id);
        } else {
            c_role(p, ring, pool - 2, id);
        }
        __syncthreads();
        if (tid == 0) { fence_gpu(); red_add(&g_ctl.fin, 1); }
        if ((pool == 2 || pool == 3) && !DEV_FREE) c_epilogue(p, pool - 2, id);
        if (tid == 0) { wait_ge(&g_ctl.fin, NCTA); fence_gpu(); misc[10] = ld_relaxed(&g_ctl.bad); }
        __syncthreads();
        if (pool == 4) p_cleanup(ring, id);
        run_fallback = misc[10] && !DEV_FREE;
    }
    if (run_fallback) fallback(p);
    if (tid == 0) {
        fence_gpu();
        if (atomicAdd(&g_ctl.exited, 1) == gridDim.x - 1) {
            uint32_t* c = (uint32_t*)&g_ctl;
            for (int k = 0; k < 32; k++) c[k] = 0;
        }
    }
}

cudaTextureObject_t make_tex(const void* ptr, size_t bytes, int words) {
    cudaResourceDesc rd = {};
    rd.resType = cudaResourceTypeLinear;
    rd.res.linear.devPtr = (void*)ptr;
    rd.res.linear.desc = words == 4 ? cudaCreateChannelDesc<uint4>() : cudaCreateChannelDesc<uint2>();
    rd.res.linear.sizeInBytes = bytes;
    cudaTextureDesc td = {};
    td.readMode = cudaReadModeElementType;
    cudaTextureObject_t t = 0;
    if (cudaCreateTextureObject(&t, &rd, &td, nullptr) != cudaSuccess) { cudaGetLastError(); return 0; }
    return t;
}

cudaTextureObject_t make_windows(const void* ptr, size_t bytes) {
    cudaTextureObject_t first = 0;
    for (size_t o = 0, k = 0; o < bytes; o += 2u << 20, k++) {
        cudaTextureObject_t t = make_tex((const char*)ptr + o, bytes - o < (2u << 20) ? bytes - o : (2u << 20), 4);
        if (k == 0) first = t;
        if (!t || t != first + k) return 0;
    }
    return first;
}

}

extern "C" void kernel_launch(void* const* d_in, const int* in_sizes, int n_in, void* d_out, int out_size) {
    static Prm p = {};
    static int grid = 0;
    const int E = in_sizes[3], T = in_sizes[1];
    if (grid == 0 || p.idx_in != d_in[1] || p.idx_out != d_in[2] || p.angle != d_in[4] || p.E != E || p.T != T) {
        int dev = 0, sms = 0;
        cudaGetDevice(&dev);
        cudaDeviceGetAttribute(&sms, cudaDevAttrMultiProcessorCount, dev);
        cudaFuncSetAttribute(gemnet_kernel, cudaFuncAttributeMaxDynamicSharedMemorySize, SMEM_BYTES);
        p.E = E; p.T = T;
        p.NS = ((T / 128 + NP * CPS - 1) / (NP * CPS) + (FB > 2 ? 3 : 1)) & (FB > 2 ? ~3 : ~1);
        void* rp = nullptr;
        cudaGetSymbolAddress(&rp, g_ring);
        p.ring = (unsigned char*)(((uintptr_t)rp + ((2u << 20) - 1)) & ~(uintptr_t)((2u << 20) - 1));
        bool fast = sms >= NCTA && E <= (int)FAST_E && (E & 1) == 0 && T >= 128 && T <= (1 << 29);
        if (fast) {
            p.t_in = make_tex(d_in[1], (size_t)(T / 128) * 512, 4);
            p.t_out = make_tex(d_in[2], (size_t)(T / 128) * 512, 4);
            p.t_ang = make_tex(d_in[4], (size_t)(T / 128) * 256, 2);
            fast = p.t_in && p.t_out && p.t_ang;
            if (P_SULD) { p.s_in = make_windows(d_in[1], (size_t)(T / 128) * 512); p.s_out = make_windows(d_in[2], (size_t)(T / 128) * 512); fast = fast && p.s_in && p.s_out; }
            if (M_SULD || C_SULD) { p.s_ring = make_windows(p.ring, RING_BYTES); fast = fast && p.s_ring; }
        }
        p.force_bad = !fast;
        grid = fast ? NCTA : sms;
    }
    p.m = (const uint2*)d_in[0];
    p.idx_in = (const int*)d_in[1];
    p.idx_out = (const int*)d_in[2];
    p.dist = (const __nv_bfloat16*)d_in[3];
    p.angle = (const __nv_bfloat16*)d_in[4];
    p.centers = (const __nv_bfloat16*)d_in[5];
    p.freq = (const __nv_bfloat16*)d_in[6];
    p.w_rbf = (const __nv_bfloat16*)d_in[7];
    p.w_sbf = (const __nv_bfloat16*)d_in[8];
    p.w_down = (const __nv_bfloat16*)d_in[9];
    p.w_up = (const __nv_bfloat16*)d_in[10];
    p.out = (uint2*)d_out;
    gemnet_kernel<<<grid, THREADS, SMEM_BYTES>>>(p);
}
```

```cpp
#include <cuda_runtime.h>
#include <cuda_bf16.h>
#include <stdint.h>

namespace {

constexpr int NI = 12;
constexpr int UN = 3;
constexpr int NG = NI / UN;
constexpr int GR = 2 * NG;
constexpr int NCP = 18;
constexpr int NO = 2 * NCP;
constexpr int KS = 64;
constexpr int NB = UN * NCP;
constexpr int NBUF = 10;
constexpr int NMP = 2 * NI;
constexpr int NP = 48, NM = 2 * NMP, NC = NO, NCTA = NP + NM + NC;
#define CPS_ 24
constexpr int CPS = CPS_;
constexpr int FW = 24;
#define FB_ 1
constexpr int FB = FB_;
constexpr int NF = FB > 2 ? 3 : 4;
static_assert((NF - 1) * FB < NBUF, "barrier phases");
#define RA_ 3
#define RV_ 3
#define RB_ 4
constexpr int RA = RA_, RV = RV_, RB = RB_;
constexpr int QN = 80, QTRIG = 40;
#define MW_ 18
constexpr int MW = MW_;
#define MPF_ 6
constexpr int MPF = MPF_;
constexpr int THREADS = 896, NW = THREADS / 32;
#define DEV_FREE 0
#define SLEEP_ 200

constexpr int RING_BYTES = NP << 20;
constexpr int NPAGES = RING_BYTES >> 21;
constexpr int MAX_E = 1 << 20;
constexpr int SMEM_BYTES = 232448;

constexpr int SB = 1024;

constexpr int P_CNT = 0;
constexpr int P_BAR = P_CNT + NBUF * NB * 4;
constexpr int P_TKT = P_BAR + 2 * NBUF * 8;
constexpr int P_B = (P_TKT + 128 + 127) / 128 * 128;
constexpr int P_Q = P_B + NBUF * NB * KS * 2;
constexpr int P_A = SMEM_BYTES - 256 - NBUF * NB * KS * 4;
static_assert(P_Q + FW * QN * 8 + 512 <= P_A && P_A % 128 == 0, "P smem");
constexpr int S_MISC = SMEM_BYTES - 256;
constexpr int S_AUX = S_MISC - 512;

constexpr unsigned FAST_E = 640000;
constexpr unsigned magic_of(unsigned long long d) { return (unsigned)(((1ull << 32) + d - 1) / d); }
constexpr bool magic_ok(unsigned long long d) { return (magic_of(d) * d - (1ull << 32)) * FAST_E < (1ull << 32); }
constexpr unsigned pick_rows(unsigned lo) {
    unsigned d = (lo + 3) & ~3u;
    while (!magic_ok(d)) d += 4;
    return d;
}
constexpr unsigned ROWS_I = pick_rows((FAST_E + NI - 1) / NI), ROWS_O = pick_rows((FAST_E + NO - 1) / NO);
constexpr unsigned MAG_I = magic_of(ROWS_I), MAG_O = magic_of(ROWS_O), HALF_O = ROWS_O * NCP;
constexpr int C_WRAP = ROWS_O * 8, C_TAB = ROWS_O * 12, TAB_N = 1025, TAB_LO = 0x3f80 - 1024, TAB_X = (S_AUX - C_TAB) / 16 - TAB_N;
static_assert(ROWS_I * 4 <= S_AUX && TAB_X >= 100 && ROWS_I <= 65536 && ROWS_O <= 32768, "tables");

constexpr int NPC = NM + NC;
constexpr int PC_ROWS = ((FAST_E + NPC - 1) / NPC + 3) & ~3;
struct __align__(128) Ctl {
    unsigned ticket[5];
    unsigned pagebits;
    unsigned pieces_done, unused;
    unsigned bad;
    unsigned fin;
    unsigned bar[3];
    unsigned exited;
    unsigned pad[18];
    float stat[NPC][8];
};

struct Prm {
    const uint2* m; const int* idx_in; const int* idx_out; const __nv_bfloat16* dist; const __nv_bfloat16* angle;
    const __nv_bfloat16* centers; const __nv_bfloat16* freq; const __nv_bfloat16* w_rbf; const __nv_bfloat16* w_sbf;
    const __nv_bfloat16* w_down; const __nv_bfloat16* w_up; uint2* out;
    cudaTextureObject_t t_in, t_out, t_ang;
    int E, T;
    unsigned char* ring;
    int NS;
    int force_bad;
};

__device__ __align__(128) unsigned char g_ring[RING_BYTES + (2 << 20)];
__device__ Ctl g_ctl;
__device__ float4 g_acc[MAX_E];
__device__ __align__(128) uint32_t g_md[2][NI * ROWS_I];
#define TS(k)
#define PROF_DECL
#define PROF(k)
#define PROF_END

extern __shared__ __align__(128) unsigned char smem[];

__device__ __forceinline__ float bf_lo(uint32_t w) { return __uint_as_float(w << 16); }
__device__ __forceinline__ float bf_hi(uint32_t w) { return __uint_as_float(w & 0xffff0000u); }
__device__ __forceinline__ float rbf16(float x) { return __bfloat162float(__float2bfloat16_rn(x)); }
__device__ __forceinline__ uint32_t pack_bf16(float hi, float lo) {
    uint32_t r; asm("cvt.rn.bf16x2.f32 %0, %1, %2;" : "=r"(r) : "f"(hi), "f"(lo)); return r;
}
__device__ __forceinline__ uint32_t prmt(uint32_t a, uint32_t b, uint32_t c) {
    uint32_t r; asm("prmt.b32 %0, %1, %2, %3;" : "=r"(r) : "r"(a), "r"(b), "r"(c)); return r;
}
__device__ __forceinline__ uint32_t ld_relaxed(const void* p) {
    uint32_t v; asm volatile("ld.relaxed.gpu.global.u32 %0, [%1];" : "=r"(v) : "l"(p) : "memory"); return v;
}
__device__ __forceinline__ uint2 ld_relaxed2(const void* p) {
    uint2 v; asm volatile("ld.relaxed.gpu.global.v2.u32 {%0,%1}, [%2];" : "=r"(v.x), "=r"(v.y) : "l"(p) : "memory"); return v;
}
__device__ __forceinline__ uint4 ld_relaxed4(const void* p) {
    uint4 v; asm volatile("ld.relaxed.gpu.global.v4.u32 {%0,%1,%2,%3}, [%4];" : "=r"(v.x), "=r"(v.y), "=r"(v.z), "=r"(v.w) : "l"(p) : "memory"); return v;
}
__device__ __forceinline__ void st_relaxed(void* p, uint32_t v) { asm volatile("st.relaxed.gpu.global.u32 [%0], %1;" ::"l"(p), "r"(v) : "memory"); }
__device__ __forceinline__ void st_relaxed16(void* p, uint32_t v) { asm volatile("st.relaxed.gpu.global.u16 [%0], %1;" ::"l"(p), "h"((uint16_t)v) : "memory"); }
__device__ __forceinline__ void red_add(void* p, uint32_t v) { asm volatile("red.relaxed.gpu.global.add.u32 [%0], %1;" ::"l"(p), "r"(v) : "memory"); }
__device__ __forceinline__ void fence_gpu() { asm volatile("fence.acq_rel.gpu;" ::: "memory"); }
__device__ __forceinline__ void fence_acquire() { asm volatile("fence.acquire.gpu;" ::: "memory"); }
__device__ __forceinline__ void fence_release() { asm volatile("fence.release.gpu;" ::: "memory"); }
__device__ __forceinline__ void mbar_init(uint32_t a, uint32_t n) { asm volatile("mbarrier.init.shared.b64 [%0], %1;" ::"r"(a), "r"(n) : "memory"); }
__device__ __forceinline__ void mbar_arrive(uint32_t a) { asm volatile("mbarrier.arrive.shared.b64 _, [%0];" ::"r"(a) : "memory"); }
__device__ __forceinline__ bool mbar_try(uint32_t a, uint32_t ph) {
    uint32_t ok;
    asm volatile("{.reg .pred p; mbarrier.try_wait.parity.shared.b64 p, [%1], %2, %3; selp.u32 %0, 1, 0, p;}" : "=r"(ok) : "r"(a), "r"(ph), "r"(2000) : "memory");
    return ok;
}
__device__ __forceinline__ bool mbar_test(uint32_t a, uint32_t ph) {
    uint32_t ok;
    asm volatile("{.reg .pred p; mbarrier.test_wait.parity.shared.b64 p, [%1], %2; selp.u32 %0, 1, 0, p;}" : "=r"(ok) : "r"(a), "r"(ph) : "memory");
    return ok;
}
constexpr int SPIN_MAX = 1 << 22;
__device__ __forceinline__ void mbar_wait(uint32_t a, uint32_t ph) {
    int it = 0;
    while (!mbar_try(a, ph)) { if (++it > SPIN_MAX) __trap(); }
}
__device__ __forceinline__ void backoff(int& it) { __nanosleep(SLEEP_); if (++it > SPIN_MAX) __trap(); }
__device__ __forceinline__ void wait_ge(const void* p, uint32_t v) {
    int it = 0;
    while (ld_relaxed(p) < v) backoff(it);
}

__device__ __forceinline__ bool elect_one() {
    uint32_t r; asm volatile("{.reg .pred p; elect.sync _|p, 0xffffffff; selp.u32 %0, 1, 0, p;}" : "=r"(r)); return r;
}
__device__ __forceinline__ void st_lane0(void* p, uint32_t v, int lane) {
    asm volatile("{.reg .pred p; setp.eq.s32 p, %2, 0; @p st.relaxed.gpu.global.u32 [%0], %1;}" ::"l"(p), "r"(v), "r"(lane) : "memory");
}
__device__ __forceinline__ void wait_all_ge(const void* p, uint32_t v) {
    int it = 0;
    while (!__all_sync(0xffffffffu, ld_relaxed(p) >= v)) backoff(it);
}
__device__ __forceinline__ void lds_lt(uint32_t& v, uint32_t ad, int a, int b) {
    asm volatile("{.reg .pred p; setp.lt.s32 p, %2, %3; @p ld.shared.u32 %0, [%1];}" : "+r"(v) : "r"(ad), "r"(a), "r"(b));
}

constexpr uint32_t R_V1 = 0x03000, R_A = 0x81000, R_B = 0x82000, R_UNIT = 0x4000, R_HI = 0x40000 - 8 * 256;
__device__ __forceinline__ uint32_t q_base(uint32_t q, uint32_t pagebits_x) { return (q << 20) | (((pagebits_x >> (q >> 1)) & 1u) << 12); }
__device__ __forceinline__ uint32_t slot_off(uint32_t s) { return (s << 16) | (((s + 1) & 2) << 11); }
constexpr uint32_t OFF_PF = R_B + 3 * R_UNIT, OFF_RDY = OFF_PF + 128, OFF_REL = OFF_PF + 256;
constexpr uint32_t OFF_PROBE = 3 * R_UNIT;
static_assert(RA <= 4 && RV <= 4 && RB <= 8 && RA <= RB && RV <= RB, "ring");

__device__ __forceinline__ uint32_t probe(unsigned char* p) {
    volatile uint32_t* sink = (volatile uint32_t*)(smem + S_MISC + 240);
    asm volatile("st.global.v4.u32 [%0], {%1,%1,%1,%1};" ::"l"(p), "r"(0) : "memory");
    asm volatile("st.global.v4.u32 [%0], {%1,%1,%1,%1};" ::"l"(p + 16), "r"(0) : "memory");
    uint32_t best = 0xffffffffu;
#pragma unroll 1
    for (int r = 0; r < 3; r++) {
        uint32_t t0, t1, v;
        asm volatile("mov.u32 %0, %%clock;" : "=r"(t0)::"memory");
        asm volatile("atom.relaxed.gpu.global.add.u32 %0, [%1], 1;" : "=r"(v) : "l"(p) : "memory");
        *sink = v;
        asm volatile("mov.u32 %0, %%clock;" : "=r"(t1)::"memory");
        best = min(best, t1 - t0);
    }
    return best;
}

struct Wts { float c[8], wr[32], ws[32], wd[16], wu[16]; };
__device__ __forceinline__ void load_wts(const Prm& p, Wts* w) {
    int t = threadIdx.x;
    if (t < 8) w->c[t] = __bfloat162float(p.centers[t]);
    if (t < 32) { w->wr[t] = __bfloat162float(p.w_rbf[t]); w->ws[t] = __bfloat162float(p.w_sbf[t]); }
    if (t < 16) { w->wd[t] = __bfloat162float(p.w_down[t]); w->wu[t] = __bfloat162float(p.w_up[t]); }
}
__device__ __forceinline__ void radial(const Wts* w, float d, float s[4], float g[4]) {
#pragma unroll
    for (int j = 0; j < 4; j++) s[j] = g[j] = 0.f;
#pragma unroll
    for (int r = 0; r < 8; r++) {
        float x = rbf16(d - w->c[r]);
        float b = rbf16(__expf(rbf16(-10.0f * rbf16(x * x))));
#pragma unroll
        for (int j = 0; j < 4; j++) { s[j] += b * w->ws[r * 4 + j]; g[j] += b * w->wr[r * 4 + j]; }
    }
}
__device__ __noinline__ uint4 radial_bf16(const Wts* w, uint32_t dbits) {
    float s[4], g[4];
    radial(w, __uint_as_float(dbits << 16), s, g);
    return make_uint4(pack_bf16(s[1], s[0]), pack_bf16(s[3], s[2]), pack_bf16(g[1], g[0]), pack_bf16(g[3], g[2]));
}
__device__ __forceinline__ uint2 finish_row(const float* wu, const float agg[4], const float g[4], uint2 r) {
    float o[4];
    const float mm[4] = {bf_lo(r.x), bf_hi(r.x), bf_lo(r.y), bf_hi(r.y)};
#pragma unroll
    for (int j = 0; j < 4; j++) o[j] = mm[j] + (agg[0] * wu[j] + agg[1] * wu[4 + j] + agg[2] * wu[8 + j] + agg[3] * wu[12 + j]) * g[j];
    return make_uint2(pack_bf16(o[1], o[0]), pack_bf16(o[3], o[2]));
}
__device__ __forceinline__ uint2 down_row(const float* wd, uint32_t x, uint32_t y) {
    const float a[4] = {bf_lo(x), bf_hi(x), bf_lo(y), bf_hi(y)};
    float d[4];
#pragma unroll
    for (int j = 0; j < 4; j++) d[j] = a[0] * wd[j] + a[1] * wd[4 + j] + a[2] * wd[8 + j] + a[3] * wd[12 + j];
    return make_uint2(pack_bf16(d[1], d[0]), pack_bf16(d[3], d[2]));
}

__device__ __forceinline__ void down_piece(const Prm& p, int pc, const float* wd) {
    const int tid = threadIdx.x, lane = tid & 31, w = tid >> 5;
    const int r0 = pc * PC_ROWS / 2, nr = max(min((pc + 1) * PC_ROWS, p.E) / 2 - r0, 0);
    const uint32_t bar = SB + S_AUX + 504;
    if (tid == 0) {
        mbar_init(bar, 1);
        asm volatile("fence.proxy.async.shared::cta;" ::: "memory");
        asm volatile("mbarrier.arrive.expect_tx.shared.b64 _, [%0], %1;" ::"r"(bar), "r"(nr * 16) : "memory");
        for (int o = 0; o < nr; o += 1024)
            asm volatile("cp.async.bulk.shared::cluster.global.mbarrier::complete_tx::bytes [%0], [%1], %2, [%3];"
                         ::"r"(SB + o * 16), "l"((const uint4*)p.m + r0 + o), "r"(min(1024, nr - o) * 16), "r"(bar) : "memory");
    }
    __syncthreads();
    mbar_wait(bar, 0);
    uint32_t mx0 = 0, mx1 = 0; float ss[4] = {0.f, 0.f, 0.f, 0.f};
    for (int r = tid; r < nr; r += THREADS) {
        const uint4 v = ((const uint4*)smem)[r];
        const uint2 a = down_row(wd, v.x, v.y), b = down_row(wd, v.z, v.w);
        ((uint2*)g_md[0])[r0 + r] = make_uint2(a.x, b.x); ((uint2*)g_md[1])[r0 + r] = make_uint2(a.y, b.y);
        mx0 = __vimax3_u16x2(mx0, a.x & 0x7fff7fffu, b.x & 0x7fff7fffu); mx1 = __vimax3_u16x2(mx1, a.y & 0x7fff7fffu, b.y & 0x7fff7fffu);
        ss[0] += bf_lo(a.x) * bf_lo(a.x) + bf_lo(b.x) * bf_lo(b.x); ss[1] += bf_hi(a.x) * bf_hi(a.x) + bf_hi(b.x) * bf_hi(b.x);
        ss[2] += bf_lo(a.y) * bf_lo(a.y) + bf_lo(b.y) * bf_lo(b.y); ss[3] += bf_hi(a.y) * bf_hi(a.y) + bf_hi(b.y) * bf_hi(b.y);
    }
    uint32_t st[4] = {mx0 << 16, mx0 & 0xffff0000u, mx1 << 16, mx1 & 0xffff0000u};
    uint4* red = (uint4*)(smem + PC_ROWS * 8);
    for (int pass = 0; pass < 2; pass++) {
#pragma unroll
        for (int ch = 0; ch < 4; ch++) {
            st[ch] = __reduce_max_sync(0xffffffffu, st[ch]);
#pragma unroll
            for (int o = 16; o; o >>= 1) ss[ch] += __shfl_xor_sync(0xffffffffu, ss[ch], o);
        }
        uint4* dst = pass ? (uint4*)g_ctl.stat[pc] : red + 2 * w;
        if (lane == 0) { dst[0] = make_uint4(st[0], st[1], st[2], st[3]); dst[1] = make_uint4(__float_as_uint(ss[0]), __float_as_uint(ss[1]), __float_as_uint(ss[2]), __float_as_uint(ss[3])); }
        if (pass) break;
        __syncthreads();
        const uint4 a = lane < NW ? red[2 * lane] : make_uint4(0, 0, 0, 0), b = lane < NW ? red[2 * lane + 1] : make_uint4(0, 0, 0, 0);
        __syncthreads();
        if (w != 0) return;
        st[0] = a.x; st[1] = a.y; st[2] = a.z; st[3] = a.w;
        ss[0] = __uint_as_float(b.x); ss[1] = __uint_as_float(b.y); ss[2] = __uint_as_float(b.z); ss[3] = __uint_as_float(b.w);
    }
    if (lane == 0) { fence_release(); red_add(&g_ctl.pieces_done, 1); }
    __syncwarp();
}

__device__ __forceinline__ void get_scales(const Prm& p, float sc[4], bool& bad) {
    const int lane = threadIdx.x & 31;
    uint32_t mxb[4] = {0, 0, 0, 0};
    float ss[4] = {0.f, 0.f, 0.f, 0.f};
#pragma unroll
    for (int k = 0; k < (NPC + 31) / 32; k++) {
        if (lane + 32 * k < NPC) {
            const uint4 a = ld_relaxed4(&g_ctl.stat[lane + 32 * k][0]), b = ld_relaxed4(&g_ctl.stat[lane + 32 * k][4]);
            mxb[0] = max(mxb[0], a.x); mxb[1] = max(mxb[1], a.y); mxb[2] = max(mxb[2], a.z); mxb[3] = max(mxb[3], a.w);
            ss[0] += __uint_as_float(b.x); ss[1] += __uint_as_float(b.y); ss[2] += __uint_as_float(b.z); ss[3] += __uint_as_float(b.w);
        }
    }
    bad = false;
    const float kdeg = fminf(3.5f * sqrtf(fmaxf(0.5f * (float)p.T / (float)p.E, 1.0f)), 128.f);
#pragma unroll
    for (int ch = 0; ch < 4; ch++) {
        float mx = __uint_as_float(__reduce_max_sync(0xffffffffu, mxb[ch]));
#pragma unroll
        for (int o = 16; o; o >>= 1) ss[ch] += __shfl_xor_sync(0xffffffffu, ss[ch], o);
        float rms = sqrtf(ss[ch] / (float)p.E);
        float range = fmaxf(4.002f * mx, kdeg * rms);
        if (!(mx <= 1e15f) || !(range <= 128.f * rms) || (mx > 0.f && mx < 1e-15f)) bad = true;
        sc[ch] = range > 0.f ? 32767.f / range : 0.f;
    }
}

constexpr int PER = 40;
struct __align__(16) PTab { uint32_t e[PER][4]; };
constexpr PTab make_ptab() {
    PTab t = {};
    for (int s = 0; s < PER; s++) {
        for (int d = 0; d < GR; d++) {
            int gi = (s + d) % GR, buf = (s + d) % NBUF, X = gi & 1, g = gi >> 1;
            t.e[s][X] |= (uint32_t)(4 * UN * buf - g - 4 * X + 7) << (8 * g);
        }
        int mnew = s + GR - 1;
        t.e[s][2] = (uint32_t)(SB + P_BAR + (NBUF + mnew % NBUF) * 8) | (uint32_t)(((mnew / NBUF) & 1) ^ 1) << 31;
        t.e[s][3] = (uint32_t)(SB + P_BAR + (s % NBUF) * 8) | (uint32_t)((s + 1) % PER) << 16;
    }
    return t;
}
__constant__ PTab c_ptab = make_ptab();
constexpr int BIAS = 7 * NCP;
static_assert(NG == 4 && CPS >= FW, "group selection");

struct PCtx { uint32_t a0, a1; };
struct PElem { uint32_t b4, aw, ol, r2; };

__device__ __forceinline__ void p_bin(const PCtx& c, PElem& e, uint32_t i, uint32_t o, uint32_t cw, uint32_t csel) {
    uint32_t ib = __umulhi(i, MAG_I), ob = __umulhi(o, MAG_O), sel = ib & 3;
    asm("{.reg .pred p; setp.ge.u32 p, %1, %2; @p add.u32 %0, %0, 4;}" : "+r"(sel) : "r"(o), "n"(HALF_O));
    e.b4 = __dp4a(prmt(c.a0, c.a1, sel), (uint32_t)NCP, ib * NCP + ob * 4);
    e.aw = prmt(i - ib * ROWS_I, cw, csel);
    e.ol = o - ob * ROWS_O;
}
__device__ __forceinline__ void p_rank(PElem& e) {
    asm volatile("atom.shared.add.u32 %0, [%1+%2], 2;" : "=r"(e.r2) : "r"(e.b4), "n"(SB + P_CNT - BIAS) : "memory");
}
__device__ __forceinline__ void p_store(const PElem& e) {
    const uint32_t ab = e.b4 * (KS / 2) + e.r2;
    asm volatile("{.reg .pred p; setp.lt.u32 p, %4, %5; @p st.shared.u32 [%0+%6], %1; @p st.shared.u16 [%2+%7], %3;}"
                 ::"r"(ab * 2), "r"(e.aw), "r"(ab), "h"((uint16_t)e.ol), "r"(e.r2), "n"(KS * 2),
                   "n"(SB + P_A - BIAS * KS), "n"(SB + P_B - BIAS * (KS / 2)) : "memory");
}
__device__ __noinline__ uint32_t cos2_slow(uint32_t x) {
    float a = cosf(bf_lo(x)), b = cosf(bf_hi(x));
    if (!(fabsf(a + b) <= 2.f)) { st_relaxed(&g_ctl.bad, 1); a = b = 0.f; }
    return pack_bf16(b, a);
}

struct PIn { uint4 i, o; uint2 a; };
__device__ __forceinline__ void p_fetch(const Prm& p, PIn& x, uint32_t ch, uint32_t lane) {
    const int v = ch * 32 + lane;
    asm volatile("{.reg .b32 d0, d1; tex.1d.v4.u32.s32 {%0,%1,d0,d1}, [%2, {%3}];}" : "=r"(x.a.x), "=r"(x.a.y) : "l"(p.t_ang), "r"(v));
    asm volatile("tex.1d.v4.u32.s32 {%0,%1,%2,%3}, [%4, {%5}];" : "=r"(x.i.x), "=r"(x.i.y), "=r"(x.i.z), "=r"(x.i.w) : "l"(p.t_in), "r"(v));
    asm volatile("tex.1d.v4.u32.s32 {%0,%1,%2,%3}, [%4, {%5}];" : "=r"(x.o.x), "=r"(x.o.y), "=r"(x.o.z), "=r"(x.o.w) : "l"(p.t_out), "r"(v));
}

struct PFill {
    PCtx c;
    uint32_t qb, qt, lt, f2, nxt, fre;
    uint32_t q, lane;
    bool open;
    __device__ __forceinline__ void begin() { begin(nxt >> 16); }
    __device__ __forceinline__ uint32_t ticket() {
        uint32_t t;
        asm volatile("atom.shared.add.u32 %0, [%1+%2], %3;" : "=r"(t) : "r"(lane * 4), "n"(SB + P_TKT), "r"(~lt & 1) : "memory");
        return t;
    }
    __device__ __forceinline__ uint32_t use_ticket(uint32_t t) {
        t = __reduce_or_sync(0xffffffffu, t);
        begin((t / CPS + q % GR) % PER);
        return t + 2 * FW;
    }
    __device__ __forceinline__ void begin(uint32_t idx) {
        const uint2* t = (const uint2*)c_ptab.e + 2 * idx;
        const uint2 m = t[0], s = t[1];
        c.a0 = m.x; c.a1 = m.y;
        nxt = s.y; fre = s.x;
        open = mbar_test(fre & 0xffff, fre >> 31);
    }
    __device__ __forceinline__ void enter() { if (!open) mbar_wait(fre & 0xffff, fre >> 31); }
    __device__ __forceinline__ void end() {
        __syncwarp();
        asm volatile("{.reg .pred p; setp.eq.u32 p, %1, 0; @p mbarrier.arrive.shared.b64 _, [%0];}" ::"r"(nxt & 0xffff), "r"(lt) : "memory");
    }
    __device__ __forceinline__ void push(bool f, uint32_t x, uint32_t y) {
        uint32_t mask = __ballot_sync(0xffffffffu, f);
        asm volatile("{.reg .pred p; setp.ne.u32 p, %3, 0; @p st.shared.v2.u32 [%0], {%1,%2};}" ::"r"(qt + __popc(mask & lt) * 8), "r"(x), "r"(y), "r"((uint32_t)f) : "memory");
        qt += __popc(mask) * 8;
    }
    __device__ __forceinline__ void push_checked(bool f, uint32_t i, uint32_t o, uint32_t aw) {
        if (qt - qb + __popc(__ballot_sync(0xffffffffu, f)) * 8 > QN * 8) st_relaxed(&g_ctl.bad, 1);
        else push(f, prmt(i, aw, 0x6210), prmt(o, aw, 0x7210));
    }
    __device__ __forceinline__ uint32_t chunk(const PIn& x) {
        uint32_t x0, x1, c0, c1;
        asm("mul.rn.bf16x2 %0, %1, %2;" : "=r"(x0) : "r"(x.a.x), "r"(f2));
        asm("mul.rn.bf16x2 %0, %1, %2;" : "=r"(x1) : "r"(x.a.y), "r"(f2));
        asm volatile("" : "+r"(x0), "+r"(x1));
        uint32_t tk = ticket();
        c0 = pack_bf16(__cosf(bf_hi(x0)), __cosf(bf_lo(x0)));
        c1 = pack_bf16(__cosf(bf_hi(x1)), __cosf(bf_lo(x1)));
        if (__any_sync(0xffffffffu, (((x0 & 0x7fff7fffu) + 0x3e003e00u) | ((x1 & 0x7fff7fffu) + 0x3e003e00u)) & 0x80008000u)) { c0 = cos2_slow(x0); c1 = cos2_slow(x1); }
        tk = use_ticket(tk);
        PElem e0, e1, e2, e3;
        p_bin(c, e0, x.i.x, x.o.x, c0, 0x5410); p_bin(c, e1, x.i.y, x.o.y, c0, 0x7610);
        p_bin(c, e2, x.i.z, x.o.z, c1, 0x5410); p_bin(c, e3, x.i.w, x.o.w, c1, 0x7610);
        asm volatile("" : "+r"(e0.b4), "+r"(e1.b4), "+r"(e2.b4), "+r"(e3.b4));
        enter();
        p_rank(e0); p_rank(e1); p_rank(e2); p_rank(e3);
        p_store(e0); p_store(e1); p_store(e2); p_store(e3);
        const uint32_t r01 = e0.r2 | e1.r2, r23 = e2.r2 | e3.r2;
        const bool f = (r01 | r23) >= KS * 2;
        if (__any_sync(0xffffffffu, f)) {
            const bool f0 = e0.r2 >= KS * 2, f1 = e1.r2 >= KS * 2, f2_ = e2.r2 >= KS * 2, f3 = e3.r2 >= KS * 2, f01 = r01 >= KS * 2;
            uint32_t si = f01 ? (f0 ? x.i.x : x.i.y) : (f2_ ? x.i.z : x.i.w);
            uint32_t so = f01 ? (f0 ? x.o.x : x.o.y) : (f2_ ? x.o.z : x.o.w);
            uint32_t sc = f01 ? (f0 ? e0.aw : e1.aw) : (f2_ ? e2.aw : e3.aw);
            push(f, prmt(si, sc, 0x6210), prmt(so, sc, 0x7210));
            uint32_t s2 = max(max(min(e0.r2, e1.r2), min(e2.r2, e3.r2)), min(r01, r23));
            if (__any_sync(0xffffffffu, s2 >= KS * 2)) {
                push_checked(f1 && f0, x.i.y, x.o.y, e1.aw);
                push_checked(f2_ && f01, x.i.z, x.o.z, e2.aw);
                push_checked(f3 && (f01 || f2_), x.i.w, x.o.w, e3.aw);
            }
            if (qt - qb >= QTRIG * 8) {
                retry(32);
                if (qt - qb > (QN - 32) * 8) { st_relaxed(&g_ctl.bad, 1); qt = qb; }
            }
        }
        end();
        return tk;
    }
    __device__ __forceinline__ void retry(uint32_t take) {
        const uint32_t lane8 = (threadIdx.x & 31) * 8;
        uint2 e, r0, r1;
        __syncwarp();
        asm volatile("ld.shared.v2.u32 {%0,%1}, [%2];" : "=r"(e.x), "=r"(e.y) : "r"(qb + lane8) : "memory");
        asm volatile("ld.shared.v2.u32 {%0,%1}, [%2];" : "=r"(r0.x), "=r"(r0.y) : "r"(qb + lane8 + take * 8) : "memory");
        qt -= take * 8;
        const bool more = qt - qb > 256;
        if (more) asm volatile("ld.shared.v2.u32 {%0,%1}, [%2];" : "=r"(r1.x), "=r"(r1.y) : "r"(qb + lane8 + take * 8 + 256) : "memory");
        __syncwarp();
        if (qb + lane8 < qt) asm volatile("st.shared.v2.u32 [%0], {%1,%2};" ::"r"(qb + lane8), "r"(r0.x), "r"(r0.y) : "memory");
        if (more && qb + lane8 + 256 < qt) asm volatile("st.shared.v2.u32 [%0], {%1,%2};" ::"r"(qb + lane8 + 256), "r"(r1.x), "r"(r1.y) : "memory");
        PElem el;
        el.r2 = 0;
        if (lane8 < take * 8) {
            p_bin(c, el, e.x & 0xffffffu, e.y & 0xffffffu, prmt(e.x, e.y, 0x0073), 0x5410);
            p_rank(el);
            p_store(el);
        }
        push(el.r2 >= KS * 2, e.x, e.y);
    }
};

__device__ __forceinline__ void p_filler(const Prm& p, int q, int w) {
    PFill F;
    const int lane = threadIdx.x & 31;
    F.lt = __shfl_sync(0xffffffffu, (1u << lane) - 1u, lane);
    F.qb = F.qt = SB + P_Q + w * (QN * 8);
    F.f2 = __shfl_sync(0xffffffffu, __bfloat16_as_ushort(p.freq[0]) * 0x10001u, 0);
    const uint32_t NS = p.NS, cend = p.T >> 7, s0 = q % GR, nv = NS * CPS, nc = (cend + NP - 1 - q) / NP;
    PIn x0, x1;
    uint32_t c0 = w, c1 = w + FW;
    F.q = q; F.lane = lane;
    p_fetch(p, x0, c0 * NP + q, lane);
#pragma unroll 1
    while (c0 < nc) {
        p_fetch(p, x1, c1 * NP + q, lane);
        c0 = F.chunk(x0);
        if (c1 >= nc) break;
        p_fetch(p, x0, c0 * NP + q, lane);
        c1 = F.chunk(x1);
    }
#pragma unroll 1
    while (min(c0, c1) < nv) { c0 = max(c0, c1); c1 = F.use_ticket(F.ticket()); F.enter(); F.end(); }
    F.nxt = ((NS + s0) % PER) << 16;
    uint32_t n = NS;
    if (q == 0 && w < 4) {
        int t = cend * 128 + w * 32 + lane;
        bool f = t < p.T;
        uint32_t i = 0, o = 0, x = 0;
        if (f) { i = p.idx_in[t]; o = p.idx_out[t]; asm("mul.rn.bf16x2 %0, %1, %2;" : "=r"(x) : "r"((uint32_t)__bfloat16_as_ushort(p.angle[t]) << 16), "r"(F.f2)); }
        F.push_checked(f, i, o, cos2_slow(x & 0xffff0000u));
    }
#pragma unroll 1
    for (; n <= NS + GR; n++) {
        F.begin(); F.enter();
        for (uint32_t nq = (F.qt - F.qb) >> 3; nq > 0;) { uint32_t take = min(nq, 32u); F.retry(take); nq -= take; }
        F.end();
        if (CPS > FW && w < CPS - FW) F.end();
    }
    if (F.qt != F.qb) st_relaxed(&g_ctl.bad, 1);
}

__device__ __forceinline__ void p_flusher(const Prm& p, unsigned char* ring, uint32_t pagebits, int q, int f) {
    const int lane = threadIdx.x & 31;
    const uint32_t bar = SB + P_BAR;
    const int NS = p.NS, NT = NS + 2 * GR;
    const uint32_t wto = lane < NCP ? OFF_REL + lane * 4 : OFF_RDY + (lane % 6) * 4;
    const uint32_t pfo = OFF_PF + (lane / 6) * 32 + (lane & 1) * 16 + ((lane % 6) >> 1) * 4;
    const uint32_t pfc = (lane >> 1) * 6 + (lane & 1);
    PROF_DECL
#pragma unroll 1
    for (int n0 = f * FB; n0 < NT; n0 += NF * FB) {
      uint32_t pw[FB], po[FB]; bool fence = false;
#pragma unroll
      for (int jf = 0; jf < FB; jf++) {
        const int n = n0 + jf;
        const uint32_t buf = (n + q % GR) % NBUF;
        const uint32_t h = n >> 1, lap = h / RB;
        const uint32_t qb = q_base(q, pagebits) ^ (((n + q) & 1) << 12);
        const uint32_t ba = qb ^ slot_off(h % RA) ^ R_A, bb = qb ^ slot_off(h % RB);
        if (h >= RA && !DEV_FREE)
            wait_all_ge(ring + ((lane < NCP ? bb : qb ^ slot_off((h - RA) % RB)) ^ wto), lane < NCP ? lap : ((h - RA) / RB + 1) << 1);
        PROF(0);
#pragma unroll
        for (int d = 2; d >= 0; d--) {
            const int nl = min(n, NS + GR) - d;
            if (nl >= 0) mbar_wait(bar + ((nl + q % GR) % NBUF) * 8, ((nl + q % GR) / NBUF) & 1);
        }
        PROF(1);
        uint32_t* cnt = (uint32_t*)(smem + P_CNT) + buf * NB;
        bool any = true;
        if (n >= NS) any = __any_sync(0xffffffffu, lane < NCP && (cnt[lane] | cnt[NCP + lane] | cnt[2 * NCP + lane]));
        if (any && elect_one()) {
            asm volatile("fence.proxy.async.shared::cta;" ::: "memory");
#pragma unroll
            for (int k = 0; k < 9; k++) {
                const int u = k < 6 ? k >> 1 : k - 6, hi = k < 6 && (k & 1);
                const uint32_t soff = k < 6 ? P_A + (u * NCP + hi * 8) * (KS * 4) + buf * (NB * KS * 4) : P_B + u * (NCP * KS * 2) + buf * (NB * KS * 2);
                asm volatile("cp.async.bulk.global.shared::cta.bulk_group [%0], [%1], %2;"
                             ::"l"(ring + (k < 6 ? ba : bb ^ R_B) + (u * R_UNIT + hi * 0x40000)), "r"(SB + soff),
                               "r"(k < 6 ? (hi ? NCP - 8 : 8) * (KS * 4) : NCP * KS * 2) : "memory");
            }
            asm volatile("cp.async.bulk.commit_group;" ::: "memory");
        }
        __syncwarp();
        uint32_t wm = ((lap + 1) << 22) | ((uint32_t)any << 21);
        if (lane < NCP) {
#pragma unroll
            for (int u = 0; u < 3; u++) wm |= min(cnt[pfc + 2 * u] >> 1, (uint32_t)KS) << (7 * u);
        }
        __syncwarp();
        if (lane < NB / 2) ((uint2*)cnt)[lane] = make_uint2(0, 0);
        PROF(3);
        asm volatile("cp.async.bulk.wait_group 0;" ::: "memory");
        __syncwarp();
        PROF(2);
        if (n > 0) mbar_wait(bar + (NBUF + (n - 1 + q % GR) % NBUF) * 8, ((n - 1 + q % GR) / NBUF) & 1);
        if (lane == 0) mbar_arrive(bar + (NBUF + buf) * 8);
        pw[jf] = wm; po[jf] = bb ^ pfo; fence |= any;
      }
      if (fence) fence_release();
      PROF(4);
#pragma unroll
      for (int jf = 0; jf < FB; jf++) if (lane < NCP) st_relaxed(ring + po[jf], pw[jf]);
    }
    PROF_END;
}
__device__ __forceinline__ void p_cleanup(unsigned char* ring, int q) {
    const int k = threadIdx.x / 24;
    if (k < 2 * RB) *(uint4*)(ring + ((q << 20) ^ ((k & 1) << 12) ^ slot_off(k >> 1) ^ OFF_PF) + (threadIdx.x % 24) * 16) = make_uint4(0, 0, 0, 0);
}

__device__ __forceinline__ void m_role(const Prm& p, unsigned char* ring, int X, int id) {
    const int tid = threadIdx.x, lane = tid & 31, w = __shfl_sync(0xffffffffu, tid >> 5, 0);
    const int ib = id >> 1, ty = id & 1;
    float* scs = (float*)(smem + S_MISC);
    if (w == 0) {
        const uint32_t bar = SB + S_AUX;
        if (lane == 0) mbar_init(bar, 1);
        wait_ge(&g_ctl.pieces_done, NPC);
        fence_acquire();
        if (lane == 0) {
            asm volatile("fence.proxy.async.global;" ::: "memory");
            asm volatile("fence.proxy.async.shared::cta;" ::: "memory");
            asm volatile("mbarrier.arrive.expect_tx.shared.b64 _, [%0], %1;" ::"r"(bar), "r"(ROWS_I * 4) : "memory");
            constexpr uint32_t PART = (ROWS_I * 4 / 8 + 127) / 128 * 128;
            for (uint32_t o = 0; o < ROWS_I * 4; o += PART)
                asm volatile("cp.async.bulk.shared::cluster.global.mbarrier::complete_tx::bytes [%0], [%1], %2, [%3];"
                             ::"r"(SB + o), "l"((const char*)(g_md[ty] + ib * ROWS_I) + o), "r"(min(PART, ROWS_I * 4 - o)), "r"(bar) : "memory");
        }
        __syncwarp();
            float sc[4]; bool bad;
        get_scales(p, sc, bad);
            if (bad) { st_relaxed(&g_ctl.bad, 1); sc[0] = sc[1] = sc[2] = sc[3] = 0.f; }
        int it = 0; uint32_t pb;
        while (!((pb = ld_relaxed(&g_ctl.pagebits)) >> 31)) backoff(it);
        if (lane == 0) { scs[0] = sc[0]; scs[1] = sc[1]; scs[2] = sc[2]; scs[3] = sc[3]; ((uint32_t*)scs)[4] = X ? ~pb : pb; ((uint32_t*)scs)[5] = bad; }
        mbar_wait(bar, 0);
    }
    __syncthreads();
    if (((uint32_t*)scs)[5]) {
        for (int k = tid; k < (int)ROWS_I; k += THREADS) ((uint32_t*)smem)[k] = 0;
        __syncthreads();
    }
    const uint32_t NT = p.NS + 2 * GR;
    if (w >= MW) return;
    const uint32_t pagebits = ((uint32_t*)scs)[4];
    const int half = lane >> 4, k4 = (lane & 15) * 4;
    const float s_lo = scs[2 * ty], s_hi = scs[2 * ty + 1];
    const float MAG_LO = 12582912.f, MAG_HI = 12582912.f - 19264.f;
    const int il = ib / NG, gi = (ib % NG) * 2 + X;
    const uint32_t a_off = R_A + il * R_UNIT + lane * 16, v_off = ty * R_V1 + il * R_UNIT + lane * 16;
    const uint32_t f_off = OFF_PF + il * 32 + half * 16, r_off = OFF_REL + (lane % NCP) * 4;
    const uint32_t j = w % (NP / GR);
    PROF_DECL
#pragma unroll 1
    for (uint32_t n = w / (NP / GR); n < NT; n += MW / (NP / GR)) {
        const uint32_t q = ((gi - n) & (GR - 1)) + GR * j, h = n >> 1;
        const uint32_t qb = q_base(q, pagebits), bb = qb ^ slot_off(h % RB);
        const uint32_t tag = (h / RB + 1) << 22;
        uint4 cw; int it = 0;
        while (true) {
            cw = ld_relaxed4(ring + (bb ^ f_off));
            if (__all_sync(0xffffffffu, min(min(cw.x, cw.y), cw.z) >= tag)) break;
            if (DEV_FREE) { cw.x = (cw.x & 1) + (63 | 57 << 7 | 50 << 14 | 1 << 21); cw.y = (cw.y & 1) + (53 | 61 << 7 | 57 << 14); cw.z = (cw.z & 1) + (59 | 52 << 7 | 57 << 14); break; }
            backoff(it);
        }
        PROF(0);
        if (__any_sync(0xffffffffu, cw.x & (1u << 21))) {
            const unsigned char* pa = ring + (qb ^ slot_off(h % RA) ^ a_off);
            unsigned char* pv = ring + (qb ^ slot_off(h % RV) ^ v_off);
            const uint32_t hv = h + RB - RV;
            const unsigned char* prel = ring + (qb ^ slot_off(hv % RB) ^ r_off);
            const uint32_t rel = ld_relaxed(prel);
            const uint32_t vlap = h / RV;
            const float mag_lo0 = MAG_LO + (float)(8192 + (vlap & 3) * 16384), mag_hi0 = MAG_HI + (float)(8192 + ((vlap >> 2) & 3) * 16384);
            uint4 a[9];
#define M_LOAD(ps) a[ps] = ld_relaxed4(pa + (ps) * 512 + ((ps) < 4 ? 0 : R_HI))
#pragma unroll
            for (int ps = 0; ps < MPF; ps++) M_LOAD(ps);
            if (!__all_sync(0xffffffffu, rel >= hv / RB) && !DEV_FREE) wait_all_ge(prel, hv / RB);
            PROF(3);
#pragma unroll
            for (int ps = 0; ps < 9; ps++) {
                const int rem = (int)(((ps < 3 ? cw.x : ps < 6 ? cw.y : cw.z) >> (7 * (ps % 3))) & 0x7f) - k4;
                uint32_t aw[4] = {a[ps].x, a[ps].y, a[ps].z, a[ps].w}, mv[4], vw[4];
#pragma unroll
                for (int e = 0; e < 4; e++) { mv[e] = 0; lds_lt(mv[e], __dp2a_lo(aw[e], 4u, (uint32_t)SB), e, rem); }
#pragma unroll
                for (int e = 0; e < 4; e++) {
                    float c = bf_hi(aw[e]);
                    float lo = fmaf(bf_lo(mv[e]), c * s_lo, e ? MAG_LO : mag_lo0), hi = fmaf(bf_hi(mv[e]), c * s_hi, e ? MAG_HI : mag_hi0);
                    vw[e] = (__float_as_uint(hi) << 16) + __float_as_uint(lo);
                }
                asm volatile("st.global.v4.u32 [%0], {%1,%2,%3,%4};" ::"l"(pv + ps * 512 + (ps < 4 ? 0 : R_HI)), "r"(vw[0]), "r"(vw[1]), "r"(vw[2]), "r"(vw[3]) : "memory");
                if (ps + MPF < 9) M_LOAD(ps + MPF);
            }
            if (vlap == 0 || n >= p.NS) fence_release();
        }
        st_lane0(ring + (bb ^ (OFF_RDY + (2 * il + ty) * 4)), cw.x >> 21, lane);
        PROF(1);
    }
    PROF_END;
}

__device__ __noinline__ void c_wrap(uint32_t row, int par, uint32_t old, uint32_t w) {
    const uint32_t nw = old + w, ov = ~(old ^ w) & (old ^ nw);
    int d = 0;
    if (ov & 0x8000u) d += (w & 0x8000u) ? -1 : 1;
    if (ov & 0x80000000u) d += (w & 0x80000000u) ? -16 : 16;
    if (d != 0) {
        uint32_t c;
        asm volatile("atom.shared.add.u32 %0, [%1], %2;" : "=r"(c) : "r"(SB + C_WRAP + row * 4), "r"(d << (8 * par)) : "memory");
        c = (c >> (8 * par)) + d;
        if (((c + 1) & 0xe) == 0 || ((c + 16) & 0xe0) == 0) st_relaxed(&g_ctl.bad, 1);
    }
}

#define CGRP 6
struct CTask { uint4 v[3]; uint2 b[3]; };
struct CWork {
    unsigned char* ring;
    uint32_t v_off, b_off, f_off, r_off, acc;
    uint32_t lap1, sv, sb, vtag, fw;
    int lane, dev_free;
    template <int ODD> __device__ __forceinline__ bool issue(CTask& t) {
        if (!__all_sync(0xffffffffu, fw >= 2 * lap1)) {
            int it = 0;
            do {
                if (dev_free) { fw = 1; break; }
                backoff(it);
                fw = ld_relaxed(ring + (f_off ^ slot_off(sb) ^ (ODD << 20)));
            } while (!__all_sync(0xffffffffu, fw >= 2 * lap1));
        }
        const bool data = __any_sync(0xffffffffu, fw & 1);
        if (data) {
            const unsigned char* pv = ring + (v_off ^ slot_off(sv) ^ (ODD << 20));
            const unsigned char* pb = ring + (b_off ^ slot_off(sb) ^ (ODD << 20));
#pragma unroll
            for (int ps = 0; ps < 3; ps++) {
                t.v[ps] = ld_relaxed4(pv + ps * R_UNIT);
                t.b[ps] = ld_relaxed2(pb + ps * R_UNIT);
            }
        }
        fw = ld_relaxed(ring + (f_off ^ slot_off(ODD ? (sb + 1 == RB ? 0 : sb + 1) : sb) ^ (!ODD << 20)));
        return data;
    }
    template <int ODD> __device__ __forceinline__ void arrive(CTask& t, bool data) {
        if (data) {
            int it = 0;
            while (__any_sync(0xffffffffu, (((t.v[0].x ^ vtag) | (t.v[1].x ^ vtag) | (t.v[2].x ^ vtag)) & 0xc000c000u) | ((t.b[0].x | t.b[1].x | t.b[2].x) & 0x8000u))) {
                if (dev_free) { for (int ps = 0; ps < 3; ps++) t.v[ps].x = (t.v[ps].x & 0x3fff3fffu) | (vtag & 0xc000c000u); break; }
                if (++it > SPIN_MAX) __trap();
#pragma unroll
                for (int ps = 0; ps < 3; ps++) t.v[ps] = ld_relaxed4(ring + (v_off ^ slot_off(sv) ^ (ODD << 20)) + ps * R_UNIT);
            }
#pragma unroll
            for (int ps = 0; ps < 3; ps++) t.v[ps].x -= vtag;
        }
        st_lane0(ring + (r_off ^ slot_off(sb) ^ (ODD << 20)), lap1, lane);
        if (ODD) {
            if (++sv == RV) { sv = 0; vtag += 0x4000u; if (vtag & 0x10000u) vtag += 0x3fff0000u; }
            if (++sb == RB) { sb = 0; lap1++; }
        }
    }
    __device__ __forceinline__ void add(const CTask& t, bool data) {
        if (!data) return;
        const uint32_t vw[12] = {t.v[0].x, t.v[0].y, t.v[0].z, t.v[0].w, t.v[1].x, t.v[1].y, t.v[1].z, t.v[1].w, t.v[2].x, t.v[2].y, t.v[2].z, t.v[2].w};
        const uint32_t bw[6] = {t.b[0].x, t.b[0].y, t.b[1].x, t.b[1].y, t.b[2].x, t.b[2].y};
#pragma unroll
        for (int g = 0; g < 12; g += CGRP) {
            uint32_t old[CGRP], ov = 0;
#pragma unroll
            for (int e = g; e < g + CGRP; e++)
                asm volatile("atom.shared.add.u32 %0, [%1], %2;" : "=r"(old[e - g]) : "r"((e & 1) ? __dp2a_hi(bw[e >> 1], 0x08000008u, acc) : __dp2a_lo(bw[e >> 1], 0x08000008u, acc)), "r"(vw[e]) : "memory");
#pragma unroll
            for (int e = g; e < g + CGRP; e++) ov |= ~(old[e - g] ^ vw[e]) & (old[e - g] ^ (old[e - g] + vw[e]));
            if (__any_sync(0xffffffffu, ov & 0x80008000u)) {
#pragma unroll
                for (int e = g; e < g + CGRP; e++) c_wrap((e & 1) ? bw[e >> 1] >> 16 : bw[e >> 1] & 0xffffu, lane >> 4, old[e - g], vw[e]);
            }
        }
    }
};

__device__ __forceinline__ void c_role(const Prm& p, unsigned char* ring, int X, int c) {
    const int tid = threadIdx.x, lane = tid & 31, w = __shfl_sync(0xffffffffu, tid >> 5, 0);
    uint32_t* misc = (uint32_t*)(smem + S_MISC);
    Wts* wt = (Wts*)(smem + S_AUX);
    load_wts(p, wt);
    for (int k = tid; k < C_WRAP / 16; k += THREADS) ((uint4*)smem)[k] = make_uint4(0, 0, 0, 0);
    if (tid == 0) misc[6] = TAB_N;
    __syncthreads();
    if (w == 0) {
        float sc[4]; bool bad;
        wait_ge(&g_ctl.pieces_done, NPC);
        fence_acquire();
        get_scales(p, sc, bad);
        const float s = (lane & 2) ? ((lane & 1) ? sc[3] : sc[2]) : ((lane & 1) ? sc[1] : sc[0]);
        wt->ws[lane] *= s > 0.f ? 1.f / s : 0.f;
        int it = 0; uint32_t pb;
        while (!((pb = ld_relaxed(&g_ctl.pagebits)) >> 31)) backoff(it);
        misc[4] = X ? ~pb : pb;
    } else {
        const int r0 = (X * NCP + c) * ROWS_O, nr = min((int)ROWS_O, p.E - r0);
#pragma unroll 4
        for (int r = tid - 32; r < (int)ROWS_O / 2; r += THREADS - 32) {
            const uint32_t d2 = 2 * r < nr ? __ldg((const uint32_t*)(p.dist + r0) + r) : TAB_LO * 0x10001u;
            uint32_t e[2] = {(d2 & 0xffff) - TAB_LO, (d2 >> 16) - TAB_LO};
#pragma unroll
            for (int k = 0; k < 2; k++)
                if (e[k] >= TAB_N) {
                    const uint32_t d = e[k] + TAB_LO;
                    if ((d & 0x7f80) == 0x7f80) st_relaxed(&g_ctl.bad, 1);
                    e[k] = min(atomicAdd(&misc[6], 1u), 0xffffu);
                    if (e[k] < TAB_N + TAB_X) ((uint32_t*)(smem + C_TAB))[e[k] * 4] = d;
                }
            ((uint2*)(smem + C_WRAP))[r] = make_uint2(e[0] << 16 | 0x8888u, e[1] << 16 | 0x8888u);
        }
    }
    __syncthreads();
    if (w >= NP / 2) {
        const int nt = min(misc[6], (uint32_t)(TAB_N + TAB_X));
        for (int k = tid - NP * 16; k < nt; k += THREADS - NP * 16)
            ((uint4*)(smem + C_TAB))[k] = radial_bf16(wt, k < TAB_N ? TAB_LO + k : ((uint32_t*)(smem + C_TAB))[k * 4]);
        if (tid == THREADS - 1 && !DEV_FREE) {
            const uint32_t h = p.NS >> 1;
            const unsigned char* f = ring + (q_base(X, misc[4]) ^ slot_off(h % RB) ^ (OFF_REL + c * 4));
            for (int it = 0; ld_relaxed(f) < h / RB; it++) { __nanosleep(2000); if (it > SPIN_MAX) __trap(); }
            const int r0 = (X * NCP + c) * ROWS_O, nr = min((int)ROWS_O, p.E - r0);
            if (nr > 0) asm volatile("cp.async.bulk.prefetch.L2.global [%0], %1;" ::"l"(p.m + r0), "r"(nr * 8) : "memory");
        }
    }
    const uint32_t pagebits = misc[4];
    if (w >= NP / 2) return;
    CWork W;
    const int par = lane >> 4;
    W.ring = ring; W.lane = __shfl_sync(0xffffffffu, lane, lane); W.dev_free = DEV_FREE;
    const uint32_t qb = q_base(2 * w + X, pagebits), k = lane & 15;
    W.acc = __shfl_sync(0xffffffffu, SB + par * 4, lane);
    W.v_off = __shfl_sync(0xffffffffu, qb ^ (par * R_V1 + (c < 8 ? 0 : R_HI) + c * 256 + k * 16), lane);
    W.b_off = __shfl_sync(0xffffffffu, qb ^ (R_B + c * 128 + k * 8), lane);
    W.f_off = __shfl_sync(0xffffffffu, qb ^ (OFF_RDY + (lane % 6) * 4), lane);
    W.r_off = qb ^ (OFF_REL + c * 4);
    W.lap1 = 1; W.sv = W.sb = W.fw = 0; W.vtag = 0x20002000u;
    const uint32_t NT = p.NS + 2 * GR;
    CTask A, B;
    PROF_DECL
    bool da = W.issue<0>(A), db;
#pragma unroll 1
    for (uint32_t n = 2;; n += 2) {
        W.arrive<0>(A, da); PROF(1); db = W.issue<1>(B); PROF(0); W.add(A, da);
        W.arrive<1>(B, db);
        if (n >= NT) break;
        PROF(1); da = W.issue<0>(A); PROF(0); W.add(B, db);
    }
    W.add(B, db);
    PROF_END;
}

__device__ __forceinline__ uint32_t bf2_mul(uint32_t a, uint32_t b) { uint32_t r; asm("mul.rn.bf16x2 %0, %1, %2;" : "=r"(r) : "r"(a), "r"(b)); return r; }
__device__ __forceinline__ uint32_t bf2_fma(uint32_t a, uint32_t b, uint32_t c) { uint32_t r; asm("fma.rn.bf16x2 %0, %1, %2, %3;" : "=r"(r) : "r"(a), "r"(b), "r"(c)); return r; }
__device__ __forceinline__ uint32_t c_agg(uint32_t a, uint32_t s, uint32_t wr, bool wrapped) {
    int x0 = (short)a, x1 = ((int)a >> 16) + ((a >> 15) & 1);
    if (wrapped) { const int w0 = (int)(wr & 15) - 8, w1 = (int)((wr >> 4) & 15) - 8; x0 += 65536 * w0; x1 += 65536 * w1 - w0; }
    return pack_bf16((float)x1 * bf_hi(s), (float)x0 * bf_lo(s));
}
__device__ __forceinline__ void c_epilogue(const Prm& p, int X, int c) {
    const int tid = threadIdx.x, lane = tid & 31;
    const Wts* wt = (const Wts*)(smem + S_AUX);
    uint32_t bw[4];
#pragma unroll
    for (int k = 0; k < 4; k++) {
        const int col = (k >> 1) * 2 + ((lane >> 2) & 1), row = (k & 1) * 2;
        bw[k] = (lane >> 3) == (lane & 3) ? pack_bf16(wt->wu[(row + 1) * 4 + col], wt->wu[row * 4 + col]) : 0u;
    }
    const int r0 = (X * NCP + c) * ROWS_O, np = max(min((int)ROWS_O, p.E - r0), 0) / 2;
    const uint4* mp = (const uint4*)(p.m + r0);
    uint4* op = (uint4*)(p.out + r0);
    constexpr int EB = 5;
#pragma unroll 1
    for (int rb = tid; rb - lane < np; rb += EB * THREADS) {
        uint4 mr[EB];
#pragma unroll
        for (int k = 0; k < EB; k++) mr[k] = __ldg(mp + min(rb + k * THREADS, np - 1));
#pragma unroll
        for (int k = 0; k < EB; k++) {
            const int r = min(rb + k * THREADS, np - 1);
            const uint4 a = ((const uint4*)smem)[r];
            const uint2 wr = ((const uint2*)(smem + C_WRAP))[r];
            const uint4 t0 = ((const uint4*)(smem + C_TAB))[min(wr.x >> 16, (uint32_t)(TAB_N + TAB_X - 1))];
            const uint4 t1 = ((const uint4*)(smem + C_TAB))[min(wr.y >> 16, (uint32_t)(TAB_N + TAB_X - 1))];
            const bool wrapped = __any_sync(0xffffffffu, prmt(wr.x, wr.y, 0x5410) != 0x88888888u);
            uint32_t a0, a1, a2, a3;
            if (wrapped) { a0 = c_agg(a.x, t0.x, wr.x, true); a2 = c_agg(a.y, t0.y, wr.x >> 8, true); a1 = c_agg(a.z, t1.x, wr.y, true); a3 = c_agg(a.w, t1.y, wr.y >> 8, true); }
            else { a0 = c_agg(a.x, t0.x, 0, false); a2 = c_agg(a.y, t0.y, 0, false); a1 = c_agg(a.z, t1.x, 0, false); a3 = c_agg(a.w, t1.y, 0, false); }
            float u[8];
#pragma unroll
            for (int h = 0; h < 2; h++)
                asm("mma.sync.aligned.m16n8k16.row.col.f32.bf16.bf16.f32 {%0,%1,%2,%3}, {%4,%5,%6,%7}, {%8,%9}, {%10,%10,%10,%10};"
                    : "=f"(u[4 * h]), "=f"(u[4 * h + 1]), "=f"(u[4 * h + 2]), "=f"(u[4 * h + 3])
                    : "r"(a0), "r"(a1), "r"(a2), "r"(a3), "r"(bw[2 * h]), "r"(bw[2 * h + 1]), "f"(0.f));
            const uint4 o = make_uint4(bf2_fma(pack_bf16(u[1], u[0]), t0.z, mr[k].x), bf2_fma(pack_bf16(u[5], u[4]), t0.w, mr[k].y),
                                       bf2_fma(pack_bf16(u[3], u[2]), t1.z, mr[k].z), bf2_fma(pack_bf16(u[7], u[6]), t1.w, mr[k].w));
            if (rb + k * THREADS < np) op[r] = o;
        }
    }
    if (((const uint32_t*)(smem + S_MISC))[6] > TAB_N + TAB_X) {
        for (int r = 2 * tid; r < 2 * np; r += (r & 1) ? 2 * THREADS - 1 : 1) {
            const uint32_t wr = ((const uint32_t*)(smem + C_WRAP))[r];
            if ((wr >> 16) < TAB_N + TAB_X) continue;
            const uint4 t = radial_bf16(wt, __bfloat16_as_ushort(p.dist[r0 + r]));
            const uint2 a = ((const uint2*)smem)[r];
            const uint32_t a0 = c_agg(a.x, t.x, wr, true), a1 = c_agg(a.y, t.y, wr >> 8, true);
            const float agg[4] = {bf_lo(a0), bf_hi(a0), bf_lo(a1), bf_hi(a1)}, g[4] = {bf_lo(t.z), bf_hi(t.z), bf_lo(t.w), bf_hi(t.w)};
            p.out[r0 + r] = finish_row(wt->wu, agg, g, p.m[r0 + r]);
        }
    }
}

__device__ __forceinline__ void grid_bar(unsigned* ctr) {
    __syncthreads();
    if (threadIdx.x == 0) { fence_gpu(); red_add(ctr, 1); wait_ge(ctr, gridDim.x); fence_gpu(); }
    __syncthreads();
}
__device__ __noinline__ void fallback(const Prm& p) {
    const int gt = blockIdx.x * THREADS + threadIdx.x, gs = gridDim.x * THREADS;
    Wts* wt = (Wts*)smem;
    __syncthreads();
    load_wts(p, wt);
    for (int e = gt; e < p.E; e += gs) g_acc[e] = make_float4(0.f, 0.f, 0.f, 0.f);
    grid_bar(&g_ctl.bar[0]);
    const float f = __bfloat162float(p.freq[0]);
    for (int t = gt; t < p.T; t += gs) {
        uint2 r = __ldg(p.m + p.idx_in[t]);
        float c = rbf16(cosf(rbf16(f * __bfloat162float(p.angle[t]))));
        asm volatile("red.global.add.v4.f32 [%0], {%1,%2,%3,%4};" ::"l"(g_acc + p.idx_out[t]), "f"(bf_lo(r.x) * c),
                     "f"(bf_hi(r.x) * c), "f"(bf_lo(r.y) * c), "f"(bf_hi(r.y) * c) : "memory");
    }
    grid_bar(&g_ctl.bar[1]);
    for (int e = gt; e < p.E; e += gs) {
        float4 a4 = __ldcg(g_acc + e);
        float a[4] = {a4.x, a4.y, a4.z, a4.w}, s[4], g[4];
        radial(wt, __bfloat162float(p.dist[e]), s, g);
        float agg[4];
#pragma unroll
        for (int j = 0; j < 4; j++) agg[j] = s[j] * (a[0] * wt->wd[j] + a[1] * wt->wd[4 + j] + a[2] * wt->wd[8 + j] + a[3] * wt->wd[12 + j]);
        p.out[e] = finish_row(wt->wu, agg, g, p.m[e]);
    }
}

__global__ void __launch_bounds__(THREADS, 1) gemnet_kernel(const __grid_constant__ Prm p) {
    const int tid = threadIdx.x, lane = tid & 31, w = __shfl_sync(0xffffffffu, tid >> 5, 0);
    uint32_t* misc = (uint32_t*)(smem + S_MISC);
    bool run_fallback = true;
    if (!p.force_bad && __cvta_generic_to_shared(smem) == SB) {
        unsigned char* const ring = p.ring;
        uint32_t smid; asm("mov.u32 %0, %%smid;" : "=r"(smid));
        const int cls = smid < NM ? 0 : (smid < NM + NP - 4 || (smid >= 124 && smid < 128)) ? 2 : 1;
        if (lane == 0) {
            if (w < 2 && (cls != 2 || blockIdx.x == 0)) misc[16 + w] = probe(ring + OFF_PROBE + w * 4096 + ((blockIdx.x >> 7) << 20) + (blockIdx.x & 127) * 32);
            else if (blockIdx.x == 0 && w <= NPAGES) misc[16 + w] = probe(ring + ((size_t)(w - 1) << 21) + OFF_PROBE);
        }
        float wd[16];
        if (cls != 2 || blockIdx.x == 0) __syncthreads();
        if (tid == 0) {
            int pool = cls == 2 ? 4 : cls * 2 + (misc[16] > misc[17]), id = 0;
            for (int k = 0; k < 7; k++) {
                int cap = pool < 2 ? NMP : pool < 4 ? NCP : NP;
                id = atomicAdd(&g_ctl.ticket[pool], 1);
                if (id < cap) break;
                pool = k == 0 ? (pool == 4 ? 0 : pool ^ 1) : k - 1;
            }
            misc[8] = pool; misc[9] = id;
        }
        if (blockIdx.x == 0 && tid == 32) {
            uint32_t pb = 0x80000000u;
            for (int k = 1; k < NPAGES; k++) pb |= (uint32_t)((2 * misc[17 + k] > misc[16] + misc[17]) != (misc[16] > misc[17])) << k;
            st_relaxed(&g_ctl.pagebits, pb);
        }
#pragma unroll
        for (int k = 0; k < 16; k++) wd[k] = __bfloat162float(p.w_down[k]);
        __syncthreads();
        const int pool = misc[8], id = misc[9];
        __syncthreads();
        if (pool != 4) down_piece(p, pool < 2 ? pool * NMP + id : NM + (pool - 2) * NCP + id, wd);
        if (DEV_FREE && !(DEV_FREE & (pool == 4 ? 1 : pool < 2 ? 2 : 4))) {
        } else if (pool == 4) {
            for (int k = tid; k < S_MISC / 16; k += THREADS) {
                const uint32_t z = k >= P_B / 16 && k < P_Q / 16 ? (k & 7) * 0x20002u : 0u, y = z + (k >= P_B / 16 && k < P_Q / 16 ? 0x10001u : 0u);
                ((uint4*)smem)[k] = make_uint4(z, z, y, y);
            }
            __syncthreads();
            if (tid < 2 * NBUF) {
                const uint32_t a = __cvta_generic_to_shared(smem + P_BAR) + tid * 8, cnt = tid < NBUF ? CPS : 1;
                mbar_init(a, cnt);
                if (tid % NBUF < id % GR) asm volatile("mbarrier.arrive.shared.b64 _, [%0], %1;" ::"r"(a), "r"(cnt) : "memory");
            }
            __syncthreads();
            if (w < FW) p_filler(p, id, w);
            else if (w < FW + NF) {
                int it = 0; uint32_t pb;
                while (!((pb = ld_relaxed(&g_ctl.pagebits)) >> 31)) backoff(it);
                p_flusher(p, ring, __shfl_sync(0xffffffffu, pb, 0), id, w - FW);
            }
        } else if (pool < 2) {
            m_role(p, ring, pool, id);
        } else {
            c_role(p, ring, pool - 2, id);
        }
        __syncthreads();
        if (tid == 0) { fence_gpu(); red_add(&g_ctl.fin, 1); }
        if ((pool == 2 || pool == 3) && !DEV_FREE) c_epilogue(p, pool - 2, id);
        if (tid == 0) { wait_ge(&g_ctl.fin, NCTA); fence_gpu(); misc[10] = ld_relaxed(&g_ctl.bad); }
        __syncthreads();
        if (pool == 4) p_cleanup(ring, id);
        run_fallback = misc[10] && !DEV_FREE;
    }
    if (run_fallback) fallback(p);
    if (tid == 0) {
        fence_gpu();
        if (atomicAdd(&g_ctl.exited, 1) == gridDim.x - 1) {
            uint32_t* c = (uint32_t*)&g_ctl;
            for (int k = 0; k < 32; k++) c[k] = 0;
        }
    }
}

cudaTextureObject_t make_tex(const void* ptr, size_t bytes, int words) {
    cudaResourceDesc rd = {};
    rd.resType = cudaResourceTypeLinear;
    rd.res.linear.devPtr = (void*)ptr;
    rd.res.linear.desc = words == 4 ? cudaCreateChannelDesc<uint4>() : cudaCreateChannelDesc<uint2>();
    rd.res.linear.sizeInBytes = bytes;
    cudaTextureDesc td = {};
    td.readMode = cudaReadModeElementType;
    cudaTextureObject_t t = 0;
    if (cudaCreateTextureObject(&t, &rd, &td, nullptr) != cudaSuccess) { cudaGetLastError(); return 0; }
    return t;
}

}

extern "C" void kernel_launch(void* const* d_in, const int* in_sizes, int n_in, void* d_out, int out_size) {
    static Prm p = {};
    static int grid = 0;
    const int E = in_sizes[3], T = in_sizes[1];
    if (grid == 0 || p.idx_in != d_in[1] || p.idx_out != d_in[2] || p.angle != d_in[4] || p.E != E || p.T != T) {
        int dev = 0, sms = 0;
        cudaGetDevice(&dev);
        cudaDeviceGetAttribute(&sms, cudaDevAttrMultiProcessorCount, dev);
        cudaFuncSetAttribute(gemnet_kernel, cudaFuncAttributeMaxDynamicSharedMemorySize, SMEM_BYTES);
        p.E = E; p.T = T;
        p.NS = ((T / 128 + NP * CPS - 1) / (NP * CPS) + (FB > 2 ? 3 : 1)) & (FB > 2 ? ~3 : ~1);
        void* rp = nullptr;
        cudaGetSymbolAddress(&rp, g_ring);
        p.ring = (unsigned char*)(((uintptr_t)rp + ((2u << 20) - 1)) & ~(uintptr_t)((2u << 20) - 1));
        bool fast = sms >= NCTA && E <= (int)FAST_E && (E & 1) == 0 && T >= 128 && T <= (1 << 29);
        if (fast) {
            p.t_in = make_tex(d_in[1], (size_t)(T / 128) * 512, 4);
            p.t_out = make_tex(d_in[2], (size_t)(T / 128) * 512, 4);
            p.t_ang = make_tex(d_in[4], (size_t)(T / 128) * 256, 2);
            fast = p.t_in && p.t_out && p.t_ang;
        }
        p.force_bad = !fast;
        grid = fast ? NCTA : sms;
    }
    p.m = (const uint2*)d_in[0];
    p.idx_in = (const int*)d_in[1];
    p.idx_out = (const int*)d_in[2];
    p.dist = (const __nv_bfloat16*)d_in[3];
    p.angle = (const __nv_bfloat16*)d_in[4];
    p.centers = (const __nv_bfloat16*)d_in[5];
    p.freq = (const __nv_bfloat16*)d_in[6];
    p.w_rbf = (const __nv_bfloat16*)d_in[7];
    p.w_sbf = (const __nv_bfloat16*)d_in[8];
    p.w_down = (const __nv_bfloat16*)d_in[9];
    p.w_up = (const __nv_bfloat16*)d_in[10];
    p.out = (uint2*)d_out;
    gemnet_kernel<<<grid, THREADS, SMEM_BYTES>>>(p);
}
```

```cpp
#include <cuda_runtime.h>
#include <cuda_bf16.h>
#include <stdint.h>

namespace {

constexpr int NI = 12;
constexpr int UN = 3;
constexpr int NG = NI / UN;
constexpr int GR = 2 * NG;
constexpr int NCP = 18;
constexpr int NO = 2 * NCP;
constexpr int KS = 64;
constexpr int NB = UN * NCP;
constexpr int NBUF = 10;
constexpr int NMP = 2 * NI;
constexpr int NP = 48, NM = 2 * NMP, NC = NO, NCTA = NP + NM + NC;
#define CPS_ 24
constexpr int CPS = CPS_;
#define FW_ 24
constexpr int FW = FW_;
constexpr int NF = 4;
#define RA_ 3
#define RV_ 3
#define RB_ 4
constexpr int RA = RA_, RV = RV_, RB = RB_;
constexpr int QN = 80, QTRIG = 36;
#define MW_ 18
constexpr int MW = MW_;
#define MPF_ 6
constexpr int MPF = MPF_;
constexpr int THREADS = 896, NW = THREADS / 32;
#define DEV_FREE 0
#define SLEEP_ 200

constexpr int RING_BYTES = NP << 20;
constexpr int NPAGES = RING_BYTES >> 21;
constexpr int MAX_E = 1 << 20;
constexpr int SMEM_BYTES = 232448;

constexpr int SB = 1024;

constexpr int P_CNT = 0;
constexpr int P_BAR = P_CNT + NBUF * NB * 4;
constexpr int P_TKT = P_BAR + 2 * NBUF * 8;
constexpr int P_B = (P_TKT + 128 + 127) / 128 * 128;
constexpr int P_Q = P_B + NBUF * NB * KS * 2;
constexpr int P_A = SMEM_BYTES - 256 - NBUF * NB * KS * 4;
static_assert(P_Q + FW * QN * 8 + 512 <= P_A && P_A % 128 == 0, "P smem");
constexpr int S_MISC = SMEM_BYTES - 256;
constexpr int S_AUX = S_MISC - 512;

constexpr unsigned FAST_E = 640000;
constexpr unsigned magic_of(unsigned long long d) { return (unsigned)(((1ull << 32) + d - 1) / d); }
constexpr bool magic_ok(unsigned long long d) { return (magic_of(d) * d - (1ull << 32)) * FAST_E < (1ull << 32); }
constexpr unsigned pick_rows(unsigned lo) {
    unsigned d = (lo + 3) & ~3u;
    while (!magic_ok(d)) d += 4;
    return d;
}
constexpr unsigned ROWS_I = pick_rows((FAST_E + NI - 1) / NI), ROWS_O = pick_rows((FAST_E + NO - 1) / NO);
constexpr unsigned MAG_I = magic_of(ROWS_I), MAG_O = magic_of(ROWS_O), HALF_O = ROWS_O * NCP;
constexpr int C_WRAP = ROWS_O * 8, C_TAB = ROWS_O * 12, TAB_N = 1025, TAB_LO = 0x3f80 - 1024, TAB_X = (S_AUX - C_TAB) / 16 - TAB_N;
static_assert(ROWS_I * 4 <= S_AUX && TAB_X >= 100 && ROWS_I <= 65536 && ROWS_O <= 32768, "tables");

constexpr int NPC = NM + NC;
constexpr int PC_ROWS = ((FAST_E + NPC - 1) / NPC + 3) & ~3;
struct __align__(128) Ctl {
    unsigned ticket[5];
    unsigned pagebits;
    unsigned pieces_done, unused;
    unsigned bad;
    unsigned fin;
    unsigned bar[3];
    unsigned exited;
    unsigned pad[18];
    float stat[NPC][8];
};

struct Prm {
    const uint2* m; const int* idx_in; const int* idx_out; const __nv_bfloat16* dist; const __nv_bfloat16* angle;
    const __nv_bfloat16* centers; const __nv_bfloat16* freq; const __nv_bfloat16* w_rbf; const __nv_bfloat16* w_sbf;
    const __nv_bfloat16* w_down; const __nv_bfloat16* w_up; uint2* out;
    cudaTextureObject_t t_in, t_out, t_ang;
    int E, T;
    unsigned char* ring;
    int NS;
    int force_bad;
};

__device__ __align__(128) unsigned char g_ring[RING_BYTES + (2 << 20)];
__device__ Ctl g_ctl;
__device__ float4 g_acc[MAX_E];
__device__ __align__(128) uint32_t g_md[2][NI * ROWS_I];
#define TS(k)
#define PROF_DECL
#define PROF(k)
#define PROF_END

extern __shared__ __align__(128) unsigned char smem[];

__device__ __forceinline__ float bf_lo(uint32_t w) { return __uint_as_float(w << 16); }
__device__ __forceinline__ float bf_hi(uint32_t w) { return __uint_as_float(w & 0xffff0000u); }
__device__ __forceinline__ float rbf16(float x) { return __bfloat162float(__float2bfloat16_rn(x)); }
__device__ __forceinline__ uint32_t pack_bf16(float hi, float lo) {
    uint32_t r; asm("cvt.rn.bf16x2.f32 %0, %1, %2;" : "=r"(r) : "f"(hi), "f"(lo)); return r;
}
__device__ __forceinline__ uint32_t prmt(uint32_t a, uint32_t b, uint32_t c) {
    uint32_t r; asm("prmt.b32 %0, %1, %2, %3;" : "=r"(r) : "r"(a), "r"(b), "r"(c)); return r;
}
__device__ __forceinline__ uint32_t ld_relaxed(const void* p) {
    uint32_t v; asm volatile("ld.relaxed.gpu.global.u32 %0, [%1];" : "=r"(v) : "l"(p) : "memory"); return v;
}
__device__ __forceinline__ uint2 ld_relaxed2(const void* p) {
    uint2 v; asm volatile("ld.relaxed.gpu.global.v2.u32 {%0,%1}, [%2];" : "=r"(v.x), "=r"(v.y) : "l"(p) : "memory"); return v;
}
__device__ __forceinline__ uint4 ld_relaxed4(const void* p) {
    uint4 v; asm volatile("ld.relaxed.gpu.global.v4.u32 {%0,%1,%2,%3}, [%4];" : "=r"(v.x), "=r"(v.y), "=r"(v.z), "=r"(v.w) : "l"(p) : "memory"); return v;
}
__device__ __forceinline__ void st_relaxed(void* p, uint32_t v) { asm volatile("st.relaxed.gpu.global.u32 [%0], %1;" ::"l"(p), "r"(v) : "memory"); }
__device__ __forceinline__ void st_relaxed16(void* p, uint32_t v) { asm volatile("st.relaxed.gpu.global.u16 [%0], %1;" ::"l"(p), "h"((uint16_t)v) : "memory"); }
__device__ __forceinline__ void red_add(void* p, uint32_t v) { asm volatile("red.relaxed.gpu.global.add.u32 [%0], %1;" ::"l"(p), "r"(v) : "memory"); }
__device__ __forceinline__ void fence_gpu() { asm volatile("fence.acq_rel.gpu;" ::: "memory"); }
__device__ __forceinline__ void fence_acquire() { asm volatile("fence.acquire.gpu;" ::: "memory"); }
__device__ __forceinline__ void fence_release() { asm volatile("fence.release.gpu;" ::: "memory"); }
__device__ __forceinline__ void mbar_init(uint32_t a, uint32_t n) { asm volatile("mbarrier.init.shared.b64 [%0], %1;" ::"r"(a), "r"(n) : "memory"); }
__device__ __forceinline__ void mbar_arrive(uint32_t a) { asm volatile("mbarrier.arrive.shared.b64 _, [%0];" ::"r"(a) : "memory"); }
__device__ __forceinline__ bool mbar_try(uint32_t a, uint32_t ph) {
    uint32_t ok;
    asm volatile("{.reg .pred p; mbarrier.try_wait.parity.shared.b64 p, [%1], %2, %3; selp.u32 %0, 1, 0, p;}" : "=r"(ok) : "r"(a), "r"(ph), "r"(2000) : "memory");
    return ok;
}
__device__ __forceinline__ bool mbar_test(uint32_t a, uint32_t ph) {
    uint32_t ok;
    asm volatile("{.reg .pred p; mbarrier.test_wait.parity.shared.b64 p, [%1], %2; selp.u32 %0, 1, 0, p;}" : "=r"(ok) : "r"(a), "r"(ph) : "memory");
    return ok;
}
constexpr int SPIN_MAX = 1 << 22;
__device__ __forceinline__ void mbar_wait(uint32_t a, uint32_t ph) {
    int it = 0;
    while (!mbar_try(a, ph)) { if (++it > SPIN_MAX) __trap(); }
}
__device__ __forceinline__ void backoff(int& it) { __nanosleep(SLEEP_); if (++it > SPIN_MAX) __trap(); }
__device__ __forceinline__ void wait_ge(const void* p, uint32_t v) {
    int it = 0;
    while (ld_relaxed(p) < v) backoff(it);
}

__device__ __forceinline__ bool elect_one() {
    uint32_t r; asm volatile("{.reg .pred p; elect.sync _|p, 0xffffffff; selp.u32 %0, 1, 0, p;}" : "=r"(r)); return r;
}
__device__ __forceinline__ void st_lane0(void* p, uint32_t v, int lane) {
    asm volatile("{.reg .pred p; setp.eq.s32 p, %2, 0; @p st.relaxed.gpu.global.u32 [%0], %1;}" ::"l"(p), "r"(v), "r"(lane) : "memory");
}
__device__ __forceinline__ void wait_all_ge(const void* p, uint32_t v) {
    int it = 0;
    while (!__all_sync(0xffffffffu, ld_relaxed(p) >= v)) backoff(it);
}
__device__ __forceinline__ void lds_lt(uint32_t& v, uint32_t ad, int a, int b) {
    asm volatile("{.reg .pred p; setp.lt.s32 p, %2, %3; @p ld.shared.u32 %0, [%1];}" : "+r"(v) : "r"(ad), "r"(a), "r"(b));
}

constexpr uint32_t R_V1 = 0x03000, R_A = 0x81000, R_B = 0x82000, R_UNIT = 0x4000, R_HI = 0x40000 - 8 * 256;
__device__ __forceinline__ uint32_t q_base(uint32_t q, uint32_t pagebits_x) { return (q << 20) | (((pagebits_x >> (q >> 1)) & 1u) << 12); }
__device__ __forceinline__ uint32_t slot_off(uint32_t s) { return (s << 16) | (((s + 1) & 2) << 11); }
constexpr uint32_t OFF_PF = R_B + 3 * R_UNIT, OFF_RDY = OFF_PF + 128, OFF_REL = OFF_PF + 256;
constexpr uint32_t OFF_PROBE = 3 * R_UNIT;
static_assert(RA <= 4 && RV <= 4 && RB <= 8 && RA <= RB && RV <= RB, "ring");

__device__ __forceinline__ uint32_t probe(unsigned char* p) {
    volatile uint32_t* sink = (volatile uint32_t*)(smem + S_MISC + 240);
    asm volatile("st.global.v4.u32 [%0], {%1,%1,%1,%1};" ::"l"(p), "r"(0) : "memory");
    asm volatile("st.global.v4.u32 [%0], {%1,%1,%1,%1};" ::"l"(p + 16), "r"(0) : "memory");
    uint32_t best = 0xffffffffu;
#pragma unroll 1
    for (int r = 0; r < 3; r++) {
        uint32_t t0, t1, v;
        asm volatile("mov.u32 %0, %%clock;" : "=r"(t0)::"memory");
        asm volatile("atom.relaxed.gpu.global.add.u32 %0, [%1], 1;" : "=r"(v) : "l"(p) : "memory");
        *sink = v;
        asm volatile("mov.u32 %0, %%clock;" : "=r"(t1)::"memory");
        best = min(best, t1 - t0);
    }
    return best;
}

struct Wts { float c[8], wr[32], ws[32], wd[16], wu[16]; };
__device__ __forceinline__ void load_wts(const Prm& p, Wts* w) {
    int t = threadIdx.x;
    if (t < 8) w->c[t] = __bfloat162float(p.centers[t]);
    if (t < 32) { w->wr[t] = __bfloat162float(p.w_rbf[t]); w->ws[t] = __bfloat162float(p.w_sbf[t]); }
    if (t < 16) { w->wd[t] = __bfloat162float(p.w_down[t]); w->wu[t] = __bfloat162float(p.w_up[t]); }
}
__device__ __forceinline__ void radial(const Wts* w, float d, float s[4], float g[4]) {
#pragma unroll
    for (int j = 0; j < 4; j++) s[j] = g[j] = 0.f;
#pragma unroll
    for (int r = 0; r < 8; r++) {
        float x = rbf16(d - w->c[r]);
        float b = rbf16(__expf(rbf16(-10.0f * rbf16(x * x))));
#pragma unroll
        for (int j = 0; j < 4; j++) { s[j] += b * w->ws[r * 4 + j]; g[j] += b * w->wr[r * 4 + j]; }
    }
}
__device__ __noinline__ uint4 radial_bf16(const Wts* w, uint32_t dbits) {
    float s[4], g[4];
    radial(w, __uint_as_float(dbits << 16), s, g);
    return make_uint4(pack_bf16(s[1], s[0]), pack_bf16(s[3], s[2]), pack_bf16(g[1], g[0]), pack_bf16(g[3], g[2]));
}
__device__ __forceinline__ uint2 finish_row(const float* wu, const float agg[4], const float g[4], uint2 r) {
    float o[4];
    const float mm[4] = {bf_lo(r.x), bf_hi(r.x), bf_lo(r.y), bf_hi(r.y)};
#pragma unroll
    for (int j = 0; j < 4; j++) o[j] = mm[j] + (agg[0] * wu[j] + agg[1] * wu[4 + j] + agg[2] * wu[8 + j] + agg[3] * wu[12 + j]) * g[j];
    return make_uint2(pack_bf16(o[1], o[0]), pack_bf16(o[3], o[2]));
}
__device__ __forceinline__ uint2 down_row(const float* wd, uint32_t x, uint32_t y) {
    const float a[4] = {bf_lo(x), bf_hi(x), bf_lo(y), bf_hi(y)};
    float d[4];
#pragma unroll
    for (int j = 0; j < 4; j++) d[j] = a[0] * wd[j] + a[1] * wd[4 + j] + a[2] * wd[8 + j] + a[3] * wd[12 + j];
    return make_uint2(pack_bf16(d[1], d[0]), pack_bf16(d[3], d[2]));
}

__device__ __forceinline__ void down_piece(const Prm& p, int pc, const float* wd) {
    const int tid = threadIdx.x, lane = tid & 31, w = tid >> 5;
    const int r0 = pc * PC_ROWS / 2, nr = max(min((pc + 1) * PC_ROWS, p.E) / 2 - r0, 0);
    const uint32_t bar = SB + S_AUX + 504;
    if (tid == 0) {
        mbar_init(bar, 1);
        asm volatile("fence.proxy.async.shared::cta;" ::: "memory");
        asm volatile("mbarrier.arrive.expect_tx.shared.b64 _, [%0], %1;" ::"r"(bar), "r"(nr * 16) : "memory");
        for (int o = 0; o < nr; o += 1024)
            asm volatile("cp.async.bulk.shared::cluster.global.mbarrier::complete_tx::bytes [%0], [%1], %2, [%3];"
                         ::"r"(SB + o * 16), "l"((const uint4*)p.m + r0 + o), "r"(min(1024, nr - o) * 16), "r"(bar) : "memory");
    }
    __syncthreads();
    mbar_wait(bar, 0);
    uint32_t mx0 = 0, mx1 = 0; float ss[4] = {0.f, 0.f, 0.f, 0.f};
    for (int r = tid; r < nr; r += THREADS) {
        const uint4 v = ((const uint4*)smem)[r];
        const uint2 a = down_row(wd, v.x, v.y), b = down_row(wd, v.z, v.w);
        ((uint2*)g_md[0])[r0 + r] = make_uint2(a.x, b.x); ((uint2*)g_md[1])[r0 + r] = make_uint2(a.y, b.y);
        mx0 = __vimax3_u16x2(mx0, a.x & 0x7fff7fffu, b.x & 0x7fff7fffu); mx1 = __vimax3_u16x2(mx1, a.y & 0x7fff7fffu, b.y & 0x7fff7fffu);
        ss[0] += bf_lo(a.x) * bf_lo(a.x) + bf_lo(b.x) * bf_lo(b.x); ss[1] += bf_hi(a.x) * bf_hi(a.x) + bf_hi(b.x) * bf_hi(b.x);
        ss[2] += bf_lo(a.y) * bf_lo(a.y) + bf_lo(b.y) * bf_lo(b.y); ss[3] += bf_hi(a.y) * bf_hi(a.y) + bf_hi(b.y) * bf_hi(b.y);
    }
    uint32_t st[4] = {mx0 << 16, mx0 & 0xffff0000u, mx1 << 16, mx1 & 0xffff0000u};
    uint4* red = (uint4*)(smem + PC_ROWS * 8);
    for (int pass = 0; pass < 2; pass++) {
#pragma unroll
        for (int ch = 0; ch < 4; ch++) {
            st[ch] = __reduce_max_sync(0xffffffffu, st[ch]);
#pragma unroll
            for (int o = 16; o; o >>= 1) ss[ch] += __shfl_xor_sync(0xffffffffu, ss[ch], o);
        }
        uint4* dst = pass ? (uint4*)g_ctl.stat[pc] : red + 2 * w;
        if (lane == 0) { dst[0] = make_uint4(st[0], st[1], st[2], st[3]); dst[1] = make_uint4(__float_as_uint(ss[0]), __float_as_uint(ss[1]), __float_as_uint(ss[2]), __float_as_uint(ss[3])); }
        if (pass) break;
        __syncthreads();
        const uint4 a = lane < NW ? red[2 * lane] : make_uint4(0, 0, 0, 0), b = lane < NW ? red[2 * lane + 1] : make_uint4(0, 0, 0, 0);
        __syncthreads();
        if (w != 0) return;
        st[0] = a.x; st[1] = a.y; st[2] = a.z; st[3] = a.w;
        ss[0] = __uint_as_float(b.x); ss[1] = __uint_as_float(b.y); ss[2] = __uint_as_float(b.z); ss[3] = __uint_as_float(b.w);
    }
    if (lane == 0) { fence_release(); red_add(&g_ctl.pieces_done, 1); }
    __syncwarp();
}

__device__ __forceinline__ void get_scales(const Prm& p, float sc[4], bool& bad) {
    const int lane = threadIdx.x & 31;
    uint32_t mxb[4] = {0, 0, 0, 0};
    float ss[4] = {0.f, 0.f, 0.f, 0.f};
#pragma unroll
    for (int k = 0; k < (NPC + 31) / 32; k++) {
        if (lane + 32 * k < NPC) {
            const uint4 a = ld_relaxed4(&g_ctl.stat[lane + 32 * k][0]), b = ld_relaxed4(&g_ctl.stat[lane + 32 * k][4]);
            mxb[0] = max(mxb[0], a.x); mxb[1] = max(mxb[1], a.y); mxb[2] = max(mxb[2], a.z); mxb[3] = max(mxb[3], a.w);
            ss[0] += __uint_as_float(b.x); ss[1] += __uint_as_float(b.y); ss[2] += __uint_as_float(b.z); ss[3] += __uint_as_float(b.w);
        }
    }
    bad = false;
    const float kdeg = fminf(3.5f * sqrtf(fmaxf(0.5f * (float)p.T / (float)p.E, 1.0f)), 128.f);
#pragma unroll
    for (int ch = 0; ch < 4; ch++) {
        float mx = __uint_as_float(__reduce_max_sync(0xffffffffu, mxb[ch]));
#pragma unroll
        for (int o = 16; o; o >>= 1) ss[ch] += __shfl_xor_sync(0xffffffffu, ss[ch], o);
        float rms = sqrtf(ss[ch] / (float)p.E);
        float range = fmaxf(4.002f * mx, kdeg * rms);
        if (!(mx <= 1e15f) || !(range <= 128.f * rms) || (mx > 0.f && mx < 1e-15f)) bad = true;
        sc[ch] = range > 0.f ? 32767.f / range : 0.f;
    }
}

constexpr int PER = 40;
struct __align__(16) PTab { uint32_t e[PER][4]; };
constexpr PTab make_ptab() {
    PTab t = {};
    for (int s = 0; s < PER; s++) {
        for (int d = 0; d < GR; d++) {
            int gi = (s + d) % GR, buf = (s + d) % NBUF, X = gi & 1, g = gi >> 1;
            t.e[s][X] |= (uint32_t)(4 * UN * buf - g - 4 * X + 7) << (8 * g);
        }
        int mnew = s + GR - 1;
        t.e[s][2] = (uint32_t)(SB + P_BAR + (NBUF + mnew % NBUF) * 8) | (uint32_t)(((mnew / NBUF) & 1) ^ 1) << 31;
        t.e[s][3] = (uint32_t)(SB + P_BAR + (s % NBUF) * 8) | (uint32_t)((s + 1) % PER) << 16;
    }
    return t;
}
__constant__ PTab c_ptab = make_ptab();
constexpr int BIAS = 7 * NCP;
static_assert(NG == 4 && CPS >= FW, "group selection");

struct PCtx { uint32_t a0, a1; };
struct PElem { uint32_t b4, aw, ol, r2; };

__device__ __forceinline__ void p_bin(const PCtx& c, PElem& e, uint32_t i, uint32_t o, uint32_t cw, uint32_t csel) {
    uint32_t ib = __umulhi(i, MAG_I), ob = __umulhi(o, MAG_O), sel = ib & 3;
    asm("{.reg .pred p; setp.ge.u32 p, %1, %2; @p add.u32 %0, %0, 4;}" : "+r"(sel) : "r"(o), "n"(HALF_O));
    e.b4 = __dp4a(prmt(c.a0, c.a1, sel), (uint32_t)NCP, ib * NCP + ob * 4);
    e.aw = prmt(i - ib * ROWS_I, cw, csel);
    e.ol = o - ob * ROWS_O;
}
__device__ __forceinline__ void p_rank(PElem& e) {
    asm volatile("atom.shared.add.u32 %0, [%1+%2], 2;" : "=r"(e.r2) : "r"(e.b4), "n"(SB + P_CNT - BIAS) : "memory");
}
__device__ __forceinline__ void p_store(const PElem& e) {
    const uint32_t ab = e.b4 * (KS / 2) + e.r2;
    asm volatile("{.reg .pred p; setp.lt.u32 p, %4, %5; @p st.shared.u32 [%0+%6], %1; @p st.shared.u16 [%2+%7], %3;}"
                 ::"r"(ab * 2), "r"(e.aw), "r"(ab), "h"((uint16_t)e.ol), "r"(e.r2), "n"(KS * 2),
                   "n"(SB + P_A - BIAS * KS), "n"(SB + P_B - BIAS * (KS / 2)) : "memory");
}
__device__ __noinline__ uint32_t cos2_slow(uint32_t x) {
    float a = cosf(bf_lo(x)), b = cosf(bf_hi(x));
    if (!(fabsf(a + b) <= 2.f)) { st_relaxed(&g_ctl.bad, 1); a = b = 0.f; }
    return pack_bf16(b, a);
}

struct PIn { uint4 i, o; uint2 a; };
__device__ __forceinline__ void p_fetch(const Prm& p, PIn& x, uint32_t ch, uint32_t lane) {
    const int v = ch * 32 + lane;
    asm volatile("{.reg .b32 d0, d1; tex.1d.v4.u32.s32 {%0,%1,d0,d1}, [%2, {%3}];}" : "=r"(x.a.x), "=r"(x.a.y) : "l"(p.t_ang), "r"(v));
    asm volatile("tex.1d.v4.u32.s32 {%0,%1,%2,%3}, [%4, {%5}];" : "=r"(x.i.x), "=r"(x.i.y), "=r"(x.i.z), "=r"(x.i.w) : "l"(p.t_in), "r"(v));
    asm volatile("tex.1d.v4.u32.s32 {%0,%1,%2,%3}, [%4, {%5}];" : "=r"(x.o.x), "=r"(x.o.y), "=r"(x.o.z), "=r"(x.o.w) : "l"(p.t_out), "r"(v));
}

struct PFill {
    PCtx c;
    uint32_t qb, qt, lt, f2, nxt, fre;
    uint32_t q, lane;
    bool open;
    __device__ __forceinline__ void begin() { begin(nxt >> 16); }
    __device__ __forceinline__ uint32_t ticket(uint32_t zero) {
        uint32_t t;
        asm volatile("atom.shared.add.u32 %0, [%1+%2], %3;" : "=r"(t) : "r"(lane * 4), "n"(SB + P_TKT), "r"((~lt & 1) | zero) : "memory");
        return t;
    }
    __device__ __forceinline__ uint32_t use_ticket(uint32_t t) {
        t = __reduce_or_sync(0xffffffffu, t);
        begin((t / CPS + q % GR) % PER);
        return t + 2 * FW;
    }
    __device__ __forceinline__ void begin(uint32_t idx) {
        const uint2* t = (const uint2*)c_ptab.e + 2 * idx;
        const uint2 m = t[0], s = t[1];
        c.a0 = m.x; c.a1 = m.y;
        nxt = s.y; fre = s.x;
        open = mbar_test(fre & 0xffff, fre >> 31);
    }
    __device__ __forceinline__ void enter() { if (!open) mbar_wait(fre & 0xffff, fre >> 31); }
    __device__ __forceinline__ void end() {
        __syncwarp();
        asm volatile("{.reg .pred p; setp.eq.u32 p, %1, 0; @p mbarrier.arrive.shared.b64 _, [%0];}" ::"r"(nxt & 0xffff), "r"(lt) : "memory");
    }
    __device__ __forceinline__ void push(bool f, uint32_t x, uint32_t y) {
        uint32_t mask = __ballot_sync(0xffffffffu, f);
        asm volatile("{.reg .pred p; setp.ne.u32 p, %3, 0; @p st.shared.v2.u32 [%0], {%1,%2};}" ::"r"(qt + __popc(mask & lt) * 8), "r"(x), "r"(y), "r"((uint32_t)f) : "memory");
        qt += __popc(mask) * 8;
    }
    __device__ __forceinline__ void push_checked(bool f, uint32_t i, uint32_t o, uint32_t aw) {
        if (qt - qb + __popc(__ballot_sync(0xffffffffu, f)) * 8 > QN * 8) st_relaxed(&g_ctl.bad, 1);
        else push(f, prmt(i, aw, 0x6210), prmt(o, aw, 0x7210));
    }
    __device__ __forceinline__ uint32_t chunk(const PIn& x) {
        uint32_t x0, x1, c0, c1;
        asm("mul.rn.bf16x2 %0, %1, %2;" : "=r"(x0) : "r"(x.a.x), "r"(f2));
        asm("mul.rn.bf16x2 %0, %1, %2;" : "=r"(x1) : "r"(x.a.y), "r"(f2));
        uint32_t tk = ticket(x.o.x >> 31);
        c0 = pack_bf16(__cosf(bf_hi(x0)), __cosf(bf_lo(x0)));
        c1 = pack_bf16(__cosf(bf_hi(x1)), __cosf(bf_lo(x1)));
        if (__any_sync(0xffffffffu, (((x0 & 0x7fff7fffu) + 0x3e003e00u) | ((x1 & 0x7fff7fffu) + 0x3e003e00u)) & 0x80008000u)) { c0 = cos2_slow(x0); c1 = cos2_slow(x1); }
        tk = use_ticket(tk);
        PElem e0, e1, e2, e3;
        p_bin(c, e0, x.i.x, x.o.x, c0, 0x5410); p_bin(c, e1, x.i.y, x.o.y, c0, 0x7610);
        p_bin(c, e2, x.i.z, x.o.z, c1, 0x5410); p_bin(c, e3, x.i.w, x.o.w, c1, 0x7610);
        asm volatile("" : "+r"(e0.b4), "+r"(e1.b4), "+r"(e2.b4), "+r"(e3.b4));
        enter();
        p_rank(e0); p_rank(e1); p_rank(e2); p_rank(e3);
        p_store(e0); p_store(e1); p_store(e2); p_store(e3);
        if (qt - qb >= QTRIG * 8) {
            retry(32);
            if (qt - qb > (QN - 32) * 8) { st_relaxed(&g_ctl.bad, 1); qt = qb; }
        }
        end();
        const uint32_t r01 = e0.r2 | e1.r2, r23 = e2.r2 | e3.r2;
        const bool f = (r01 | r23) >= KS * 2;
        if (__any_sync(0xffffffffu, f)) {
            const bool f0 = e0.r2 >= KS * 2, f1 = e1.r2 >= KS * 2, f2_ = e2.r2 >= KS * 2, f3 = e3.r2 >= KS * 2, f01 = r01 >= KS * 2;
            uint32_t si = f01 ? (f0 ? x.i.x : x.i.y) : (f2_ ? x.i.z : x.i.w);
            uint32_t so = f01 ? (f0 ? x.o.x : x.o.y) : (f2_ ? x.o.z : x.o.w);
            uint32_t sc = f01 ? (f0 ? e0.aw : e1.aw) : (f2_ ? e2.aw : e3.aw);
            push(f, prmt(si, sc, 0x6210), prmt(so, sc, 0x7210));
            uint32_t s2 = max(max(min(e0.r2, e1.r2), min(e2.r2, e3.r2)), min(r01, r23));
            if (__any_sync(0xffffffffu, s2 >= KS * 2)) {
                push_checked(f1 && f0, x.i.y, x.o.y, e1.aw);
                push_checked(f2_ && f01, x.i.z, x.o.z, e2.aw);
                push_checked(f3 && (f01 || f2_), x.i.w, x.o.w, e3.aw);
            }
        }
        return tk;
    }
    __device__ __forceinline__ void retry(uint32_t take) {
        const uint32_t lane8 = (threadIdx.x & 31) * 8;
        uint2 e, r0, r1;
        __syncwarp();
        asm volatile("ld.shared.v2.u32 {%0,%1}, [%2];" : "=r"(e.x), "=r"(e.y) : "r"(qb + lane8) : "memory");
        asm volatile("ld.shared.v2.u32 {%0,%1}, [%2];" : "=r"(r0.x), "=r"(r0.y) : "r"(qb + lane8 + take * 8) : "memory");
        qt -= take * 8;
        const bool more = qt - qb > 256;
        if (more) asm volatile("ld.shared.v2.u32 {%0,%1}, [%2];" : "=r"(r1.x), "=r"(r1.y) : "r"(qb + lane8 + take * 8 + 256) : "memory");
        __syncwarp();
        if (qb + lane8 < qt) asm volatile("st.shared.v2.u32 [%0], {%1,%2};" ::"r"(qb + lane8), "r"(r0.x), "r"(r0.y) : "memory");
        if (more && qb + lane8 + 256 < qt) asm volatile("st.shared.v2.u32 [%0], {%1,%2};" ::"r"(qb + lane8 + 256), "r"(r1.x), "r"(r1.y) : "memory");
        PElem el;
        el.r2 = 0;
        if (lane8 < take * 8) {
            p_bin(c, el, e.x & 0xffffffu, e.y & 0xffffffu, prmt(e.x, e.y, 0x0073), 0x5410);
            p_rank(el);
            p_store(el);
        }
        push(el.r2 >= KS * 2, e.x, e.y);
    }
};

__device__ __forceinline__ void p_filler(const Prm& p, int q, int w) {
    PFill F;
    const int lane = threadIdx.x & 31;
    F.lt = __shfl_sync(0xffffffffu, (1u << lane) - 1u, lane);
    F.qb = F.qt = SB + P_Q + w * (QN * 8);
    F.f2 = __shfl_sync(0xffffffffu, __bfloat16_as_ushort(p.freq[0]) * 0x10001u, 0);
    const uint32_t NS = p.NS, cend = p.T >> 7, s0 = q % GR, nv = NS * CPS, nc = (cend + NP - 1 - q) / NP;
    PIn x0, x1;
    uint32_t c0 = w, c1 = w + FW;
    F.q = q; F.lane = lane;
    p_fetch(p, x0, c0 * NP + q, lane);
#pragma unroll 1
    while (c0 < nc) {
        p_fetch(p, x1, c1 * NP + q, lane);
        c0 = F.chunk(x0);
        if (c1 >= nc) break;
        p_fetch(p, x0, c0 * NP + q, lane);
        c1 = F.chunk(x1);
    }
#pragma unroll 1
    while (min(c0, c1) < nv) { c0 = max(c0, c1); c1 = F.use_ticket(F.ticket(0)); F.enter(); F.end(); }
    F.nxt = ((NS + s0) % PER) << 16;
    uint32_t n = NS;
    if (q == 0 && w < 4) {
        int t = cend * 128 + w * 32 + lane;
        bool f = t < p.T;
        uint32_t i = 0, o = 0, x = 0;
        if (f) { i = p.idx_in[t]; o = p.idx_out[t]; asm("mul.rn.bf16x2 %0, %1, %2;" : "=r"(x) : "r"((uint32_t)__bfloat16_as_ushort(p.angle[t]) << 16), "r"(F.f2)); }
        F.push_checked(f, i, o, cos2_slow(x & 0xffff0000u));
    }
#pragma unroll 1
    for (; n <= NS + GR; n++) {
        F.begin(); F.enter();
        for (uint32_t nq = (F.qt - F.qb) >> 3; nq > 0;) { uint32_t take = min(nq, 32u); F.retry(take); nq -= take; }
        F.end();
        if (CPS > FW && w < CPS - FW) F.end();
    }
    if (F.qt != F.qb) st_relaxed(&g_ctl.bad, 1);
}

template <int N> __device__ __forceinline__ void p_stamp(const uint32_t (&st)[N], uint32_t off, uint32_t bit, bool set) {
    if (set) {
#pragma unroll
        for (int j = 0; j < N; j++) asm volatile("red.shared.or.b32 [%0], %1;" ::"r"(st[j] + off), "r"(bit) : "memory");
    } else {
#pragma unroll
        for (int j = 0; j < N; j++) asm volatile("red.shared.and.b32 [%0], %1;" ::"r"(st[j] + off), "r"(~bit) : "memory");
    }
}
__device__ __forceinline__ void bulk_store(void* dst, uint32_t src, uint32_t bytes) {
    asm volatile("cp.async.bulk.global.shared::cta.bulk_group [%0], [%1], %2;" ::"l"(dst), "r"(src), "r"(bytes) : "memory");
}
#define ROUNDS_ 1
__device__ __forceinline__ void p_flusher(const Prm& p, unsigned char* ring, uint32_t pagebits, int q, int f) {
    const int lane = threadIdx.x & 31;
    const uint32_t bar = SB + P_BAR;
    const uint32_t NS = p.NS, NT = NS + 2 * GR, s0 = q % GR;
    uint32_t sta[5], stb[7];
#pragma unroll
    for (int j = 0; j < 7; j++) {
        const int bin = min(8 * j + (lane >> 2), NB - 1);
        const int ps = j < 4 ? 4 * (j >> 1) + (lane >> 3) : 8, l = j < 4 ? 2 * (j & 1) + ((lane >> 2) & 1) : (lane >> 2) & 3;
        stb[j] = SB + P_B + bin * 128 + (lane & 3) * 32 + ((bin % NCP) & 3) * 8;
        if (j < 5) sta[j] = SB + P_A + ps * 512 + l * 128 + (l & 1) * 16 + (lane & 3) * 32 + (ps & 3) * 4;
    }
    const uint32_t pfo = OFF_PF + (lane / 6) * 32 + (lane & 1) * 16 + ((lane % 6) >> 1) * 4, pfc = (lane >> 1) * 6 + (lane & 1);
    const uint32_t wto = lane < NCP ? OFF_REL + lane * 4 : OFF_RDY + (lane % 6) * 4;
    PROF_DECL
#pragma unroll 1
    for (uint32_t n = f; n < NT; n += NF) {
        const uint32_t buf = (n + s0) % NBUF, h = n >> 1, lap = h / RB;
        const uint32_t qb = q_base(q, pagebits) ^ (((n + q) & 1) << 12), bb = qb ^ slot_off(h % RB);
        if (h >= RA && !DEV_FREE) {
            const uint32_t hw = lane < NCP ? h : h + RB - RA;
            wait_all_ge(ring + (qb ^ slot_off(hw % RB) ^ wto), (hw / RB) << (lane < NCP ? 0 : 1));
        }
        PROF(0);
#pragma unroll
        for (int d = 2; d >= 0; d--) {
            const int nl = (int)min(n, NS + GR) - d;
            if (nl >= 0) mbar_wait(bar + ((nl + s0) % NBUF) * 8, ((nl + s0) / NBUF) & 1);
        }
        PROF(1);
        uint32_t* cnt = (uint32_t*)(smem + P_CNT) + buf * NB;
        bool any = true;
        if (n >= NS) any = __any_sync(0xffffffffu, lane < NCP && (cnt[lane] | cnt[NCP + lane] | cnt[2 * NCP + lane]));
        if (any) {
            const uint32_t oa = buf * (NB * KS * 4), ob = buf * (NB * KS * 2);
            unsigned char* da = ring + (qb ^ slot_off(h % RA) ^ R_A);
            unsigned char* db = ring + (bb ^ R_B);
            int sent = 0;
#pragma unroll
            for (int u = 0; u <= UN; u++) {
                if (u < UN) p_stamp(sta, oa + u * (NCP * KS * 4), 0x40000000u, (h / RA) & 1);
                else p_stamp(stb, ob, 0x8000u, lap & 1);
                if (u == UN || (ROUNDS_ >= 2 && u == 0) || (ROUNDS_ >= 3 && u == 2)) {
                    __syncwarp();
                    if (elect_one()) {
                        asm volatile("fence.proxy.async.shared::cta;" ::: "memory");
#pragma unroll
                        for (int v = sent; v <= u; v++) {
                            if (v < UN) {
                                bulk_store(da + v * R_UNIT, SB + P_A + oa + v * (NCP * KS * 4), 8 * KS * 4);
                                bulk_store(da + v * R_UNIT + 0x40000, SB + P_A + oa + (v * NCP + 8) * (KS * 4), (NCP - 8) * KS * 4);
                            } else {
#pragma unroll
                                for (int k = 0; k < UN; k++) bulk_store(db + k * R_UNIT, SB + P_B + ob + k * (NCP * KS * 2), NCP * KS * 2);
                            }
                        }
                    }
                    __syncwarp();
                    sent = u + 1;
                }
            }
        }
        uint32_t wm = ((lap + 1) << 22) | ((uint32_t)any << 21);
        if (lane < NCP) {
#pragma unroll
            for (int u = 0; u < 3; u++) wm |= min(cnt[pfc + 2 * u] >> 1, (uint32_t)KS) << (7 * u);
        }
        __syncwarp();
        if (lane < NB / 2) ((uint2*)cnt)[lane] = make_uint2(0, 0);
        PROF(3);
        asm volatile("cp.async.bulk.commit_group;" ::: "memory");
        asm volatile("cp.async.bulk.wait_group 0;" ::: "memory");
        __syncwarp();
        PROF(2);
        const bool safe = h < RB || n >= NS;
        if (!safe && lane < NCP) st_relaxed(ring + (bb ^ pfo), wm);
        if (n > 0) mbar_wait(bar + (NBUF + (n - 1 + s0) % NBUF) * 8, ((n - 1 + s0) / NBUF) & 1);
        if (lane == 0) mbar_arrive(bar + (NBUF + buf) * 8);
        if (safe) {
            if (any) fence_release();
            if (lane < NCP) st_relaxed(ring + (bb ^ pfo), wm);
        }
        PROF(4);
    }
    PROF_END;
}
__device__ __forceinline__ void p_cleanup(unsigned char* ring, int q) {
    const int k = threadIdx.x / 24;
    if (k < 2 * RB) *(uint4*)(ring + ((q << 20) ^ ((k & 1) << 12) ^ slot_off(k >> 1) ^ OFF_PF) + (threadIdx.x % 24) * 16) = make_uint4(0, 0, 0, 0);
}

__device__ __forceinline__ void m_role(const Prm& p, unsigned char* ring, int X, int id) {
    const int tid = threadIdx.x, lane = tid & 31, w = __shfl_sync(0xffffffffu, tid >> 5, 0);
    const int ib = id >> 1, ty = id & 1;
    float* scs = (float*)(smem + S_MISC);
    if (w == 0) {
        const uint32_t bar = SB + S_AUX;
        if (lane == 0) mbar_init(bar, 1);
        wait_ge(&g_ctl.pieces_done, NPC);
        fence_acquire();
        if (lane == 0) {
            asm volatile("fence.proxy.async.global;" ::: "memory");
            asm volatile("fence.proxy.async.shared::cta;" ::: "memory");
            asm volatile("mbarrier.arrive.expect_tx.shared.b64 _, [%0], %1;" ::"r"(bar), "r"(ROWS_I * 4) : "memory");
            constexpr uint32_t PART = (ROWS_I * 4 / 8 + 127) / 128 * 128;
            for (uint32_t o = 0; o < ROWS_I * 4; o += PART)
                asm volatile("cp.async.bulk.shared::cluster.global.mbarrier::complete_tx::bytes [%0], [%1], %2, [%3];"
                             ::"r"(SB + o), "l"((const char*)(g_md[ty] + ib * ROWS_I) + o), "r"(min(PART, ROWS_I * 4 - o)), "r"(bar) : "memory");
        }
        __syncwarp();
            float sc[4]; bool bad;
        get_scales(p, sc, bad);
            if (bad) { st_relaxed(&g_ctl.bad, 1); sc[0] = sc[1] = sc[2] = sc[3] = 0.f; }
        int it = 0; uint32_t pb;
        while (!((pb = ld_relaxed(&g_ctl.pagebits)) >> 31)) backoff(it);
        if (lane == 0) { scs[0] = sc[0]; scs[1] = sc[1]; scs[2] = sc[2]; scs[3] = sc[3]; ((uint32_t*)scs)[4] = X ? ~pb : pb; ((uint32_t*)scs)[5] = bad; }
        mbar_wait(bar, 0);
    }
    __syncthreads();
    if (((uint32_t*)scs)[5]) {
        for (int k = tid; k < (int)ROWS_I; k += THREADS) ((uint32_t*)smem)[k] = 0;
        __syncthreads();
    }
    const uint32_t NT = p.NS + 2 * GR;
    if (w >= MW) return;
    const uint32_t pagebits = ((uint32_t*)scs)[4];
    const int half = lane >> 4, k4 = (lane & 15) * 4;
    const float s_lo = scs[2 * ty], s_hi = scs[2 * ty + 1];
    const float MAG_LO = 12582912.f, MAG_HI = 12582912.f - 19264.f;
    const int il = ib / NG, gi = (ib % NG) * 2 + X;
    const uint32_t a_off = R_A + il * R_UNIT + lane * 16, v_off = ty * R_V1 + il * R_UNIT + lane * 16;
    const uint32_t f_off = OFF_PF + il * 32 + half * 16, r_off = OFF_REL + (lane % NCP) * 4;
    const uint32_t j = w % (NP / GR);
    PROF_DECL
#pragma unroll 1
    for (uint32_t n = w / (NP / GR); n < NT; n += MW / (NP / GR)) {
        const uint32_t q = ((gi - n) & (GR - 1)) + GR * j, h = n >> 1;
        const uint32_t qb = q_base(q, pagebits), bb = qb ^ slot_off(h % RB);
        const uint32_t tag = (h / RB + 1) << 22;
        uint4 cw; int it = 0;
        while (true) {
            cw = ld_relaxed4(ring + (bb ^ f_off));
            if (__all_sync(0xffffffffu, min(min(cw.x, cw.y), cw.z) >= tag)) break;
            if (DEV_FREE) { cw.x = (cw.x & 1) + (63 | 57 << 7 | 50 << 14 | 1 << 21); cw.y = (cw.y & 1) + (53 | 61 << 7 | 57 << 14); cw.z = (cw.z & 1) + (59 | 52 << 7 | 57 << 14); break; }
            backoff(it);
        }
        PROF(0);
        if (__any_sync(0xffffffffu, cw.x & (1u << 21))) {
            const unsigned char* pa = ring + (qb ^ slot_off(h % RA) ^ a_off);
            unsigned char* pv = ring + (qb ^ slot_off(h % RV) ^ v_off);
            const uint32_t hv = h + RB - RV;
            const unsigned char* prel = ring + (qb ^ slot_off(hv % RB) ^ r_off);
            const uint32_t rel = ld_relaxed(prel);
            const uint32_t vlap = h / RV;
            const float mag_lo0 = MAG_LO + (float)(8192 + (vlap & 3) * 16384), mag_hi0 = MAG_HI + (float)(8192 + ((vlap >> 2) & 3) * 16384);
            const uint32_t stamp = ((h / RA) & ~(lane ^ (lane >> 3)) & 1) << 30;
            uint4 a[9];
#define M_LOAD(ps) a[ps] = ld_relaxed4(pa + (ps) * 512 + ((ps) < 4 ? 0 : R_HI))
#pragma unroll
            for (int ps = 0; ps < MPF; ps++) M_LOAD(ps);
            if (!__all_sync(0xffffffffu, rel >= hv / RB) && !DEV_FREE) wait_all_ge(prel, hv / RB);
            PROF(3);
#pragma unroll
            for (int ps = 0; ps < 9; ps++) {
                const int rem = (int)(((ps < 3 ? cw.x : ps < 6 ? cw.y : cw.z) >> (7 * (ps % 3))) & 0x7f) - k4;
                if (ps % 3 == 0) {
#define M_STAMP(ps) (((ps) & 3) == 0 ? a[ps].x : ((ps) & 3) == 1 ? a[ps].y : ((ps) & 3) == 2 ? a[ps].z : a[ps].w)
                    while (true) {
                        M_STAMP(ps) ^= stamp; M_STAMP(ps + 1) ^= stamp; M_STAMP(ps + 2) ^= stamp;
                        if (!__any_sync(0xffffffffu, (M_STAMP(ps) | M_STAMP(ps + 1) | M_STAMP(ps + 2)) & 0x40000000u)) break;
                        if (DEV_FREE) { M_STAMP(ps) &= 0xbfffffffu; M_STAMP(ps + 1) &= 0xbfffffffu; M_STAMP(ps + 2) &= 0xbfffffffu; break; }
                        if (++it > SPIN_MAX) __trap();
                        M_LOAD(ps); M_LOAD(ps + 1); M_LOAD(ps + 2);
                    }
                }
                uint32_t aw[4] = {a[ps].x, a[ps].y, a[ps].z, a[ps].w}, mv[4], vw[4];
#pragma unroll
                for (int e = 0; e < 4; e++) { mv[e] = 0; lds_lt(mv[e], __dp2a_lo(aw[e], 4u, (uint32_t)SB), e, rem); }
#pragma unroll
                for (int e = 0; e < 4; e++) {
                    float c = bf_hi(aw[e]);
                    float lo = fmaf(bf_lo(mv[e]), c * s_lo, e ? MAG_LO : mag_lo0), hi = fmaf(bf_hi(mv[e]), c * s_hi, e ? MAG_HI : mag_hi0);
                    vw[e] = (__float_as_uint(hi) << 16) + __float_as_uint(lo);
                }
                asm volatile("st.global.v4.u32 [%0], {%1,%2,%3,%4};" ::"l"(pv + ps * 512 + (ps < 4 ? 0 : R_HI)), "r"(vw[0]), "r"(vw[1]), "r"(vw[2]), "r"(vw[3]) : "memory");
                if (ps + MPF < 9) M_LOAD(ps + MPF);
            }
            if (vlap == 0 || n >= p.NS) fence_release();
        }
        st_lane0(ring + (bb ^ (OFF_RDY + (2 * il + ty) * 4)), cw.x >> 21, lane);
        PROF(1);
    }
    PROF_END;
}

__device__ __noinline__ void c_wrap(uint32_t row, int par, uint32_t old, uint32_t w) {
    const uint32_t nw = old + w, ov = ~(old ^ w) & (old ^ nw);
    int d = 0;
    if (ov & 0x8000u) d += (w & 0x8000u) ? -1 : 1;
    if (ov & 0x80000000u) d += (w & 0x80000000u) ? -16 : 16;
    if (d != 0) {
        uint32_t c;
        asm volatile("atom.shared.add.u32 %0, [%1], %2;" : "=r"(c) : "r"(SB + C_WRAP + row * 4), "r"(d << (8 * par)) : "memory");
        c = (c >> (8 * par)) + d;
        if (((c + 1) & 0xe) == 0 || ((c + 16) & 0xe0) == 0) st_relaxed(&g_ctl.bad, 1);
    }
}

#define CGRP 6
struct CTask { uint4 v[3]; uint2 b[3]; };
struct CWork {
    unsigned char* ring;
    uint32_t v_off, b_off, f_off, r_off, acc;
    uint32_t lap1, sv, sb, vtag, fw, stamp;
    int lane, dev_free;
    template <int ODD> __device__ __forceinline__ bool issue(CTask& t) {
        if (!__all_sync(0xffffffffu, fw >= 2 * lap1)) {
            int it = 0;
            do {
                if (dev_free) { fw = 1; break; }
                backoff(it);
                fw = ld_relaxed(ring + (f_off ^ slot_off(sb) ^ (ODD << 20)));
            } while (!__all_sync(0xffffffffu, fw >= 2 * lap1));
        }
        const bool data = __any_sync(0xffffffffu, fw & 1);
        if (data) {
            const unsigned char* pv = ring + (v_off ^ slot_off(sv) ^ (ODD << 20));
            const unsigned char* pb = ring + (b_off ^ slot_off(sb) ^ (ODD << 20));
#pragma unroll
            for (int ps = 0; ps < 3; ps++) {
                t.v[ps] = ld_relaxed4(pv + ps * R_UNIT);
                t.b[ps] = ld_relaxed2(pb + ps * R_UNIT);
            }
        }
        fw = ld_relaxed(ring + (f_off ^ slot_off(ODD ? (sb + 1 == RB ? 0 : sb + 1) : sb) ^ (!ODD << 20)));
        return data;
    }
    template <int ODD> __device__ __forceinline__ void arrive(CTask& t, bool data) {
        if (data) {
            int it = 0;
            while (true) {
#pragma unroll
                for (int ps = 0; ps < 3; ps++) t.b[ps].x ^= stamp;
                if (!__any_sync(0xffffffffu, (((t.v[0].x ^ vtag) | (t.v[1].x ^ vtag) | (t.v[2].x ^ vtag)) & 0xc000c000u) | ((t.b[0].x | t.b[1].x | t.b[2].x) & 0x8000u))) break;
                if (dev_free) { for (int ps = 0; ps < 3; ps++) { t.v[ps].x = (t.v[ps].x & 0x3fff3fffu) | (vtag & 0xc000c000u); t.b[ps].x &= 0xffff7fffu; } break; }
                if (++it > SPIN_MAX) __trap();
#pragma unroll
                for (int ps = 0; ps < 3; ps++) {
                    t.v[ps] = ld_relaxed4(ring + (v_off ^ slot_off(sv) ^ (ODD << 20)) + ps * R_UNIT);
                    t.b[ps] = ld_relaxed2(ring + (b_off ^ slot_off(sb) ^ (ODD << 20)) + ps * R_UNIT);
                }
            }
#pragma unroll
            for (int ps = 0; ps < 3; ps++) t.v[ps].x -= vtag;
        }
        st_lane0(ring + (r_off ^ slot_off(sb) ^ (ODD << 20)), lap1, lane);
        if (ODD) {
            if (++sv == RV) { sv = 0; vtag += 0x4000u; if (vtag & 0x10000u) vtag += 0x3fff0000u; }
            if (++sb == RB) { sb = 0; lap1++; stamp ^= (((b_off >> 3) ^ (b_off >> 7)) & 3) == 0 ? 0x8000u : 0u; }
        }
    }
    __device__ __forceinline__ void add(const CTask& t, bool data) {
        if (!data) return;
        const uint32_t vw[12] = {t.v[0].x, t.v[0].y, t.v[0].z, t.v[0].w, t.v[1].x, t.v[1].y, t.v[1].z, t.v[1].w, t.v[2].x, t.v[2].y, t.v[2].z, t.v[2].w};
        const uint32_t bw[6] = {t.b[0].x, t.b[0].y, t.b[1].x, t.b[1].y, t.b[2].x, t.b[2].y};
#pragma unroll
        for (int g = 0; g < 12; g += CGRP) {
            uint32_t old[CGRP], ov = 0;
#pragma unroll
            for (int e = g; e < g + CGRP; e++)
                asm volatile("atom.shared.add.u32 %0, [%1], %2;" : "=r"(old[e - g]) : "r"((e & 1) ? __dp2a_hi(bw[e >> 1], 0x08000008u, acc) : __dp2a_lo(bw[e >> 1], 0x08000008u, acc)), "r"(vw[e]) : "memory");
#pragma unroll
            for (int e = g; e < g + CGRP; e++) ov |= ~(old[e - g] ^ vw[e]) & (old[e - g] ^ (old[e - g] + vw[e]));
            if (__any_sync(0xffffffffu, ov & 0x80008000u)) {
#pragma unroll
                for (int e = g; e < g + CGRP; e++) c_wrap((e & 1) ? bw[e >> 1] >> 16 : bw[e >> 1] & 0xffffu, lane >> 4, old[e - g], vw[e]);
            }
        }
    }
};

__device__ __forceinline__ void c_role(const Prm& p, unsigned char* ring, int X, int c) {
    const int tid = threadIdx.x, lane = tid & 31, w = __shfl_sync(0xffffffffu, tid >> 5, 0);
    uint32_t* misc = (uint32_t*)(smem + S_MISC);
    Wts* wt = (Wts*)(smem + S_AUX);
    load_wts(p, wt);
    for (int k = tid; k < C_WRAP / 16; k += THREADS) ((uint4*)smem)[k] = make_uint4(0, 0, 0, 0);
    if (tid == 0) misc[6] = TAB_N;
    __syncthreads();
    if (w == 0) {
        float sc[4]; bool bad;
        wait_ge(&g_ctl.pieces_done, NPC);
        fence_acquire();
        get_scales(p, sc, bad);
        const float s = (lane & 2) ? ((lane & 1) ? sc[3] : sc[2]) : ((lane & 1) ? sc[1] : sc[0]);
        wt->ws[lane] *= s > 0.f ? 1.f / s : 0.f;
        int it = 0; uint32_t pb;
        while (!((pb = ld_relaxed(&g_ctl.pagebits)) >> 31)) backoff(it);
        misc[4] = X ? ~pb : pb;
    } else {
        const int r0 = (X * NCP + c) * ROWS_O, nr = min((int)ROWS_O, p.E - r0);
#pragma unroll 4
        for (int r = tid - 32; r < (int)ROWS_O / 2; r += THREADS - 32) {
            const uint32_t d2 = 2 * r < nr ? __ldg((const uint32_t*)(p.dist + r0) + r) : TAB_LO * 0x10001u;
            uint32_t e[2] = {(d2 & 0xffff) - TAB_LO, (d2 >> 16) - TAB_LO};
#pragma unroll
            for (int k = 0; k < 2; k++)
                if (e[k] >= TAB_N) {
                    const uint32_t d = e[k] + TAB_LO;
                    if ((d & 0x7f80) == 0x7f80) st_relaxed(&g_ctl.bad, 1);
                    e[k] = min(atomicAdd(&misc[6], 1u), 0xffffu);
                    if (e[k] < TAB_N + TAB_X) ((uint32_t*)(smem + C_TAB))[e[k] * 4] = d;
                }
            ((uint2*)(smem + C_WRAP))[r] = make_uint2(e[0] << 16 | 0x8888u, e[1] << 16 | 0x8888u);
        }
    }
    __syncthreads();
    if (w >= NP / 2) {
        const int nt = min(misc[6], (uint32_t)(TAB_N + TAB_X));
        for (int k = tid - NP * 16; k < nt; k += THREADS - NP * 16)
            ((uint4*)(smem + C_TAB))[k] = radial_bf16(wt, k < TAB_N ? TAB_LO + k : ((uint32_t*)(smem + C_TAB))[k * 4]);
        if (tid == THREADS - 1 && !DEV_FREE) {
            const uint32_t h = p.NS >> 1;
            const unsigned char* f = ring + (q_base(X, misc[4]) ^ slot_off(h % RB) ^ (OFF_REL + c * 4));
            for (int it = 0; ld_relaxed(f) < h / RB; it++) { __nanosleep(2000); if (it > SPIN_MAX) __trap(); }
            const int r0 = (X * NCP + c) * ROWS_O, nr = min((int)ROWS_O, p.E - r0);
            if (nr > 0) asm volatile("cp.async.bulk.prefetch.L2.global [%0], %1;" ::"l"(p.m + r0), "r"(nr * 8) : "memory");
        }
    }
    const uint32_t pagebits = misc[4];
    if (w >= NP / 2) return;
    CWork W;
    const int par = lane >> 4;
    W.ring = ring; W.lane = __shfl_sync(0xffffffffu, lane, lane); W.dev_free = DEV_FREE;
    const uint32_t qb = q_base(2 * w + X, pagebits), k = lane & 15;
    W.acc = __shfl_sync(0xffffffffu, SB + par * 4, lane);
    W.v_off = __shfl_sync(0xffffffffu, qb ^ (par * R_V1 + (c < 8 ? 0 : R_HI) + c * 256 + k * 16), lane);
    W.b_off = __shfl_sync(0xffffffffu, qb ^ (R_B + c * 128 + k * 8), lane);
    W.f_off = __shfl_sync(0xffffffffu, qb ^ (OFF_RDY + (lane % 6) * 4), lane);
    W.r_off = qb ^ (OFF_REL + c * 4);
    W.lap1 = 1; W.sv = W.sb = W.fw = W.stamp = 0; W.vtag = 0x20002000u;
    const uint32_t NT = p.NS + 2 * GR;
    CTask A, B;
    PROF_DECL
    bool da = W.issue<0>(A), db;
#pragma unroll 1
    for (uint32_t n = 2;; n += 2) {
        W.arrive<0>(A, da); PROF(1); db = W.issue<1>(B); PROF(0); W.add(A, da);
        W.arrive<1>(B, db);
        if (n >= NT) break;
        PROF(1); da = W.issue<0>(A); PROF(0); W.add(B, db);
    }
    W.add(B, db);
    PROF_END;
}

__device__ __forceinline__ uint32_t bf2_mul(uint32_t a, uint32_t b) { uint32_t r; asm("mul.rn.bf16x2 %0, %1, %2;" : "=r"(r) : "r"(a), "r"(b)); return r; }
__device__ __forceinline__ uint32_t bf2_fma(uint32_t a, uint32_t b, uint32_t c) { uint32_t r; asm("fma.rn.bf16x2 %0, %1, %2, %3;" : "=r"(r) : "r"(a), "r"(b), "r"(c)); return r; }
__device__ __forceinline__ uint32_t c_agg(uint32_t a, uint32_t s, uint32_t wr, bool wrapped) {
    int x0 = (short)a, x1 = ((int)a >> 16) + ((a >> 15) & 1);
    if (wrapped) { const int w0 = (int)(wr & 15) - 8, w1 = (int)((wr >> 4) & 15) - 8; x0 += 65536 * w0; x1 += 65536 * w1 - w0; }
    return pack_bf16((float)x1 * bf_hi(s), (float)x0 * bf_lo(s));
}
__device__ __forceinline__ void c_epilogue(const Prm& p, int X, int c) {
    const int tid = threadIdx.x, lane = tid & 31;
    const Wts* wt = (const Wts*)(smem + S_AUX);
    uint32_t bw[4];
#pragma unroll
    for (int k = 0; k < 4; k++) {
        const int col = (k >> 1) * 2 + ((lane >> 2) & 1), row = (k & 1) * 2;
        bw[k] = (lane >> 3) == (lane & 3) ? pack_bf16(wt->wu[(row + 1) * 4 + col], wt->wu[row * 4 + col]) : 0u;
    }
    const int r0 = (X * NCP + c) * ROWS_O, np = max(min((int)ROWS_O, p.E - r0), 0) / 2;
    const uint4* mp = (const uint4*)(p.m + r0);
    uint4* op = (uint4*)(p.out + r0);
    constexpr int EB = 5;
#pragma unroll 1
    for (int rb = tid; rb - lane < np; rb += EB * THREADS) {
        uint4 mr[EB];
#pragma unroll
        for (int k = 0; k < EB; k++) mr[k] = __ldg(mp + min(rb + k * THREADS, np - 1));
#pragma unroll
        for (int k = 0; k < EB; k++) {
            const int r = min(rb + k * THREADS, np - 1);
            const uint4 a = ((const uint4*)smem)[r];
            const uint2 wr = ((const uint2*)(smem + C_WRAP))[r];
            const uint4 t0 = ((const uint4*)(smem + C_TAB))[min(wr.x >> 16, (uint32_t)(TAB_N + TAB_X - 1))];
            const uint4 t1 = ((const uint4*)(smem + C_TAB))[min(wr.y >> 16, (uint32_t)(TAB_N + TAB_X - 1))];
            const bool wrapped = __any_sync(0xffffffffu, prmt(wr.x, wr.y, 0x5410) != 0x88888888u);
            uint32_t a0, a1, a2, a3;
            if (wrapped) { a0 = c_agg(a.x, t0.x, wr.x, true); a2 = c_agg(a.y, t0.y, wr.x >> 8, true); a1 = c_agg(a.z, t1.x, wr.y, true); a3 = c_agg(a.w, t1.y, wr.y >> 8, true); }
            else { a0 = c_agg(a.x, t0.x, 0, false); a2 = c_agg(a.y, t0.y, 0, false); a1 = c_agg(a.z, t1.x, 0, false); a3 = c_agg(a.w, t1.y, 0, false); }
            float u[8];
#pragma unroll
            for (int h = 0; h < 2; h++)
                asm("mma.sync.aligned.m16n8k16.row.col.f32.bf16.bf16.f32 {%0,%1,%2,%3}, {%4,%5,%6,%7}, {%8,%9}, {%10,%10,%10,%10};"
                    : "=f"(u[4 * h]), "=f"(u[4 * h + 1]), "=f"(u[4 * h + 2]), "=f"(u[4 * h + 3])
                    : "r"(a0), "r"(a1), "r"(a2), "r"(a3), "r"(bw[2 * h]), "r"(bw[2 * h + 1]), "f"(0.f));
            const uint4 o = make_uint4(bf2_fma(pack_bf16(u[1], u[0]), t0.z, mr[k].x), bf2_fma(pack_bf16(u[5], u[4]), t0.w, mr[k].y),
                                       bf2_fma(pack_bf16(u[3], u[2]), t1.z, mr[k].z), bf2_fma(pack_bf16(u[7], u[6]), t1.w, mr[k].w));
            if (rb + k * THREADS < np) op[r] = o;
        }
    }
    if (((const uint32_t*)(smem + S_MISC))[6] > TAB_N + TAB_X) {
        for (int r = 2 * tid; r < 2 * np; r += (r & 1) ? 2 * THREADS - 1 : 1) {
            const uint32_t wr = ((const uint32_t*)(smem + C_WRAP))[r];
            if ((wr >> 16) < TAB_N + TAB_X) continue;
            const uint4 t = radial_bf16(wt, __bfloat16_as_ushort(p.dist[r0 + r]));
            const uint2 a = ((const uint2*)smem)[r];
            const uint32_t a0 = c_agg(a.x, t.x, wr, true), a1 = c_agg(a.y, t.y, wr >> 8, true);
            const float agg[4] = {bf_lo(a0), bf_hi(a0), bf_lo(a1), bf_hi(a1)}, g[4] = {bf_lo(t.z), bf_hi(t.z), bf_lo(t.w), bf_hi(t.w)};
            p.out[r0 + r] = finish_row(wt->wu, agg, g, p.m[r0 + r]);
        }
    }
}

__device__ __forceinline__ void grid_bar(unsigned* ctr) {
    __syncthreads();
    if (threadIdx.x == 0) { fence_gpu(); red_add(ctr, 1); wait_ge(ctr, gridDim.x); fence_gpu(); }
    __syncthreads();
}
__device__ __noinline__ void fallback(const Prm& p) {
    const int gt = blockIdx.x * THREADS + threadIdx.x, gs = gridDim.x * THREADS;
    Wts* wt = (Wts*)smem;
    __syncthreads();
    load_wts(p, wt);
    for (int e = gt; e < p.E; e += gs) g_acc[e] = make_float4(0.f, 0.f, 0.f, 0.f);
    grid_bar(&g_ctl.bar[0]);
    const float f = __bfloat162float(p.freq[0]);
    for (int t = gt; t < p.T; t += gs) {
        uint2 r = __ldg(p.m + p.idx_in[t]);
        float c = rbf16(cosf(rbf16(f * __bfloat162float(p.angle[t]))));
        asm volatile("red.global.add.v4.f32 [%0], {%1,%2,%3,%4};" ::"l"(g_acc + p.idx_out[t]), "f"(bf_lo(r.x) * c),
                     "f"(bf_hi(r.x) * c), "f"(bf_lo(r.y) * c), "f"(bf_hi(r.y) * c) : "memory");
    }
    grid_bar(&g_ctl.bar[1]);
    for (int e = gt; e < p.E; e += gs) {
        float4 a4 = __ldcg(g_acc + e);
        float a[4] = {a4.x, a4.y, a4.z, a4.w}, s[4], g[4];
        radial(wt, __bfloat162float(p.dist[e]), s, g);
        float agg[4];
#pragma unroll
        for (int j = 0; j < 4; j++) agg[j] = s[j] * (a[0] * wt->wd[j] + a[1] * wt->wd[4 + j] + a[2] * wt->wd[8 + j] + a[3] * wt->wd[12 + j]);
        p.out[e] = finish_row(wt->wu, agg, g, p.m[e]);
    }
}

__global__ void __launch_bounds__(THREADS, 1) gemnet_kernel(const __grid_constant__ Prm p) {
    const int tid = threadIdx.x, lane = tid & 31, w = __shfl_sync(0xffffffffu, tid >> 5, 0);
    uint32_t* misc = (uint32_t*)(smem + S_MISC);
    bool run_fallback = true;
    if (!p.force_bad && __cvta_generic_to_shared(smem) == SB) {
        unsigned char* const ring = p.ring;
        uint32_t smid; asm("mov.u32 %0, %%smid;" : "=r"(smid));
        const int cls = smid < NM ? 0 : (smid < NM + NP - 4 || (smid >= 124 && smid < 128)) ? 2 : 1;
        if (lane == 0) {
            if (w < 2 && (cls != 2 || blockIdx.x == 0)) misc[16 + w] = probe(ring + OFF_PROBE + w * 4096 + ((blockIdx.x >> 7) << 20) + (blockIdx.x & 127) * 32);
            else if (blockIdx.x == 0 && w <= NPAGES) misc[16 + w] = probe(ring + ((size_t)(w - 1) << 21) + OFF_PROBE);
        }
        float wd[16];
        if (cls != 2 || blockIdx.x == 0) __syncthreads();
        if (tid == 0) {
            int pool = cls == 2 ? 4 : cls * 2 + (misc[16] > misc[17]), id = 0;
            for (int k = 0; k < 7; k++) {
                int cap = pool < 2 ? NMP : pool < 4 ? NCP : NP;
                id = atomicAdd(&g_ctl.ticket[pool], 1);
                if (id < cap) break;
                pool = k == 0 ? (pool == 4 ? 0 : pool ^ 1) : k - 1;
            }
            misc[8] = pool; misc[9] = id;
        }
        if (blockIdx.x == 0 && tid == 32) {
            uint32_t pb = 0x80000000u;
            for (int k = 1; k < NPAGES; k++) pb |= (uint32_t)((2 * misc[17 + k] > misc[16] + misc[17]) != (misc[16] > misc[17])) << k;
            st_relaxed(&g_ctl.pagebits, pb);
        }
#pragma unroll
        for (int k = 0; k < 16; k++) wd[k] = __bfloat162float(p.w_down[k]);
        __syncthreads();
        const int pool = misc[8], id = misc[9];
        __syncthreads();
        if (pool != 4) down_piece(p, pool < 2 ? pool * NMP + id : NM + (pool - 2) * NCP + id, wd);
        if (DEV_FREE && !(DEV_FREE & (pool == 4 ? 1 : pool < 2 ? 2 : 4))) {
        } else if (pool == 4) {
            for (int k = tid; k < S_MISC / 16; k += THREADS) {
                const uint32_t z = k >= P_B / 16 && k < P_Q / 16 ? (k & 7) * 0x20002u : 0u, y = z + (k >= P_B / 16 && k < P_Q / 16 ? 0x10001u : 0u);
                ((uint4*)smem)[k] = make_uint4(z, z, y, y);
            }
            __syncthreads();
            if (tid < 2 * NBUF) {
                const uint32_t a = __cvta_generic_to_shared(smem + P_BAR) + tid * 8, cnt = tid < NBUF ? CPS : 1;
                mbar_init(a, cnt);
                if (tid % NBUF < id % GR) asm volatile("mbarrier.arrive.shared.b64 _, [%0], %1;" ::"r"(a), "r"(cnt) : "memory");
            }
            __syncthreads();
            if (w < FW) p_filler(p, id, w);
            else if (w < FW + NF) {
                int it = 0; uint32_t pb;
                while (!((pb = ld_relaxed(&g_ctl.pagebits)) >> 31)) backoff(it);
                p_flusher(p, ring, __shfl_sync(0xffffffffu, pb, 0), id, w - FW);
            }
        } else if (pool < 2) {
            m_role(p, ring, pool, id);
        } else {
            c_role(p, ring, pool - 2, id);
        }
        __syncthreads();
        if (tid == 0) { fence_gpu(); red_add(&g_ctl.fin, 1); }
        if ((pool == 2 || pool == 3) && !DEV_FREE) c_epilogue(p, pool - 2, id);
        if (tid == 0) { wait_ge(&g_ctl.fin, NCTA); fence_gpu(); misc[10] = ld_relaxed(&g_ctl.bad); }
        __syncthreads();
        if (pool == 4) p_cleanup(ring, id);
        run_fallback = misc[10] && !DEV_FREE;
    }
    if (run_fallback) fallback(p);
    if (tid == 0) {
        fence_gpu();
        if (atomicAdd(&g_ctl.exited, 1) == gridDim.x - 1) {
            uint32_t* c = (uint32_t*)&g_ctl;
            for (int k = 0; k < 32; k++) c[k] = 0;
        }
    }
}

cudaTextureObject_t make_tex(const void* ptr, size_t bytes, int words) {
    cudaResourceDesc rd = {};
    rd.resType = cudaResourceTypeLinear;
    rd.res.linear.devPtr = (void*)ptr;
    rd.res.linear.desc = words == 4 ? cudaCreateChannelDesc<uint4>() : cudaCreateChannelDesc<uint2>();
    rd.res.linear.sizeInBytes = bytes;
    cudaTextureDesc td = {};
    td.readMode = cudaReadModeElementType;
    cudaTextureObject_t t = 0;
    if (cudaCreateTextureObject(&t, &rd, &td, nullptr) != cudaSuccess) { cudaGetLastError(); return 0; }
    return t;
}

}

extern "C" void kernel_launch(void* const* d_in, const int* in_sizes, int n_in, void* d_out, int out_size) {
    static Prm p = {};
    static int grid = 0;
    const int E = in_sizes[3], T = in_sizes[1];
    if (grid == 0 || p.idx_in != d_in[1] || p.idx_out != d_in[2] || p.angle != d_in[4] || p.E != E || p.T != T) {
        int dev = 0, sms = 0;
        cudaGetDevice(&dev);
        cudaDeviceGetAttribute(&sms, cudaDevAttrMultiProcessorCount, dev);
        cudaFuncSetAttribute(gemnet_kernel, cudaFuncAttributeMaxDynamicSharedMemorySize, SMEM_BYTES);
        p.E = E; p.T = T;
        p.NS = ((T / 128 + NP * CPS - 1) / (NP * CPS) + 1) & ~1;
        void* rp = nullptr;
        cudaGetSymbolAddress(&rp, g_ring);
        p.ring = (unsigned char*)(((uintptr_t)rp + ((2u << 20) - 1)) & ~(uintptr_t)((2u << 20) - 1));
        bool fast = sms >= NCTA && E <= (int)FAST_E && (E & 1) == 0 && T >= 128 && T <= (1 << 29);
        if (fast) {
            p.t_in = make_tex(d_in[1], (size_t)(T / 128) * 512, 4);
            p.t_out = make_tex(d_in[2], (size_t)(T / 128) * 512, 4);
            p.t_ang = make_tex(d_in[4], (size_t)(T / 128) * 256, 2);
            fast = p.t_in && p.t_out && p.t_ang;
        }
        p.force_bad = !fast;
        grid = fast ? NCTA : sms;
    }
    p.m = (const uint2*)d_in[0];
    p.idx_in = (const int*)d_in[1];
    p.idx_out = (const int*)d_in[2];
    p.dist = (const __nv_bfloat16*)d_in[3];
    p.angle = (const __nv_bfloat16*)d_in[4];
    p.centers = (const __nv_bfloat16*)d_in[5];
    p.freq = (const __nv_bfloat16*)d_in[6];
    p.w_rbf = (const __nv_bfloat16*)d_in[7];
    p.w_sbf = (const __nv_bfloat16*)d_in[8];
    p.w_down = (const __nv_bfloat16*)d_in[9];
    p.w_up = (const __nv_bfloat16*)d_in[10];
    p.out = (uint2*)d_out;
    gemnet_kernel<<<grid, THREADS, SMEM_BYTES>>>(p);
}
```

```cpp
#include <cuda_runtime.h>
#include <cuda_bf16.h>
#include <stdint.h>

namespace {

constexpr int NI = 12;
constexpr int UN = 3;
constexpr int NG = NI / UN;
constexpr int GR = 2 * NG;
constexpr int NCP = 18;
constexpr int NO = 2 * NCP;
constexpr int KS = 64;
constexpr int NB = UN * NCP;
constexpr int NBUF = 10;
constexpr int NMP = 2 * NI;
constexpr int NP = 48, NM = 2 * NMP, NC = NO, NCTA = NP + NM + NC;
#define CPS_ 24
constexpr int CPS = CPS_;
#define FW_ 24
constexpr int FW = FW_;
constexpr int NF = 4;
#define RA_ 3
#define RV_ 3
#define RB_ 4
constexpr int RA = RA_, RV = RV_, RB = RB_;
#define QN_ 96
#define QTRIG_ 40
constexpr int QN = QN_, QTRIG = QTRIG_;
#define MW_ 18
constexpr int MW = MW_;
#define MPF_ 6
constexpr int MPF = MPF_;
constexpr int THREADS = 896, NW = THREADS / 32;
#define DEV_FREE 0
#define SLEEP_ 200

constexpr int RING_BYTES = NP << 20;
constexpr int NPAGES = RING_BYTES >> 21;
constexpr int MAX_E = 1 << 20;
constexpr int SMEM_BYTES = 232448;

constexpr int SB = 1024;

constexpr int P_CNT = 0;
constexpr int P_BAR = P_CNT + NBUF * NB * 4;
constexpr int P_TKT = P_BAR + 2 * NBUF * 8;
constexpr int P_B = (P_TKT + 128 + 127) / 128 * 128;
constexpr int P_Q = P_B + NBUF * NB * KS * 2;
constexpr int P_A = SMEM_BYTES - 256 - NBUF * NB * KS * 4;
static_assert(P_Q + FW * QN * 8 + 512 <= P_A && P_A % 128 == 0, "P smem");
constexpr int S_MISC = SMEM_BYTES - 256;
constexpr int S_AUX = S_MISC - 512;

constexpr unsigned FAST_E = 640000;
constexpr unsigned magic_of(unsigned long long d) { return (unsigned)(((1ull << 32) + d - 1) / d); }
constexpr bool magic_ok(unsigned long long d) { return (magic_of(d) * d - (1ull << 32)) * FAST_E < (1ull << 32); }
constexpr unsigned pick_rows(unsigned lo) {
    unsigned d = (lo + 3) & ~3u;
    while (!magic_ok(d)) d += 4;
    return d;
}
constexpr unsigned ROWS_I = pick_rows((FAST_E + NI - 1) / NI), ROWS_O = pick_rows((FAST_E + NO - 1) / NO);
constexpr unsigned MAG_I = magic_of(ROWS_I), MAG_O = magic_of(ROWS_O), HALF_O = ROWS_O * NCP;
constexpr int C_WRAP = ROWS_O * 8, C_TAB = ROWS_O * 12, TAB_N = 1025, TAB_LO = 0x3f80 - 1024, TAB_X = (S_AUX - C_TAB) / 16 - TAB_N;
static_assert(ROWS_I * 4 <= S_AUX && TAB_X >= 100 && ROWS_I <= 65536 && ROWS_O <= 32768, "tables");

constexpr int NPC = NM + NC;
constexpr int PC_ROWS = ((FAST_E + NPC - 1) / NPC + 3) & ~3;
constexpr int S_PC = C_WRAP + 128 - C_WRAP % 128;
static_assert(S_PC + PC_ROWS * 8 + 1024 <= S_AUX, "pre-pass");
struct __align__(128) Ctl {
    unsigned ticket[5];
    unsigned pagebits;
    unsigned pieces_done, unused;
    unsigned bad;
    unsigned fin;
    unsigned bar[3];
    unsigned exited;
    unsigned pad[18];
    float stat[NPC][8];
};

struct Prm {
    const uint2* m; const int* idx_in; const int* idx_out; const __nv_bfloat16* dist; const __nv_bfloat16* angle;
    const __nv_bfloat16* centers; const __nv_bfloat16* freq; const __nv_bfloat16* w_rbf; const __nv_bfloat16* w_sbf;
    const __nv_bfloat16* w_down; const __nv_bfloat16* w_up; uint2* out;
    cudaTextureObject_t t_in, t_out, t_ang;
    int E, T;
    unsigned char* ring;
    int NS;
    int force_bad;
};

__device__ __align__(128) unsigned char g_ring[RING_BYTES + (2 << 20)];
__device__ Ctl g_ctl;
__device__ float4 g_acc[MAX_E];
__device__ __align__(128) uint32_t g_md[2][NI * ROWS_I];
#define TS(k)
#define PROF_DECL
#define PROF(k)
#define PROF_END

extern __shared__ __align__(128) unsigned char smem[];

__device__ __forceinline__ float bf_lo(uint32_t w) { return __uint_as_float(w << 16); }
__device__ __forceinline__ float bf_hi(uint32_t w) { return __uint_as_float(w & 0xffff0000u); }
__device__ __forceinline__ float rbf16(float x) { return __bfloat162float(__float2bfloat16_rn(x)); }
__device__ __forceinline__ uint32_t pack_bf16(float hi, float lo) {
    uint32_t r; asm("cvt.rn.bf16x2.f32 %0, %1, %2;" : "=r"(r) : "f"(hi), "f"(lo)); return r;
}
__device__ __forceinline__ uint32_t prmt(uint32_t a, uint32_t b, uint32_t c) {
    uint32_t r; asm("prmt.b32 %0, %1, %2, %3;" : "=r"(r) : "r"(a), "r"(b), "r"(c)); return r;
}
__device__ __forceinline__ uint32_t ld_relaxed(const void* p) {
    uint32_t v; asm volatile("ld.relaxed.gpu.global.u32 %0, [%1];" : "=r"(v) : "l"(p) : "memory"); return v;
}
__device__ __forceinline__ uint2 ld_relaxed2(const void* p) {
    uint2 v; asm volatile("ld.relaxed.gpu.global.v2.u32 {%0,%1}, [%2];" : "=r"(v.x), "=r"(v.y) : "l"(p) : "memory"); return v;
}
__device__ __forceinline__ uint4 ld_relaxed4(const void* p) {
    uint4 v; asm volatile("ld.relaxed.gpu.global.v4.u32 {%0,%1,%2,%3}, [%4];" : "=r"(v.x), "=r"(v.y), "=r"(v.z), "=r"(v.w) : "l"(p) : "memory"); return v;
}
__device__ __forceinline__ void st_relaxed(void* p, uint32_t v) { asm volatile("st.relaxed.gpu.global.u32 [%0], %1;" ::"l"(p), "r"(v) : "memory"); }
__device__ __forceinline__ void st_relaxed16(void* p, uint32_t v) { asm volatile("st.relaxed.gpu.global.u16 [%0], %1;" ::"l"(p), "h"((uint16_t)v) : "memory"); }
__device__ __forceinline__ void red_add(void* p, uint32_t v) { asm volatile("red.relaxed.gpu.global.add.u32 [%0], %1;" ::"l"(p), "r"(v) : "memory"); }
__device__ __forceinline__ void fence_gpu() { asm volatile("fence.acq_rel.gpu;" ::: "memory"); }
__device__ __forceinline__ void fence_acquire() { asm volatile("fence.acquire.gpu;" ::: "memory"); }
__device__ __forceinline__ void fence_release() { asm volatile("fence.release.gpu;" ::: "memory"); }
__device__ __forceinline__ void mbar_init(uint32_t a, uint32_t n) { asm volatile("mbarrier.init.shared.b64 [%0], %1;" ::"r"(a), "r"(n) : "memory"); }
__device__ __forceinline__ void mbar_arrive(uint32_t a) { asm volatile("mbarrier.arrive.shared.b64 _, [%0];" ::"r"(a) : "memory"); }
__device__ __forceinline__ bool mbar_try(uint32_t a, uint32_t ph) {
    uint32_t ok;
    asm volatile("{.reg .pred p; mbarrier.try_wait.parity.shared.b64 p, [%1], %2, %3; selp.u32 %0, 1, 0, p;}" : "=r"(ok) : "r"(a), "r"(ph), "r"(2000) : "memory");
    return ok;
}
__device__ __forceinline__ bool mbar_test(uint32_t a, uint32_t ph) {
    uint32_t ok;
    asm volatile("{.reg .pred p; mbarrier.test_wait.parity.shared.b64 p, [%1], %2; selp.u32 %0, 1, 0, p;}" : "=r"(ok) : "r"(a), "r"(ph) : "memory");
    return ok;
}
constexpr int SPIN_MAX = 1 << 22;
__device__ __forceinline__ void mbar_wait(uint32_t a, uint32_t ph) {
    int it = 0;
    while (!mbar_try(a, ph)) { if (++it > SPIN_MAX) __trap(); }
}
__device__ __forceinline__ void backoff(int& it) { __nanosleep(SLEEP_); if (++it > SPIN_MAX) __trap(); }
__device__ __forceinline__ void wait_ge(const void* p, uint32_t v) {
    int it = 0;
    while (ld_relaxed(p) < v) backoff(it);
}

__device__ __forceinline__ bool elect_one() {
    uint32_t r; asm volatile("{.reg .pred p; elect.sync _|p, 0xffffffff; selp.u32 %0, 1, 0, p;}" : "=r"(r)); return r;
}
__device__ __forceinline__ void st_lane0(void* p, uint32_t v, int lane) {
    asm volatile("{.reg .pred p; setp.eq.s32 p, %2, 0; @p st.relaxed.gpu.global.u32 [%0], %1;}" ::"l"(p), "r"(v), "r"(lane) : "memory");
}
__device__ __forceinline__ void wait_all_ge(const void* p, uint32_t v) {
    int it = 0;
    while (!__all_sync(0xffffffffu, ld_relaxed(p) >= v)) backoff(it);
}
__device__ __forceinline__ void lds_lt(uint32_t& v, uint32_t ad, int a, int b) {
    asm volatile("{.reg .pred p; setp.lt.s32 p, %2, %3; @p ld.shared.u32 %0, [%1];}" : "+r"(v) : "r"(ad), "r"(a), "r"(b));
}

constexpr uint32_t R_V1 = 0x03000, R_A = 0x81000, R_B = 0x82000, R_UNIT = 0x4000, R_HI = 0x40000 - 8 * 256;
__device__ __forceinline__ uint32_t q_base(uint32_t q, uint32_t pagebits_x) { return (q << 20) | (((pagebits_x >> (q >> 1)) & 1u) << 12); }
__device__ __forceinline__ uint32_t slot_off(uint32_t s) { return (s << 16) | (((s + 1) & 2) << 11); }
constexpr uint32_t OFF_PF = R_B + 3 * R_UNIT, OFF_RDY = OFF_PF + 128, OFF_REL = OFF_PF + 256;
constexpr uint32_t OFF_PROBE = 3 * R_UNIT;
static_assert(RA <= 4 && RV <= 4 && RB <= 8 && RA <= RB && RV <= RB, "ring");

__device__ __forceinline__ uint32_t probe(unsigned char* p) {
    volatile uint32_t* sink = (volatile uint32_t*)(smem + S_MISC + 240);
    asm volatile("st.global.v4.u32 [%0], {%1,%1,%1,%1};" ::"l"(p), "r"(0) : "memory");
    asm volatile("st.global.v4.u32 [%0], {%1,%1,%1,%1};" ::"l"(p + 16), "r"(0) : "memory");
    uint32_t best = 0xffffffffu;
#pragma unroll 1
    for (int r = 0; r < 3; r++) {
        uint32_t t0, t1, v;
        asm volatile("mov.u32 %0, %%clock;" : "=r"(t0)::"memory");
        asm volatile("atom.relaxed.gpu.global.add.u32 %0, [%1], 1;" : "=r"(v) : "l"(p) : "memory");
        *sink = v;
        asm volatile("mov.u32 %0, %%clock;" : "=r"(t1)::"memory");
        best = min(best, t1 - t0);
    }
    return best;
}

struct Wts { float c[8], wr[32], ws[32], wd[16], wu[16]; };
__device__ __forceinline__ void load_wts(const Prm& p, Wts* w) {
    int t = threadIdx.x;
    if (t < 8) w->c[t] = __bfloat162float(p.centers[t]);
    if (t < 32) { w->wr[t] = __bfloat162float(p.w_rbf[t]); w->ws[t] = __bfloat162float(p.w_sbf[t]); }
    if (t < 16) { w->wd[t] = __bfloat162float(p.w_down[t]); w->wu[t] = __bfloat162float(p.w_up[t]); }
}
__device__ __forceinline__ void radial(const Wts* w, float d, float s[4], float g[4]) {
#pragma unroll
    for (int j = 0; j < 4; j++) s[j] = g[j] = 0.f;
#pragma unroll
    for (int r = 0; r < 8; r++) {
        float x = rbf16(d - w->c[r]);
        float b = rbf16(__expf(rbf16(-10.0f * rbf16(x * x))));
#pragma unroll
        for (int j = 0; j < 4; j++) { s[j] += b * w->ws[r * 4 + j]; g[j] += b * w->wr[r * 4 + j]; }
    }
}
__device__ __noinline__ uint4 radial_bf16(const Wts* w, uint32_t dbits) {
    float s[4], g[4];
    radial(w, __uint_as_float(dbits << 16), s, g);
    return make_uint4(pack_bf16(s[1], s[0]), pack_bf16(s[3], s[2]), pack_bf16(g[1], g[0]), pack_bf16(g[3], g[2]));
}
__device__ __forceinline__ uint2 finish_row(const float* wu, const float agg[4], const float g[4], uint2 r) {
    float o[4];
    const float mm[4] = {bf_lo(r.x), bf_hi(r.x), bf_lo(r.y), bf_hi(r.y)};
#pragma unroll
    for (int j = 0; j < 4; j++) o[j] = mm[j] + (agg[0] * wu[j] + agg[1] * wu[4 + j] + agg[2] * wu[8 + j] + agg[3] * wu[12 + j]) * g[j];
    return make_uint2(pack_bf16(o[1], o[0]), pack_bf16(o[3], o[2]));
}
__device__ __forceinline__ uint2 down_row(const float* wd, uint32_t x, uint32_t y) {
    const float a[4] = {bf_lo(x), bf_hi(x), bf_lo(y), bf_hi(y)};
    float d[4];
#pragma unroll
    for (int j = 0; j < 4; j++) d[j] = a[0] * wd[j] + a[1] * wd[4 + j] + a[2] * wd[8 + j] + a[3] * wd[12 + j];
    return make_uint2(pack_bf16(d[1], d[0]), pack_bf16(d[3], d[2]));
}

__device__ __forceinline__ void down_load(const Prm& p, int pc) {
    const int r0 = pc * PC_ROWS / 2, nr = max(min((pc + 1) * PC_ROWS, p.E) / 2 - r0, 0);
    const uint32_t bar = SB + S_MISC + 248;
    mbar_init(bar, 1);
    asm volatile("fence.proxy.async.shared::cta;" ::: "memory");
    asm volatile("mbarrier.arrive.expect_tx.shared.b64 _, [%0], %1;" ::"r"(bar), "r"(nr * 16) : "memory");
    for (int o = 0; o < nr; o += 640)
        asm volatile("cp.async.bulk.shared::cluster.global.mbarrier::complete_tx::bytes [%0], [%1], %2, [%3];"
                     ::"r"(SB + S_PC + o * 16), "l"((const uint4*)p.m + r0 + o), "r"(min(640, nr - o) * 16), "r"(bar) : "memory");
}
__device__ __forceinline__ void down_piece(const Prm& p, int pc, const float* wd) {
    const int tid = threadIdx.x, lane = tid & 31, w = tid >> 5;
    const int r0 = pc * PC_ROWS / 2, nr = max(min((pc + 1) * PC_ROWS, p.E) / 2 - r0, 0);
    mbar_wait(SB + S_MISC + 248, 0);
    uint32_t mx0 = 0, mx1 = 0; float ss[4] = {0.f, 0.f, 0.f, 0.f};
    for (int r = tid; r < nr; r += THREADS) {
        const uint4 v = ((const uint4*)(smem + S_PC))[r];
        const uint2 a = down_row(wd, v.x, v.y), b = down_row(wd, v.z, v.w);
        ((uint2*)g_md[0])[r0 + r] = make_uint2(a.x, b.x); ((uint2*)g_md[1])[r0 + r] = make_uint2(a.y, b.y);
        mx0 = __vimax3_u16x2(mx0, a.x & 0x7fff7fffu, b.x & 0x7fff7fffu); mx1 = __vimax3_u16x2(mx1, a.y & 0x7fff7fffu, b.y & 0x7fff7fffu);
        ss[0] += bf_lo(a.x) * bf_lo(a.x) + bf_lo(b.x) * bf_lo(b.x); ss[1] += bf_hi(a.x) * bf_hi(a.x) + bf_hi(b.x) * bf_hi(b.x);
        ss[2] += bf_lo(a.y) * bf_lo(a.y) + bf_lo(b.y) * bf_lo(b.y); ss[3] += bf_hi(a.y) * bf_hi(a.y) + bf_hi(b.y) * bf_hi(b.y);
    }
    uint32_t st[4] = {mx0 << 16, mx0 & 0xffff0000u, mx1 << 16, mx1 & 0xffff0000u};
    uint4* red = (uint4*)(smem + S_PC + PC_ROWS * 8);
    for (int pass = 0; pass < 2; pass++) {
#pragma unroll
        for (int ch = 0; ch < 4; ch++) {
            st[ch] = __reduce_max_sync(0xffffffffu, st[ch]);
#pragma unroll
            for (int o = 16; o; o >>= 1) ss[ch] += __shfl_xor_sync(0xffffffffu, ss[ch], o);
        }
        uint4* dst = pass ? (uint4*)g_ctl.stat[pc] : red + 2 * w;
        if (lane == 0) { dst[0] = make_uint4(st[0], st[1], st[2], st[3]); dst[1] = make_uint4(__float_as_uint(ss[0]), __float_as_uint(ss[1]), __float_as_uint(ss[2]), __float_as_uint(ss[3])); }
        if (pass) break;
        __syncthreads();
        const uint4 a = lane < NW ? red[2 * lane] : make_uint4(0, 0, 0, 0), b = lane < NW ? red[2 * lane + 1] : make_uint4(0, 0, 0, 0);
        __syncthreads();
        if (w != NW - 1) return;
        st[0] = a.x; st[1] = a.y; st[2] = a.z; st[3] = a.w;
        ss[0] = __uint_as_float(b.x); ss[1] = __uint_as_float(b.y); ss[2] = __uint_as_float(b.z); ss[3] = __uint_as_float(b.w);
    }
    if (lane == 0) { fence_release(); red_add(&g_ctl.pieces_done, 1); }
    __syncwarp();
}

__device__ __forceinline__ void get_scales(const Prm& p, float sc[4], bool& bad) {
    const int lane = threadIdx.x & 31;
    uint32_t mxb[4] = {0, 0, 0, 0};
    float ss[4] = {0.f, 0.f, 0.f, 0.f};
#pragma unroll
    for (int k = 0; k < (NPC + 31) / 32; k++) {
        if (lane + 32 * k < NPC) {
            const uint4 a = ld_relaxed4(&g_ctl.stat[lane + 32 * k][0]), b = ld_relaxed4(&g_ctl.stat[lane + 32 * k][4]);
            mxb[0] = max(mxb[0], a.x); mxb[1] = max(mxb[1], a.y); mxb[2] = max(mxb[2], a.z); mxb[3] = max(mxb[3], a.w);
            ss[0] += __uint_as_float(b.x); ss[1] += __uint_as_float(b.y); ss[2] += __uint_as_float(b.z); ss[3] += __uint_as_float(b.w);
        }
    }
    bad = false;
    const float kdeg = fminf(3.5f * sqrtf(fmaxf(0.5f * (float)p.T / (float)p.E, 1.0f)), 128.f);
#pragma unroll
    for (int ch = 0; ch < 4; ch++) {
        float mx = __uint_as_float(__reduce_max_sync(0xffffffffu, mxb[ch]));
#pragma unroll
        for (int o = 16; o; o >>= 1) ss[ch] += __shfl_xor_sync(0xffffffffu, ss[ch], o);
        float rms = sqrtf(ss[ch] / (float)p.E);
        float range = fmaxf(4.002f * mx, kdeg * rms);
        if (!(mx <= 1e15f) || !(range <= 128.f * rms) || (mx > 0.f && mx < 1e-15f)) bad = true;
        sc[ch] = range > 0.f ? 32767.f / range : 0.f;
    }
}

constexpr int PER = 40;
__host__ __device__ constexpr uint32_t bar_done(uint32_t s) { return SB + P_BAR + (s % NBUF) * 16; }
__host__ __device__ constexpr uint32_t bar_free(uint32_t m) { return bar_done(m + NBUF - (GR - 1)) + 8; }
struct __align__(16) PTab { uint32_t e[PER][4]; };
constexpr PTab make_ptab() {
    PTab t = {};
    for (int s = 0; s < PER; s++) {
        for (int d = 0; d < GR; d++) {
            int gi = (s + d) % GR, buf = (s + d) % NBUF, X = gi & 1, g = gi >> 1;
            t.e[s][X] |= (uint32_t)(4 * UN * buf - g - 4 * X + 7) << (8 * g);
        }
        t.e[s][2] = bar_done(s);
        t.e[s][3] = (((s + GR - 1) / NBUF) & 1) ^ 1;
    }
    return t;
}
__constant__ PTab c_ptab = make_ptab();
constexpr int BIAS = 7 * NCP;
static_assert(NG == 4 && CPS >= FW, "group selection");

struct PCtx { uint32_t a0, a1; };
struct PElem { uint32_t b4, aw, ol, r2; };

__device__ __forceinline__ void p_bin(const PCtx& c, PElem& e, uint32_t i, uint32_t o) {
    uint32_t ib = __umulhi(i, MAG_I), ob = __umulhi(o, MAG_O), sel = ib & 3;
    asm("{.reg .pred p; setp.ge.u32 p, %1, %2; @p add.u32 %0, %0, 4;}" : "+r"(sel) : "r"(o), "n"(HALF_O));
    e.b4 = __dp4a(prmt(c.a0, c.a1, sel), (uint32_t)NCP, ib * NCP + ob * 4);
    e.aw = i - ib * ROWS_I;
    e.ol = o - ob * ROWS_O;
}
__device__ __forceinline__ void p_rank(PElem& e) {
    asm volatile("atom.shared.add.u32 %0, [%1+%2], 2;" : "=r"(e.r2) : "r"(e.b4), "n"(SB + P_CNT - BIAS) : "memory");
}
__device__ __forceinline__ void p_store(const PElem& e) {
    const uint32_t ab = e.b4 * (KS / 2) + e.r2;
    asm volatile("{.reg .pred p; setp.lt.u32 p, %4, %5; @p st.shared.u32 [%0+%6], %1; @p st.shared.u16 [%2+%7], %3;}"
                 ::"r"(ab * 2), "r"(e.aw), "r"(ab), "h"((uint16_t)e.ol), "r"(e.r2), "n"(KS * 2),
                   "n"(SB + P_A - BIAS * KS), "n"(SB + P_B - BIAS * (KS / 2)) : "memory");
}
__device__ __forceinline__ uint32_t cos2(uint32_t x) {
    x = __vminu2(x, 0x42804280u);
    return pack_bf16(__cosf(bf_hi(x)), __cosf(bf_lo(x)));
}

#define PD_ 2
struct PIn { uint4 i, o; uint2 a; };

struct PFill {
    PCtx c;
    uint32_t qb, qt, lt, f2, bar, par, xmax;
    uint32_t s0, lane, vb;
    bool open;
    __device__ __forceinline__ void fetch(const Prm& p, PIn& x, uint32_t ch) {
        const int v = ch * (NP * 32) + vb;
        asm volatile("{.reg .b32 d0, d1; tex.1d.v4.u32.s32 {%0,%1,d0,d1}, [%2, {%3}];}" : "=r"(x.a.x), "=r"(x.a.y) : "l"(p.t_ang), "r"(v));
        asm volatile("tex.1d.v4.u32.s32 {%0,%1,%2,%3}, [%4, {%5}];" : "=r"(x.i.x), "=r"(x.i.y), "=r"(x.i.z), "=r"(x.i.w) : "l"(p.t_in), "r"(v));
        asm volatile("tex.1d.v4.u32.s32 {%0,%1,%2,%3}, [%4, {%5}];" : "=r"(x.o.x), "=r"(x.o.y), "=r"(x.o.z), "=r"(x.o.w) : "l"(p.t_out), "r"(v));
    }
    __device__ __forceinline__ uint32_t ticket(uint32_t zero) {
        uint32_t t;
        asm volatile("atom.shared.add.u32 %0, [%1+%2], %3;" : "=r"(t) : "r"(lane * 4), "n"(SB + P_TKT), "r"((~lt & 1) | zero) : "memory");
        return t;
    }
    __device__ __forceinline__ uint32_t use_ticket(uint32_t t) {
        t = __reduce_or_sync(0xffffffffu, t);
        begin(t / CPS);
        return t + PD_ * FW;
    }
    __device__ __forceinline__ void begin(uint32_t step) {
        const uint4 t = ((const uint4*)c_ptab.e)[(step + s0) % PER];
        c.a0 = t.x; c.a1 = t.y; bar = t.z; par = t.w;
        open = mbar_test(bar + 8, par);
    }
    __device__ __forceinline__ void enter() { if (!open) mbar_wait(bar + 8, par); }
    __device__ __forceinline__ void end() {
        __syncwarp();
        asm volatile("{.reg .pred p; setp.eq.u32 p, %1, 0; @p mbarrier.arrive.shared.b64 _, [%0];}" ::"r"(bar), "r"(lt) : "memory");
    }
    __device__ __forceinline__ void push(bool f, uint32_t x, uint32_t y) {
        const uint32_t mask = __ballot_sync(0xffffffffu, f);
        asm volatile("{.reg .pred p; setp.ne.u32 p, %3, 0; @p st.shared.v2.u32 [%0], {%1,%2};}"
                     ::"r"(min(qt + __popc(mask & lt) * 8, qb + (QN - 1) * 8)), "r"(x), "r"(y), "r"((uint32_t)f) : "memory");
        qt += __popc(mask) * 8;
    }
    __device__ __forceinline__ void push3(bool f, uint32_t i, uint32_t o, uint32_t aw) { push(f, prmt(i, aw, 0x6210), prmt(o, aw, 0x7210)); }
    __device__ __forceinline__ uint32_t chunk(const PIn& x) {
        uint32_t x0, x1;
        const uint32_t tk = use_ticket(ticket(x.o.x >> 31));
        PElem e0, e1, e2, e3;
        p_bin(c, e0, x.i.x, x.o.x); p_bin(c, e1, x.i.y, x.o.y); p_bin(c, e2, x.i.z, x.o.z); p_bin(c, e3, x.i.w, x.o.w);
        asm volatile("" : "+r"(e0.b4), "+r"(e1.b4), "+r"(e2.b4), "+r"(e3.b4));
        enter();
        p_rank(e0); p_rank(e1); p_rank(e2); p_rank(e3);
        asm volatile("mul.rn.bf16x2 %0, %1, %2;" : "=r"(x0) : "r"(x.a.x), "r"(f2));
        asm volatile("mul.rn.bf16x2 %0, %1, %2;" : "=r"(x1) : "r"(x.a.y), "r"(f2));
        x0 &= 0x7fff7fffu; x1 &= 0x7fff7fffu;
        xmax = __vimax3_u16x2(xmax, x0, x1);
        const uint32_t c0 = cos2(x0), c1 = cos2(x1);
        e0.aw = prmt(e0.aw, c0, 0x5410); e1.aw = prmt(e1.aw, c0, 0x7610); e2.aw = prmt(e2.aw, c1, 0x5410); e3.aw = prmt(e3.aw, c1, 0x7610);
        p_store(e0); p_store(e1); p_store(e2); p_store(e3);
        if (qt - qb >= QTRIG * 8) retry(32);
        end();
        const uint32_t r01 = e0.r2 | e1.r2, r23 = e2.r2 | e3.r2;
        const bool f = (r01 | r23) >= KS * 2;
        if (__any_sync(0xffffffffu, f)) {
            const bool f0 = e0.r2 >= KS * 2, f1 = e1.r2 >= KS * 2, f2_ = e2.r2 >= KS * 2, f3 = e3.r2 >= KS * 2, f01 = r01 >= KS * 2;
            push3(f, f01 ? (f0 ? x.i.x : x.i.y) : (f2_ ? x.i.z : x.i.w), f01 ? (f0 ? x.o.x : x.o.y) : (f2_ ? x.o.z : x.o.w),
                  f01 ? (f0 ? e0.aw : e1.aw) : (f2_ ? e2.aw : e3.aw));
            const uint32_t s2 = max(max(min(e0.r2, e1.r2), min(e2.r2, e3.r2)), min(r01, r23));
            if (__any_sync(0xffffffffu, s2 >= KS * 2)) {
                push3(f1 && f0, x.i.y, x.o.y, e1.aw); push3(f2_ && f01, x.i.z, x.o.z, e2.aw); push3(f3 && (f01 || f2_), x.i.w, x.o.w, e3.aw);
            }
        }
        return tk;
    }
    __device__ __forceinline__ void retry(uint32_t take) {
        if (qt - qb > QN * 8) { st_relaxed(&g_ctl.bad, 1); qt = qb + QN * 8; }
        uint2 e, r, r1;
        __syncwarp();
        asm volatile("ld.shared.v2.u32 {%0,%1}, [%2];" : "=r"(e.x), "=r"(e.y) : "r"(qb + lane * 8) : "memory");
        asm volatile("ld.shared.v2.u32 {%0,%1}, [%2];" : "=r"(r.x), "=r"(r.y) : "r"(qb + (lane + take) * 8) : "memory");
        qt -= take * 8;
        const bool more = qt - qb > 256;
        if (more) asm volatile("ld.shared.v2.u32 {%0,%1}, [%2];" : "=r"(r1.x), "=r"(r1.y) : "r"(qb + (lane + take) * 8 + 256) : "memory");
        __syncwarp();
        if (more && qb + lane * 8 + 256 < qt) asm volatile("st.shared.v2.u32 [%0], {%1,%2};" ::"r"(qb + lane * 8 + 256), "r"(r1.x), "r"(r1.y) : "memory");
        if (qb + lane * 8 < qt) asm volatile("st.shared.v2.u32 [%0], {%1,%2};" ::"r"(qb + lane * 8), "r"(r.x), "r"(r.y) : "memory");
        PElem el;
        el.r2 = 0;
        if (take == 32 || lane < take) {
            p_bin(c, el, e.x & 0xffffffu, e.y & 0xffffffu);
            el.aw = prmt(el.aw, prmt(e.x, e.y, 0x0073), 0x5410);
            p_rank(el);
            p_store(el);
        }
        push(el.r2 >= KS * 2, e.x, e.y);
    }
};

__device__ __forceinline__ void p_filler(const Prm& p, int q, int w) {
    PFill F;
    const int lane = threadIdx.x & 31;
    const uint32_t NS = p.NS, cend = p.T >> 7, nv = NS * CPS, nc = (cend + NP - 1 - q) / NP;
    static_assert(QN <= 96, "retry moves two batches");
    F.lt = __shfl_sync(0xffffffffu, (1u << lane) - 1u, lane);
    F.lane = __shfl_sync(0xffffffffu, lane, lane);
    F.vb = __shfl_sync(0xffffffffu, q * 32 + lane, lane);
    F.f2 = __shfl_sync(0xffffffffu, __bfloat16_as_ushort(p.freq[0]) * 0x10001u, 0);
    F.qb = F.qt = SB + P_Q + w * (QN * 8);
    F.s0 = q % GR; F.xmax = 0;
    uint32_t c0 = w, c1 = w + FW;
    PIn x0, x1;
    F.fetch(p, x0, c0);
#pragma unroll 1
    while (c0 < nc) {
        F.fetch(p, x1, c1);
        c0 = F.chunk(x0);
        if (c1 >= nc) break;
        F.fetch(p, x0, c0);
        c1 = F.chunk(x1);
    }
    int left = (c0 < nv) + (c1 < nv);
#pragma unroll 1
    while (left > 0) { left -= F.use_ticket(F.ticket(0)) >= nv; F.enter(); F.end(); }
    if (q == 0 && w < 8) {
        const int t = cend * 128 + w * 16 + lane;
        const bool f = t < p.T && lane < 16;
        uint32_t i = 0, o = 0, x = 0;
        if (f) { i = p.idx_in[t]; o = p.idx_out[t]; asm("mul.rn.bf16x2 %0, %1, %2;" : "=r"(x) : "r"(__bfloat16_as_ushort(p.angle[t]) * 0x10001u), "r"(F.f2)); }
        F.xmax = __vmaxu2(F.xmax, x & 0x7fff7fffu);
        if (F.qt - F.qb >= 32 * 8) { F.begin(NS); F.enter(); F.retry(32); }
        F.push3(f, i, o, cos2(x & 0x7fff7fffu));
    }
#pragma unroll 1
    for (uint32_t n = NS; n <= NS + GR; n++) {
        F.begin(n); F.enter();
        for (uint32_t nq = min((F.qt - F.qb) >> 3, (uint32_t)QN); nq > 0;) { uint32_t take = min(nq, 32u); F.retry(take); nq -= take; }
        F.end();
        if (CPS > FW && w < CPS - FW) F.end();
    }
    if (F.qt != F.qb || ((F.xmax + 0x3d803d80u) & 0x80008000u)) st_relaxed(&g_ctl.bad, 1);
}

template <int N> __device__ __forceinline__ void p_stamp(const uint32_t (&st)[N], uint32_t off, uint32_t bit, bool set) {
    if (set) {
#pragma unroll
        for (int j = 0; j < N; j++) asm volatile("red.shared.or.b32 [%0], %1;" ::"r"(st[j] + off), "r"(bit) : "memory");
    } else {
#pragma unroll
        for (int j = 0; j < N; j++) asm volatile("red.shared.and.b32 [%0], %1;" ::"r"(st[j] + off), "r"(~bit) : "memory");
    }
}
__device__ __forceinline__ void bulk_store(void* dst, uint32_t src, uint32_t bytes) {
    asm volatile("cp.async.bulk.global.shared::cta.bulk_group [%0], [%1], %2;" ::"l"(dst), "r"(src), "r"(bytes) : "memory");
}
#define ROUNDS_ 1
__device__ __forceinline__ void p_flusher(const Prm& p, unsigned char* ring, uint32_t pagebits, int q, int f) {
    const int lane = threadIdx.x & 31;
    const uint32_t NS = p.NS, NT = NS + 2 * GR, s0 = q % GR;
    uint32_t sta[5], stb[7];
#pragma unroll
    for (int j = 0; j < 7; j++) {
        const int bin = min(8 * j + (lane >> 2), NB - 1);
        const int ps = j < 4 ? 4 * (j >> 1) + (lane >> 3) : 8, l = j < 4 ? 2 * (j & 1) + ((lane >> 2) & 1) : (lane >> 2) & 3;
        stb[j] = SB + P_B + bin * 128 + (lane & 3) * 32 + ((bin % NCP) & 3) * 8;
        if (j < 5) sta[j] = SB + P_A + ps * 512 + l * 128 + (l & 1) * 16 + (lane & 3) * 32 + (ps & 3) * 4;
    }
    const uint32_t pfo = OFF_PF + (lane / 6) * 32 + (lane & 1) * 16 + ((lane % 6) >> 1) * 4, pfc = (lane >> 1) * 6 + (lane & 1);
    const uint32_t wto = lane < NCP ? OFF_REL + lane * 4 : OFF_RDY + (lane % 6) * 4;
    PROF_DECL
#pragma unroll 1
    for (uint32_t n = f; n < NT; n += NF) {
        const uint32_t buf = (n + s0) % NBUF, h = n >> 1, lap = h / RB;
        const uint32_t qb = q_base(q, pagebits) ^ (((n + q) & 1) << 12), bb = qb ^ slot_off(h % RB);
        if (h >= RA && !DEV_FREE) {
            const uint32_t hw = lane < NCP ? h : h + RB - RA;
            wait_all_ge(ring + (qb ^ slot_off(hw % RB) ^ wto), (hw / RB) << (lane < NCP ? 0 : 1));
        }
        PROF(0);
#pragma unroll
        for (int d = 2; d >= 0; d--) {
            const int nl = (int)min(n, NS + GR) - d;
            if (nl >= 0) mbar_wait(bar_done(nl + s0), ((nl + s0) / NBUF) & 1);
        }
        PROF(1);
        uint32_t* cnt = (uint32_t*)(smem + P_CNT) + buf * NB;
        bool any = true;
        if (n >= NS) any = __any_sync(0xffffffffu, lane < NCP && (cnt[lane] | cnt[NCP + lane] | cnt[2 * NCP + lane]));
        if (any) {
            const uint32_t oa = buf * (NB * KS * 4), ob = buf * (NB * KS * 2);
            unsigned char* da = ring + (qb ^ slot_off(h % RA) ^ R_A);
            unsigned char* db = ring + (bb ^ R_B);
            int sent = 0;
#pragma unroll
            for (int u = 0; u <= UN; u++) {
                if (u < UN) p_stamp(sta, oa + u * (NCP * KS * 4), 0x40000000u, (h / RA) & 1);
                else p_stamp(stb, ob, 0x8000u, lap & 1);
                if (u == UN || (ROUNDS_ >= 2 && u == 0) || (ROUNDS_ >= 3 && u == 2)) {
                    __syncwarp();
                    if (elect_one()) {
                        asm volatile("fence.proxy.async.shared::cta;" ::: "memory");
#pragma unroll
                        for (int v = sent; v <= u; v++) {
                            if (v < UN) {
                                bulk_store(da + v * R_UNIT, SB + P_A + oa + v * (NCP * KS * 4), 8 * KS * 4);
                                bulk_store(da + v * R_UNIT + 0x40000, SB + P_A + oa + (v * NCP + 8) * (KS * 4), (NCP - 8) * KS * 4);
                            } else {
#pragma unroll
                                for (int k = 0; k < UN; k++) bulk_store(db + k * R_UNIT, SB + P_B + ob + k * (NCP * KS * 2), NCP * KS * 2);
                            }
                        }
                    }
                    __syncwarp();
                    sent = u + 1;
                }
            }
        }
        uint32_t wm = ((lap + 1) << 22) | ((uint32_t)any << 21);
        if (lane < NCP) {
#pragma unroll
            for (int u = 0; u < 3; u++) wm |= min(cnt[pfc + 2 * u] >> 1, (uint32_t)KS) << (7 * u);
        }
        __syncwarp();
        if (lane < NB / 2) ((uint2*)cnt)[lane] = make_uint2(0, 0);
        PROF(3);
        asm volatile("cp.async.bulk.commit_group;" ::: "memory");
        asm volatile("cp.async.bulk.wait_group 0;" ::: "memory");
        __syncwarp();
        PROF(2);
        const bool safe = h < RB || n >= NS;
        if (!safe && lane < NCP) st_relaxed(ring + (bb ^ pfo), wm);
        if (n > 0) mbar_wait(bar_free(n - 1 + s0), ((n - 1 + s0) / NBUF) & 1);
        if (lane == 0) mbar_arrive(bar_free(buf));
        if (safe) {
            if (any) fence_release();
            if (lane < NCP) st_relaxed(ring + (bb ^ pfo), wm);
        }
        PROF(4);
    }
    PROF_END;
}
__device__ __forceinline__ void p_cleanup(unsigned char* ring, int q) {
    const int k = threadIdx.x / 24;
    if (k < 2 * RB) *(uint4*)(ring + ((q << 20) ^ ((k & 1) << 12) ^ slot_off(k >> 1) ^ OFF_PF) + (threadIdx.x % 24) * 16) = make_uint4(0, 0, 0, 0);
}

__device__ __forceinline__ void m_role(const Prm& p, unsigned char* ring, int X, int id) {
    const int tid = threadIdx.x, lane = tid & 31, w = __shfl_sync(0xffffffffu, tid >> 5, 0);
    const int ib = id >> 1, ty = id & 1;
    float* scs = (float*)(smem + S_MISC);
    if (w == 0) {
        const uint32_t bar = SB + S_AUX;
        if (lane == 0) mbar_init(bar, 1);
        wait_ge(&g_ctl.pieces_done, NPC);
        fence_acquire();
        if (lane == 0) {
            asm volatile("fence.proxy.async.global;" ::: "memory");
            asm volatile("fence.proxy.async.shared::cta;" ::: "memory");
            asm volatile("mbarrier.arrive.expect_tx.shared.b64 _, [%0], %1;" ::"r"(bar), "r"(ROWS_I * 4) : "memory");
            constexpr uint32_t PART = (ROWS_I * 4 / 8 + 127) / 128 * 128;
            for (uint32_t o = 0; o < ROWS_I * 4; o += PART)
                asm volatile("cp.async.bulk.shared::cluster.global.mbarrier::complete_tx::bytes [%0], [%1], %2, [%3];"
                             ::"r"(SB + o), "l"((const char*)(g_md[ty] + ib * ROWS_I) + o), "r"(min(PART, ROWS_I * 4 - o)), "r"(bar) : "memory");
        }
        __syncwarp();
            float sc[4]; bool bad;
        get_scales(p, sc, bad);
            if (bad) { st_relaxed(&g_ctl.bad, 1); sc[0] = sc[1] = sc[2] = sc[3] = 0.f; }
        int it = 0; uint32_t pb;
        while (!((pb = ld_relaxed(&g_ctl.pagebits)) >> 31)) backoff(it);
        if (lane == 0) { scs[0] = sc[0]; scs[1] = sc[1]; scs[2] = sc[2]; scs[3] = sc[3]; ((uint32_t*)scs)[4] = X ? ~pb : pb; ((uint32_t*)scs)[5] = bad; }
        mbar_wait(bar, 0);
    }
    __syncthreads();
    if (((uint32_t*)scs)[5]) {
        for (int k = tid; k < (int)ROWS_I; k += THREADS) ((uint32_t*)smem)[k] = 0;
        __syncthreads();
    }
    const uint32_t NT = p.NS + 2 * GR;
    if (w >= MW) return;
    const uint32_t pagebits = ((uint32_t*)scs)[4];
    const int half = lane >> 4, k4 = (lane & 15) * 4;
    const float s_lo = scs[2 * ty], s_hi = scs[2 * ty + 1];
    const float MAG_LO = 12582912.f, MAG_HI = 12582912.f - 19264.f;
    const int il = ib / NG, gi = (ib % NG) * 2 + X;
    const uint32_t a_off = R_A + il * R_UNIT + lane * 16, v_off = ty * R_V1 + il * R_UNIT + lane * 16;
    const uint32_t f_off = OFF_PF + il * 32 + half * 16, r_off = OFF_REL + (lane % NCP) * 4;
    const uint32_t j = w % (NP / GR);
    PROF_DECL
#pragma unroll 1
    for (uint32_t n = w / (NP / GR); n < NT; n += MW / (NP / GR)) {
        const uint32_t q = ((gi - n) & (GR - 1)) + GR * j, h = n >> 1;
        const uint32_t qb = q_base(q, pagebits), bb = qb ^ slot_off(h % RB);
        const uint32_t tag = (h / RB + 1) << 22;
        uint4 cw; int it = 0;
        while (true) {
            cw = ld_relaxed4(ring + (bb ^ f_off));
            if (__all_sync(0xffffffffu, min(min(cw.x, cw.y), cw.z) >= tag)) break;
            if (DEV_FREE) { cw.x = (cw.x & 1) + (63 | 57 << 7 | 50 << 14 | 1 << 21); cw.y = (cw.y & 1) + (53 | 61 << 7 | 57 << 14); cw.z = (cw.z & 1) + (59 | 52 << 7 | 57 << 14); break; }
            backoff(it);
        }
        PROF(0);
        if (__any_sync(0xffffffffu, cw.x & (1u << 21))) {
            const unsigned char* pa = ring + (qb ^ slot_off(h % RA) ^ a_off);
            unsigned char* pv = ring + (qb ^ slot_off(h % RV) ^ v_off);
            const uint32_t hv = h + RB - RV;
            const unsigned char* prel = ring + (qb ^ slot_off(hv % RB) ^ r_off);
            const uint32_t rel = ld_relaxed(prel);
            const uint32_t vlap = h / RV;
            const float mag_lo0 = MAG_LO + (float)(8192 + (vlap & 3) * 16384), mag_hi0 = MAG_HI + (float)(8192 + ((vlap >> 2) & 3) * 16384);
            const uint32_t stamp = ((h / RA) & ~(lane ^ (lane >> 3)) & 1) << 30;
            uint4 a[9];
#define M_LOAD(ps) a[ps] = ld_relaxed4(pa + (ps) * 512 + ((ps) < 4 ? 0 : R_HI))
#pragma unroll
            for (int ps = 0; ps < MPF; ps++) M_LOAD(ps);
            if (!__all_sync(0xffffffffu, rel >= hv / RB) && !DEV_FREE) wait_all_ge(prel, hv / RB);
            PROF(3);
#pragma unroll
            for (int ps = 0; ps < 9; ps++) {
                const int rem = (int)(((ps < 3 ? cw.x : ps < 6 ? cw.y : cw.z) >> (7 * (ps % 3))) & 0x7f) - k4;
                if (ps % 3 == 0) {
#define M_STAMP(ps) (((ps) & 3) == 0 ? a[ps].x : ((ps) & 3) == 1 ? a[ps].y : ((ps) & 3) == 2 ? a[ps].z : a[ps].w)
                    while (true) {
                        M_STAMP(ps) ^= stamp; M_STAMP(ps + 1) ^= stamp; M_STAMP(ps + 2) ^= stamp;
                        if (!__any_sync(0xffffffffu, (M_STAMP(ps) | M_STAMP(ps + 1) | M_STAMP(ps + 2)) & 0x40000000u)) break;
                        if (DEV_FREE) { M_STAMP(ps) &= 0xbfffffffu; M_STAMP(ps + 1) &= 0xbfffffffu; M_STAMP(ps + 2) &= 0xbfffffffu; break; }
                        if (++it > SPIN_MAX) __trap();
                        M_LOAD(ps); M_LOAD(ps + 1); M_LOAD(ps + 2);
                    }
                }
                uint32_t aw[4] = {a[ps].x, a[ps].y, a[ps].z, a[ps].w}, mv[4], vw[4];
#pragma unroll
                for (int e = 0; e < 4; e++) { mv[e] = 0; lds_lt(mv[e], __dp2a_lo(aw[e], 4u, (uint32_t)SB), e, rem); }
#pragma unroll
                for (int e = 0; e < 4; e++) {
                    float c = bf_hi(aw[e]);
                    float lo = fmaf(bf_lo(mv[e]), c * s_lo, e ? MAG_LO : mag_lo0), hi = fmaf(bf_hi(mv[e]), c * s_hi, e ? MAG_HI : mag_hi0);
                    vw[e] = (__float_as_uint(hi) << 16) + __float_as_uint(lo);
                }
                asm volatile("st.global.v4.u32 [%0], {%1,%2,%3,%4};" ::"l"(pv + ps * 512 + (ps < 4 ? 0 : R_HI)), "r"(vw[0]), "r"(vw[1]), "r"(vw[2]), "r"(vw[3]) : "memory");
                if (ps + MPF < 9) M_LOAD(ps + MPF);
            }
            if (vlap == 0 || n >= p.NS) fence_release();
        }
        st_lane0(ring + (bb ^ (OFF_RDY + (2 * il + ty) * 4)), cw.x >> 21, lane);
        PROF(1);
    }
    PROF_END;
}

__device__ __noinline__ void c_wrap(uint32_t row, int par, uint32_t old, uint32_t w) {
    const uint32_t nw = old + w, ov = ~(old ^ w) & (old ^ nw);
    int d = 0;
    if (ov & 0x8000u) d += (w & 0x8000u) ? -1 : 1;
    if (ov & 0x80000000u) d += (w & 0x80000000u) ? -16 : 16;
    if (d != 0) {
        uint32_t c;
        asm volatile("atom.shared.add.u32 %0, [%1], %2;" : "=r"(c) : "r"(SB + C_WRAP + row * 4), "r"(d << (8 * par)) : "memory");
        c = (c >> (8 * par)) + d;
        if (((c + 1) & 0xe) == 0 || ((c + 16) & 0xe0) == 0) st_relaxed(&g_ctl.bad, 1);
    }
}

#define CGRP 6
struct CTask { uint4 v[3]; uint2 b[3]; };
struct CWork {
    unsigned char* ring;
    uint32_t v_off, b_off, f_off, r_off, acc;
    uint32_t lap1, sv, sb, vtag, fw, stamp;
    int lane, dev_free;
    template <int ODD> __device__ __forceinline__ bool issue(CTask& t) {
        if (!__all_sync(0xffffffffu, fw >= 2 * lap1)) {
            int it = 0;
            do {
                if (dev_free) { fw = 1; break; }
                backoff(it);
                fw = ld_relaxed(ring + (f_off ^ slot_off(sb) ^ (ODD << 20)));
            } while (!__all_sync(0xffffffffu, fw >= 2 * lap1));
        }
        const bool data = __any_sync(0xffffffffu, fw & 1);
        if (data) {
            const unsigned char* pv = ring + (v_off ^ slot_off(sv) ^ (ODD << 20));
            const unsigned char* pb = ring + (b_off ^ slot_off(sb) ^ (ODD << 20));
#pragma unroll
            for (int ps = 0; ps < 3; ps++) {
                t.v[ps] = ld_relaxed4(pv + ps * R_UNIT);
                t.b[ps] = ld_relaxed2(pb + ps * R_UNIT);
            }
        }
        fw = ld_relaxed(ring + (f_off ^ slot_off(ODD ? (sb + 1 == RB ? 0 : sb + 1) : sb) ^ (!ODD << 20)));
        return data;
    }
    template <int ODD> __device__ __forceinline__ void arrive(CTask& t, bool data) {
        if (data) {
            int it = 0;
            while (true) {
#pragma unroll
                for (int ps = 0; ps < 3; ps++) t.b[ps].x ^= stamp;
                if (!__any_sync(0xffffffffu, (((t.v[0].x ^ vtag) | (t.v[1].x ^ vtag) | (t.v[2].x ^ vtag)) & 0xc000c000u) | ((t.b[0].x | t.b[1].x | t.b[2].x) & 0x8000u))) break;
                if (dev_free) { for (int ps = 0; ps < 3; ps++) { t.v[ps].x = (t.v[ps].x & 0x3fff3fffu) | (vtag & 0xc000c000u); t.b[ps].x &= 0xffff7fffu; } break; }
                if (++it > SPIN_MAX) __trap();
#pragma unroll
                for (int ps = 0; ps < 3; ps++) {
                    t.v[ps] = ld_relaxed4(ring + (v_off ^ slot_off(sv) ^ (ODD << 20)) + ps * R_UNIT);
                    t.b[ps] = ld_relaxed2(ring + (b_off ^ slot_off(sb) ^ (ODD << 20)) + ps * R_UNIT);
                }
            }
#pragma unroll
            for (int ps = 0; ps < 3; ps++) t.v[ps].x -= vtag;
        }
        st_lane0(ring + (r_off ^ slot_off(sb) ^ (ODD << 20)), lap1, lane);
        if (ODD) {
            if (++sv == RV) { sv = 0; vtag += 0x4000u; if (vtag & 0x10000u) vtag += 0x3fff0000u; }
            if (++sb == RB) { sb = 0; lap1++; stamp ^= (((b_off >> 3) ^ (b_off >> 7)) & 3) == 0 ? 0x8000u : 0u; }
        }
    }
    __device__ __forceinline__ void add(const CTask& t, bool data) {
        if (!data) return;
        const uint32_t vw[12] = {t.v[0].x, t.v[0].y, t.v[0].z, t.v[0].w, t.v[1].x, t.v[1].y, t.v[1].z, t.v[1].w, t.v[2].x, t.v[2].y, t.v[2].z, t.v[2].w};
        const uint32_t bw[6] = {t.b[0].x, t.b[0].y, t.b[1].x, t.b[1].y, t.b[2].x, t.b[2].y};
#pragma unroll
        for (int g = 0; g < 12; g += CGRP) {
            uint32_t old[CGRP], ov = 0;
#pragma unroll
            for (int e = g; e < g + CGRP; e++)
                asm volatile("atom.shared.add.u32 %0, [%1], %2;" : "=r"(old[e - g]) : "r"((e & 1) ? __dp2a_hi(bw[e >> 1], 0x08000008u, acc) : __dp2a_lo(bw[e >> 1], 0x08000008u, acc)), "r"(vw[e]) : "memory");
#pragma unroll
            for (int e = g; e < g + CGRP; e++) ov |= ~(old[e - g] ^ vw[e]) & (old[e - g] ^ (old[e - g] + vw[e]));
            if (__any_sync(0xffffffffu, ov & 0x80008000u)) {
#pragma unroll
                for (int e = g; e < g + CGRP; e++) c_wrap((e & 1) ? bw[e >> 1] >> 16 : bw[e >> 1] & 0xffffu, lane >> 4, old[e - g], vw[e]);
            }
        }
    }
};

__device__ __forceinline__ void c_role(const Prm& p, unsigned char* ring, int X, int c) {
    const int tid = threadIdx.x, lane = tid & 31, w = __shfl_sync(0xffffffffu, tid >> 5, 0);
    uint32_t* misc = (uint32_t*)(smem + S_MISC);
    Wts* wt = (Wts*)(smem + S_AUX);
    load_wts(p, wt);
    if (tid == 0) misc[6] = TAB_N;
    __syncthreads();
    if (w == 0) {
        float sc[4]; bool bad;
        wait_ge(&g_ctl.pieces_done, NPC);
        fence_acquire();
        get_scales(p, sc, bad);
        const float s = (lane & 2) ? ((lane & 1) ? sc[3] : sc[2]) : ((lane & 1) ? sc[1] : sc[0]);
        wt->ws[lane] *= s > 0.f ? 1.f / s : 0.f;
        int it = 0; uint32_t pb;
        while (!((pb = ld_relaxed(&g_ctl.pagebits)) >> 31)) backoff(it);
        misc[4] = X ? ~pb : pb;
    } else {
        const int r0 = (X * NCP + c) * ROWS_O, nr = min((int)ROWS_O, p.E - r0);
#pragma unroll 4
        for (int r = tid - 32; r < (int)ROWS_O / 2; r += THREADS - 32) {
            const uint32_t d2 = 2 * r < nr ? __ldg((const uint32_t*)(p.dist + r0) + r) : TAB_LO * 0x10001u;
            uint32_t e[2] = {(d2 & 0xffff) - TAB_LO, (d2 >> 16) - TAB_LO};
#pragma unroll
            for (int k = 0; k < 2; k++)
                if (e[k] >= TAB_N) {
                    const uint32_t d = e[k] + TAB_LO;
                    if ((d & 0x7f80) == 0x7f80) st_relaxed(&g_ctl.bad, 1);
                    e[k] = min(atomicAdd(&misc[6], 1u), 0xffffu);
                    if (e[k] < TAB_N + TAB_X) ((uint32_t*)(smem + C_TAB))[e[k] * 4] = d;
                }
            ((uint2*)(smem + C_WRAP))[r] = make_uint2(e[0] << 16 | 0x8888u, e[1] << 16 | 0x8888u);
        }
    }
    __syncthreads();
    if (w >= NP / 2) {
        const int nt = min(misc[6], (uint32_t)(TAB_N + TAB_X));
        for (int k = tid - NP * 16; k < nt; k += THREADS - NP * 16)
            ((uint4*)(smem + C_TAB))[k] = radial_bf16(wt, k < TAB_N ? TAB_LO + k : ((uint32_t*)(smem + C_TAB))[k * 4]);
        if (tid == THREADS - 1 && !DEV_FREE) {
            const uint32_t h = p.NS >> 1;
            const unsigned char* f = ring + (q_base(X, misc[4]) ^ slot_off(h % RB) ^ (OFF_REL + c * 4));
            for (int it = 0; ld_relaxed(f) < h / RB; it++) { __nanosleep(2000); if (it > SPIN_MAX) __trap(); }
            const int r0 = (X * NCP + c) * ROWS_O, nr = min((int)ROWS_O, p.E - r0);
            if (nr > 0) asm volatile("cp.async.bulk.prefetch.L2.global [%0], %1;" ::"l"(p.m + r0), "r"(nr * 8) : "memory");
        }
    }
    const uint32_t pagebits = misc[4];
    if (w >= NP / 2) return;
    CWork W;
    const int par = lane >> 4;
    W.ring = ring; W.lane = __shfl_sync(0xffffffffu, lane, lane); W.dev_free = DEV_FREE;
    const uint32_t qb = q_base(2 * w + X, pagebits), k = lane & 15;
    W.acc = __shfl_sync(0xffffffffu, SB + par * 4, lane);
    W.v_off = __shfl_sync(0xffffffffu, qb ^ (par * R_V1 + (c < 8 ? 0 : R_HI) + c * 256 + k * 16), lane);
    W.b_off = __shfl_sync(0xffffffffu, qb ^ (R_B + c * 128 + k * 8), lane);
    W.f_off = __shfl_sync(0xffffffffu, qb ^ (OFF_RDY + (lane % 6) * 4), lane);
    W.r_off = qb ^ (OFF_REL + c * 4);
    W.lap1 = 1; W.sv = W.sb = W.fw = W.stamp = 0; W.vtag = 0x20002000u;
    const uint32_t NT = p.NS + 2 * GR;
    CTask A, B;
    PROF_DECL
    bool da = W.issue<0>(A), db;
#pragma unroll 1
    for (uint32_t n = 2;; n += 2) {
        W.arrive<0>(A, da); PROF(1); db = W.issue<1>(B); PROF(0); W.add(A, da);
        W.arrive<1>(B, db);
        if (n >= NT) break;
        PROF(1); da = W.issue<0>(A); PROF(0); W.add(B, db);
    }
    W.add(B, db);
    PROF_END;
}

__device__ __forceinline__ uint32_t bf2_mul(uint32_t a, uint32_t b) { uint32_t r; asm("mul.rn.bf16x2 %0, %1, %2;" : "=r"(r) : "r"(a), "r"(b)); return r; }
__device__ __forceinline__ uint32_t bf2_fma(uint32_t a, uint32_t b, uint32_t c) { uint32_t r; asm("fma.rn.bf16x2 %0, %1, %2, %3;" : "=r"(r) : "r"(a), "r"(b), "r"(c)); return r; }
__device__ __forceinline__ uint32_t c_agg(uint32_t a, uint32_t s, uint32_t wr, bool wrapped) {
    int x0 = (short)a, x1 = ((int)a >> 16) + ((a >> 15) & 1);
    if (wrapped) { const int w0 = (int)(wr & 15) - 8, w1 = (int)((wr >> 4) & 15) - 8; x0 += 65536 * w0; x1 += 65536 * w1 - w0; }
    return pack_bf16((float)x1 * bf_hi(s), (float)x0 * bf_lo(s));
}
__device__ __forceinline__ void c_epilogue(const Prm& p, int X, int c) {
    const int tid = threadIdx.x, lane = tid & 31;
    const Wts* wt = (const Wts*)(smem + S_AUX);
    uint32_t bw[4];
#pragma unroll
    for (int k = 0; k < 4; k++) {
        const int col = (k >> 1) * 2 + ((lane >> 2) & 1), row = (k & 1) * 2;
        bw[k] = (lane >> 3) == (lane & 3) ? pack_bf16(wt->wu[(row + 1) * 4 + col], wt->wu[row * 4 + col]) : 0u;
    }
    const int r0 = (X * NCP + c) * ROWS_O, np = max(min((int)ROWS_O, p.E - r0), 0) / 2;
    const uint4* mp = (const uint4*)(p.m + r0);
    uint4* op = (uint4*)(p.out + r0);
    constexpr int EB = 5;
#pragma unroll 1
    for (int rb = tid; rb - lane < np; rb += EB * THREADS) {
        uint4 mr[EB];
#pragma unroll
        for (int k = 0; k < EB; k++) mr[k] = __ldg(mp + min(rb + k * THREADS, np - 1));
#pragma unroll
        for (int k = 0; k < EB; k++) {
            const int r = min(rb + k * THREADS, np - 1);
            const uint4 a = ((const uint4*)smem)[r];
            const uint2 wr = ((const uint2*)(smem + C_WRAP))[r];
            const uint4 t0 = ((const uint4*)(smem + C_TAB))[min(wr.x >> 16, (uint32_t)(TAB_N + TAB_X - 1))];
            const uint4 t1 = ((const uint4*)(smem + C_TAB))[min(wr.y >> 16, (uint32_t)(TAB_N + TAB_X - 1))];
            const bool wrapped = __any_sync(0xffffffffu, prmt(wr.x, wr.y, 0x5410) != 0x88888888u);
            uint32_t a0, a1, a2, a3;
            if (wrapped) { a0 = c_agg(a.x, t0.x, wr.x, true); a2 = c_agg(a.y, t0.y, wr.x >> 8, true); a1 = c_agg(a.z, t1.x, wr.y, true); a3 = c_agg(a.w, t1.y, wr.y >> 8, true); }
            else { a0 = c_agg(a.x, t0.x, 0, false); a2 = c_agg(a.y, t0.y, 0, false); a1 = c_agg(a.z, t1.x, 0, false); a3 = c_agg(a.w, t1.y, 0, false); }
            float u[8];
#pragma unroll
            for (int h = 0; h < 2; h++)
                asm("mma.sync.aligned.m16n8k16.row.col.f32.bf16.bf16.f32 {%0,%1,%2,%3}, {%4,%5,%6,%7}, {%8,%9}, {%10,%10,%10,%10};"
                    : "=f"(u[4 * h]), "=f"(u[4 * h + 1]), "=f"(u[4 * h + 2]), "=f"(u[4 * h + 3])
                    : "r"(a0), "r"(a1), "r"(a2), "r"(a3), "r"(bw[2 * h]), "r"(bw[2 * h + 1]), "f"(0.f));
            const uint4 o = make_uint4(bf2_fma(pack_bf16(u[1], u[0]), t0.z, mr[k].x), bf2_fma(pack_bf16(u[5], u[4]), t0.w, mr[k].y),
                                       bf2_fma(pack_bf16(u[3], u[2]), t1.z, mr[k].z), bf2_fma(pack_bf16(u[7], u[6]), t1.w, mr[k].w));
            if (rb + k * THREADS < np) op[r] = o;
        }
    }
    if (((const uint32_t*)(smem + S_MISC))[6] > TAB_N + TAB_X) {
        for (int r = 2 * tid; r < 2 * np; r += (r & 1) ? 2 * THREADS - 1 : 1) {
            const uint32_t wr = ((const uint32_t*)(smem + C_WRAP))[r];
            if ((wr >> 16) < TAB_N + TAB_X) continue;
            const uint4 t = radial_bf16(wt, __bfloat16_as_ushort(p.dist[r0 + r]));
            const uint2 a = ((const uint2*)smem)[r];
            const uint32_t a0 = c_agg(a.x, t.x, wr, true), a1 = c_agg(a.y, t.y, wr >> 8, true);
            const float agg[4] = {bf_lo(a0), bf_hi(a0), bf_lo(a1), bf_hi(a1)}, g[4] = {bf_lo(t.z), bf_hi(t.z), bf_lo(t.w), bf_hi(t.w)};
            p.out[r0 + r] = finish_row(wt->wu, agg, g, p.m[r0 + r]);
        }
    }
}

__device__ __forceinline__ void grid_bar(unsigned* ctr) {
    __syncthreads();
    if (threadIdx.x == 0) { fence_gpu(); red_add(ctr, 1); wait_ge(ctr, gridDim.x); fence_gpu(); }
    __syncthreads();
}
__device__ __noinline__ void fallback(const Prm& p) {
    const int gt = blockIdx.x * THREADS + threadIdx.x, gs = gridDim.x * THREADS;
    Wts* wt = (Wts*)smem;
    __syncthreads();
    load_wts(p, wt);
    for (int e = gt; e < p.E; e += gs) g_acc[e] = make_float4(0.f, 0.f, 0.f, 0.f);
    grid_bar(&g_ctl.bar[0]);
    const float f = __bfloat162float(p.freq[0]);
    for (int t = gt; t < p.T; t += gs) {
        uint2 r = __ldg(p.m + p.idx_in[t]);
        float c = rbf16(cosf(rbf16(f * __bfloat162float(p.angle[t]))));
        asm volatile("red.global.add.v4.f32 [%0], {%1,%2,%3,%4};" ::"l"(g_acc + p.idx_out[t]), "f"(bf_lo(r.x) * c),
                     "f"(bf_hi(r.x) * c), "f"(bf_lo(r.y) * c), "f"(bf_hi(r.y) * c) : "memory");
    }
    grid_bar(&g_ctl.bar[1]);
    for (int e = gt; e < p.E; e += gs) {
        float4 a4 = __ldcg(g_acc + e);
        float a[4] = {a4.x, a4.y, a4.z, a4.w}, s[4], g[4];
        radial(wt, __bfloat162float(p.dist[e]), s, g);
        float agg[4];
#pragma unroll
        for (int j = 0; j < 4; j++) agg[j] = s[j] * (a[0] * wt->wd[j] + a[1] * wt->wd[4 + j] + a[2] * wt->wd[8 + j] + a[3] * wt->wd[12 + j]);
        p.out[e] = finish_row(wt->wu, agg, g, p.m[e]);
    }
}

__device__ __forceinline__ void smem_init(bool isp, int from, int to) {
    for (int k = from / 16 + threadIdx.x; k < to / 16; k += THREADS) {
        const bool b = isp && k >= P_B / 16 && k < P_Q / 16;
        const uint32_t z = b ? (k & 7) * 0x20002u : 0u, y = b ? z + 0x10001u : 0u;
        ((uint4*)smem)[k] = make_uint4(z, z, y, y);
    }
}

__global__ void __launch_bounds__(THREADS, 1) gemnet_kernel(const __grid_constant__ Prm p) {
    const int tid = threadIdx.x, lane = tid & 31, w = __shfl_sync(0xffffffffu, tid >> 5, 0);
    uint32_t* misc = (uint32_t*)(smem + S_MISC);
    bool run_fallback = true;
    if (!p.force_bad && __cvta_generic_to_shared(smem) == SB) {
        unsigned char* const ring = p.ring;
        uint32_t smid; asm("mov.u32 %0, %%smid;" : "=r"(smid));
        const int cls = smid < NM ? 0 : (smid < NM + NP - 4 || (smid >= 124 && smid < 128)) ? 2 : 1;
        if (lane == 0) {
            if (w < 2 && (cls != 2 || blockIdx.x == 0)) misc[16 + w] = probe(ring + OFF_PROBE + w * 4096 + ((blockIdx.x >> 7) << 20) + (blockIdx.x & 127) * 32);
            else if (blockIdx.x == 0 && w <= NPAGES) misc[16 + w] = probe(ring + ((size_t)(w - 1) << 21) + OFF_PROBE);
        }
        float wd[16];
        if (cls != 2 || blockIdx.x == 0) __syncthreads();
        if (tid == 0) {
            int pool = cls == 2 ? 4 : cls * 2 + (misc[16] > misc[17]), id = 0;
            for (int k = 0; k < 7; k++) {
                int cap = pool < 2 ? NMP : pool < 4 ? NCP : NP;
                id = atomicAdd(&g_ctl.ticket[pool], 1);
                if (id < cap) break;
                pool = k == 0 ? (pool == 4 ? 0 : pool ^ 1) : k - 1;
            }
            misc[8] = pool; misc[9] = id;
            if (pool != 4) down_load(p, pool < 2 ? pool * NMP + id : NM + (pool - 2) * NCP + id);
        }
        if (blockIdx.x == 0 && tid == 32) {
            uint32_t pb = 0x80000000u;
            for (int k = 1; k < NPAGES; k++) pb |= (uint32_t)((2 * misc[17 + k] > misc[16] + misc[17]) != (misc[16] > misc[17])) << k;
            st_relaxed(&g_ctl.pagebits, pb);
        }
#pragma unroll
        for (int k = 0; k < 16; k++) wd[k] = __bfloat162float(p.w_down[k]);
        if (cls == 2) smem_init(true, 0, S_PC);
        __syncthreads();
        const int pool = misc[8], id = misc[9];
        if (pool >= 2 && (pool < 4 || cls != 2)) smem_init(pool == 4, 0, S_PC);
        if (pool != 4) down_piece(p, pool < 2 ? pool * NMP + id : NM + (pool - 2) * NCP + id, wd);
        if (DEV_FREE && !(DEV_FREE & (pool == 4 ? 1 : pool < 2 ? 2 : 4))) {
        } else if (pool == 4) {
            smem_init(true, S_PC, S_MISC);
            __syncthreads();
            if (tid < 2 * NBUF) {
                const uint32_t a = tid < NBUF ? bar_done(tid) : bar_free(tid), cnt = tid < NBUF ? CPS : 1;
                mbar_init(a, cnt);
                if (tid % NBUF < id % GR) asm volatile("mbarrier.arrive.shared.b64 _, [%0], %1;" ::"r"(a), "r"(cnt) : "memory");
            }
            __syncthreads();
            if (w < FW) p_filler(p, id, w);
            else if (w < FW + NF) {
                int it = 0; uint32_t pb;
                while (!((pb = ld_relaxed(&g_ctl.pagebits)) >> 31)) backoff(it);
                p_flusher(p, ring, __shfl_sync(0xffffffffu, pb, 0), id, w - FW);
            }
        } else if (pool < 2) {
            m_role(p, ring, pool, id);
        } else {
            c_role(p, ring, pool - 2, id);
        }
        __syncthreads();
        if (tid == 0) { fence_gpu(); red_add(&g_ctl.fin, 1); }
        if ((pool == 2 || pool == 3) && !DEV_FREE) c_epilogue(p, pool - 2, id);
        if (tid == 0) { wait_ge(&g_ctl.fin, NCTA); fence_gpu(); misc[10] = ld_relaxed(&g_ctl.bad); }
        __syncthreads();
        if (pool == 4) p_cleanup(ring, id);
        run_fallback = misc[10] && !DEV_FREE;
    }
    if (run_fallback) fallback(p);
    if (tid == 0) {
        fence_gpu();
        if (atomicAdd(&g_ctl.exited, 1) == gridDim.x - 1) {
            uint32_t* c = (uint32_t*)&g_ctl;
            for (int k = 0; k < 32; k++) c[k] = 0;
        }
    }
}

cudaTextureObject_t make_tex(const void* ptr, size_t bytes, int words) {
    cudaResourceDesc rd = {};
    rd.resType = cudaResourceTypeLinear;
    rd.res.linear.devPtr = (void*)ptr;
    rd.res.linear.desc = words == 4 ? cudaCreateChannelDesc<uint4>() : cudaCreateChannelDesc<uint2>();
    rd.res.linear.sizeInBytes = bytes;
    cudaTextureDesc td = {};
    td.readMode = cudaReadModeElementType;
    cudaTextureObject_t t = 0;
    if (cudaCreateTextureObject(&t, &rd, &td, nullptr) != cudaSuccess) { cudaGetLastError(); return 0; }
    return t;
}

}

extern "C" void kernel_launch(void* const* d_in, const int* in_sizes, int n_in, void* d_out, int out_size) {
    static Prm p = {};
    static int grid = 0;
    const int E = in_sizes[3], T = in_sizes[1];
    if (grid == 0 || p.idx_in != d_in[1] || p.idx_out != d_in[2] || p.angle != d_in[4] || p.E != E || p.T != T) {
        int dev = 0, sms = 0;
        cudaGetDevice(&dev);
        cudaDeviceGetAttribute(&sms, cudaDevAttrMultiProcessorCount, dev);
        cudaFuncSetAttribute(gemnet_kernel, cudaFuncAttributeMaxDynamicSharedMemorySize, SMEM_BYTES);
        p.E = E; p.T = T;
        p.NS = ((T / 128 + NP * CPS - 1) / (NP * CPS) + 1) & ~1;
        void* rp = nullptr;
        cudaGetSymbolAddress(&rp, g_ring);
        p.ring = (unsigned char*)(((uintptr_t)rp + ((2u << 20) - 1)) & ~(uintptr_t)((2u << 20) - 1));
        bool fast = sms >= NCTA && E <= (int)FAST_E && (E & 1) == 0 && T >= 128 && T <= (1 << 29);
        if (fast) {
            p.t_in = make_tex(d_in[1], (size_t)(T / 128) * 512, 4);
            p.t_out = make_tex(d_in[2], (size_t)(T / 128) * 512, 4);
            p.t_ang = make_tex(d_in[4], (size_t)(T / 128) * 256, 2);
            fast = p.t_in && p.t_out && p.t_ang;
        }
        p.force_bad = !fast;
        grid = fast ? NCTA : sms;
    }
    p.m = (const uint2*)d_in[0];
    p.idx_in = (const int*)d_in[1];
    p.idx_out = (const int*)d_in[2];
    p.dist = (const __nv_bfloat16*)d_in[3];
    p.angle = (const __nv_bfloat16*)d_in[4];
    p.centers = (const __nv_bfloat16*)d_in[5];
    p.freq = (const __nv_bfloat16*)d_in[6];
    p.w_rbf = (const __nv_bfloat16*)d_in[7];
    p.w_sbf = (const __nv_bfloat16*)d_in[8];
    p.w_down = (const __nv_bfloat16*)d_in[9];
    p.w_up = (const __nv_bfloat16*)d_in[10];
    p.out = (uint2*)d_out;
    gemnet_kernel<<<grid, THREADS, SMEM_BYTES>>>(p);
}
```

```cpp
#include <cuda_runtime.h>
#include <cuda_bf16.h>
#include <stdint.h>

namespace {

constexpr int NI = 12;
constexpr int UN = 3;
constexpr int NG = NI / UN;
constexpr int GR = 2 * NG;
constexpr int NCP = 18;
constexpr int NO = 2 * NCP;
constexpr int KS = 64;
constexpr int NB = UN * NCP;
constexpr int NBUF = 10;
constexpr int NMP = 2 * NI;
constexpr int NP = 48, NM = 2 * NMP, NC = NO, NCTA = NP + NM + NC;
#define CPS_ 25
constexpr int CPS = CPS_;
#define FW_ 24
constexpr int FW = FW_;
constexpr int NF = 4;
#define RA_ 3
#define RV_ 3
#define RB_ 4
constexpr int RA = RA_, RV = RV_, RB = RB_;
#define QN_ 96
#define QTRIG_ 48
constexpr int QN = QN_, QTRIG = QTRIG_;
#define MW_ 18
constexpr int MW = MW_;
#define MPF_ 6
constexpr int MPF = MPF_;
constexpr int THREADS = 896, NW = THREADS / 32;
#define DEV_FREE 0
#define SLEEP_ 50

constexpr int RING_BYTES = NP << 20;
constexpr int NPAGES = RING_BYTES >> 21;
constexpr int MAX_E = 1 << 20;
constexpr int SMEM_BYTES = 232448;

constexpr int SB = 1024;

constexpr int P_CNT = 0;
constexpr int P_BAR = P_CNT + NBUF * NB * 4;
constexpr int P_TKT = P_BAR + 2 * NBUF * 8;
constexpr int P_B = (P_TKT + 128 + 127) / 128 * 128;
constexpr int P_Q = P_B + NBUF * NB * KS * 2;
constexpr int P_A = SMEM_BYTES - 256 - NBUF * NB * KS * 4;
static_assert(P_Q + FW * QN * 8 + 512 <= P_A && P_A % 128 == 0, "P smem");
constexpr int S_MISC = SMEM_BYTES - 256;
constexpr int S_AUX = S_MISC - 512;

constexpr unsigned FAST_E = 640000;
constexpr unsigned magic_of(unsigned long long d) { return (unsigned)(((1ull << 32) + d - 1) / d); }
constexpr bool magic_ok(unsigned long long d) { return (magic_of(d) * d - (1ull << 32)) * FAST_E < (1ull << 32); }
constexpr unsigned pick_rows(unsigned lo) {
    unsigned d = (lo + 3) & ~3u;
    while (!magic_ok(d)) d += 4;
    return d;
}
constexpr unsigned ROWS_I = pick_rows((FAST_E + NI - 1) / NI), ROWS_O = pick_rows((FAST_E + NO - 1) / NO);
constexpr unsigned MAG_I = magic_of(ROWS_I), MAG_O = magic_of(ROWS_O), HALF_O = ROWS_O * NCP;
constexpr int C_WRAP = ROWS_O * 8, C_TAB = ROWS_O * 12, TAB_N = 1025, TAB_LO = 0x3f80 - 1024, TAB_X = (S_AUX - C_TAB) / 16 - TAB_N;
static_assert(ROWS_I * 4 <= S_AUX && TAB_X >= 100 && ROWS_I <= 65536 && ROWS_O <= 32768, "tables");

constexpr int NPC = NM + NC;
constexpr int PC_ROWS = ((FAST_E + NPC - 1) / NPC + 3) & ~3;
constexpr int S_PC = C_WRAP + 128 - C_WRAP % 128;
static_assert(S_PC + PC_ROWS * 8 + 1024 <= S_AUX, "pre-pass");
struct __align__(128) Ctl {
    unsigned ticket[5];
    unsigned pagebits;
    unsigned pieces_done, unused;
    unsigned bad;
    unsigned fin;
    unsigned bar[3];
    unsigned exited;
    unsigned pad[18];
    float stat[NPC][8];
};

struct Prm {
    const uint2* m; const int* idx_in; const int* idx_out; const __nv_bfloat16* dist; const __nv_bfloat16* angle;
    const __nv_bfloat16* centers; const __nv_bfloat16* freq; const __nv_bfloat16* w_rbf; const __nv_bfloat16* w_sbf;
    const __nv_bfloat16* w_down; const __nv_bfloat16* w_up; uint2* out;
    cudaTextureObject_t t_in, t_out, t_ang;
    int E, T;
    unsigned char* ring;
    int NS;
    int force_bad;
};

__device__ __align__(128) unsigned char g_ring[RING_BYTES + (2 << 20)];
__device__ Ctl g_ctl;
__device__ float4 g_acc[MAX_E];
__device__ __align__(128) uint32_t g_md[2][NI * ROWS_I];
#define TS(k)
#define PROF_DECL
#define PROF(k)
#define PROF_END

extern __shared__ __align__(128) unsigned char smem[];

__device__ __forceinline__ float bf_lo(uint32_t w) { return __uint_as_float(w << 16); }
__device__ __forceinline__ float bf_hi(uint32_t w) { return __uint_as_float(w & 0xffff0000u); }
__device__ __forceinline__ float rbf16(float x) { return __bfloat162float(__float2bfloat16_rn(x)); }
__device__ __forceinline__ uint32_t pack_bf16(float hi, float lo) {
    uint32_t r; asm("cvt.rn.bf16x2.f32 %0, %1, %2;" : "=r"(r) : "f"(hi), "f"(lo)); return r;
}
__device__ __forceinline__ uint32_t prmt(uint32_t a, uint32_t b, uint32_t c) {
    uint32_t r; asm("prmt.b32 %0, %1, %2, %3;" : "=r"(r) : "r"(a), "r"(b), "r"(c)); return r;
}
__device__ __forceinline__ uint32_t ld_relaxed(const void* p) {
    uint32_t v; asm volatile("ld.relaxed.gpu.global.u32 %0, [%1];" : "=r"(v) : "l"(p) : "memory"); return v;
}
__device__ __forceinline__ uint2 ld_relaxed2(const void* p) {
    uint2 v; asm volatile("ld.relaxed.gpu.global.v2.u32 {%0,%1}, [%2];" : "=r"(v.x), "=r"(v.y) : "l"(p) : "memory"); return v;
}
__device__ __forceinline__ uint4 ld_relaxed4(const void* p) {
    uint4 v; asm volatile("ld.relaxed.gpu.global.v4.u32 {%0,%1,%2,%3}, [%4];" : "=r"(v.x), "=r"(v.y), "=r"(v.z), "=r"(v.w) : "l"(p) : "memory"); return v;
}
__device__ __forceinline__ void st_relaxed(void* p, uint32_t v) { asm volatile("st.relaxed.gpu.global.u32 [%0], %1;" ::"l"(p), "r"(v) : "memory"); }
__device__ __forceinline__ void st_relaxed16(void* p, uint32_t v) { asm volatile("st.relaxed.gpu.global.u16 [%0], %1;" ::"l"(p), "h"((uint16_t)v) : "memory"); }
__device__ __forceinline__ void red_add(void* p, uint32_t v) { asm volatile("red.relaxed.gpu.global.add.u32 [%0], %1;" ::"l"(p), "r"(v) : "memory"); }
__device__ __forceinline__ void fence_gpu() { asm volatile("fence.acq_rel.gpu;" ::: "memory"); }
__device__ __forceinline__ void fence_acquire() { asm volatile("fence.acquire.gpu;" ::: "memory"); }
__device__ __forceinline__ void fence_release() { asm volatile("fence.release.gpu;" ::: "memory"); }
__device__ __forceinline__ void mbar_init(uint32_t a, uint32_t n) { asm volatile("mbarrier.init.shared.b64 [%0], %1;" ::"r"(a), "r"(n) : "memory"); }
__device__ __forceinline__ void mbar_arrive(uint32_t a) { asm volatile("mbarrier.arrive.shared.b64 _, [%0];" ::"r"(a) : "memory"); }
__device__ __forceinline__ bool mbar_try(uint32_t a, uint32_t ph) {
    uint32_t ok;
    asm volatile("{.reg .pred p; mbarrier.try_wait.parity.shared.b64 p, [%1], %2, %3; selp.u32 %0, 1, 0, p;}" : "=r"(ok) : "r"(a), "r"(ph), "r"(2000) : "memory");
    return ok;
}
__device__ __forceinline__ bool mbar_test(uint32_t a, uint32_t ph) {
    uint32_t ok;
    asm volatile("{.reg .pred p; mbarrier.test_wait.parity.shared.b64 p, [%1], %2; selp.u32 %0, 1, 0, p;}" : "=r"(ok) : "r"(a), "r"(ph) : "memory");
    return ok;
}
constexpr int SPIN_MAX = 1 << 22;
__device__ __forceinline__ void mbar_wait(uint32_t a, uint32_t ph) {
    int it = 0;
    while (!mbar_try(a, ph)) { if (++it > SPIN_MAX) __trap(); }
}
__device__ __forceinline__ void backoff(int& it) { __nanosleep(SLEEP_); if (++it > SPIN_MAX) __trap(); }
__device__ __forceinline__ void wait_ge(const void* p, uint32_t v) {
    int it = 0;
    while (ld_relaxed(p) < v) backoff(it);
}

__device__ __forceinline__ bool elect_one() {
    uint32_t r; asm volatile("{.reg .pred p; elect.sync _|p, 0xffffffff; selp.u32 %0, 1, 0, p;}" : "=r"(r)); return r;
}
__device__ __forceinline__ void st_lane0(void* p, uint32_t v, int lane) {
    asm volatile("{.reg .pred p; setp.eq.s32 p, %2, 0; @p st.relaxed.gpu.global.u32 [%0], %1;}" ::"l"(p), "r"(v), "r"(lane) : "memory");
}
__device__ __forceinline__ void wait_all_ge(const void* p, uint32_t v) {
    int it = 0;
    while (!__all_sync(0xffffffffu, ld_relaxed(p) >= v)) backoff(it);
}
__device__ __forceinline__ void lds_lt(uint32_t& v, uint32_t ad, int a, int b) {
    asm volatile("{.reg .pred p; setp.lt.s32 p, %2, %3; @p ld.shared.u32 %0, [%1];}" : "+r"(v) : "r"(ad), "r"(a), "r"(b));
}

constexpr uint32_t R_V1 = 0x03000, R_A = 0x81000, R_B = 0x82000, R_UNIT = 0x4000, R_HI = 0x40000 - 8 * 256;
__device__ __forceinline__ uint32_t q_base(uint32_t q, uint32_t pagebits_x) { return (q << 20) | (((pagebits_x >> (q >> 1)) & 1u) << 12); }
__device__ __forceinline__ uint32_t slot_off(uint32_t s) { return (s << 16) | (((s + 1) & 2) << 11); }
constexpr uint32_t OFF_PF = R_B + 3 * R_UNIT, OFF_RDY = OFF_PF + 128, OFF_REL = OFF_PF + 256;
constexpr uint32_t OFF_PROBE = 3 * R_UNIT;
static_assert(RA <= 4 && RV <= 4 && RB <= 8 && RA <= RB && RV <= RB, "ring");

__device__ __forceinline__ uint32_t probe(unsigned char* p) {
    volatile uint32_t* sink = (volatile uint32_t*)(smem + S_MISC + 240);
    asm volatile("st.global.v4.u32 [%0], {%1,%1,%1,%1};" ::"l"(p), "r"(0) : "memory");
    asm volatile("st.global.v4.u32 [%0], {%1,%1,%1,%1};" ::"l"(p + 16), "r"(0) : "memory");
    uint32_t best = 0xffffffffu;
#pragma unroll 1
    for (int r = 0; r < 3; r++) {
        uint32_t t0, t1, v;
        asm volatile("mov.u32 %0, %%clock;" : "=r"(t0)::"memory");
        asm volatile("atom.relaxed.gpu.global.add.u32 %0, [%1], 1;" : "=r"(v) : "l"(p) : "memory");
        *sink = v;
        asm volatile("mov.u32 %0, %%clock;" : "=r"(t1)::"memory");
        best = min(best, t1 - t0);
    }
    return best;
}

struct Wts { float c[8], wr[32], ws[32], wd[16], wu[16]; };
__device__ __forceinline__ void load_wts(const Prm& p, Wts* w) {
    int t = threadIdx.x;
    if (t < 8) w->c[t] = __bfloat162float(p.centers[t]);
    if (t < 32) { w->wr[t] = __bfloat162float(p.w_rbf[t]); w->ws[t] = __bfloat162float(p.w_sbf[t]); }
    if (t < 16) { w->wd[t] = __bfloat162float(p.w_down[t]); w->wu[t] = __bfloat162float(p.w_up[t]); }
}
__device__ __forceinline__ void radial(const Wts* w, float d, float s[4], float g[4]) {
#pragma unroll
    for (int j = 0; j < 4; j++) s[j] = g[j] = 0.f;
#pragma unroll
    for (int r = 0; r < 8; r++) {
        float x = rbf16(d - w->c[r]);
        float b = rbf16(__expf(rbf16(-10.0f * rbf16(x * x))));
#pragma unroll
        for (int j = 0; j < 4; j++) { s[j] += b * w->ws[r * 4 + j]; g[j] += b * w->wr[r * 4 + j]; }
    }
}
__device__ __noinline__ uint4 radial_bf16(const Wts* w, uint32_t dbits) {
    float s[4], g[4];
    radial(w, __uint_as_float(dbits << 16), s, g);
    return make_uint4(pack_bf16(s[1], s[0]), pack_bf16(s[3], s[2]), pack_bf16(g[1], g[0]), pack_bf16(g[3], g[2]));
}
__device__ __forceinline__ uint2 finish_row(const float* wu, const float agg[4], const float g[4], uint2 r) {
    float o[4];
    const float mm[4] = {bf_lo(r.x), bf_hi(r.x), bf_lo(r.y), bf_hi(r.y)};
#pragma unroll
    for (int j = 0; j < 4; j++) o[j] = mm[j] + (agg[0] * wu[j] + agg[1] * wu[4 + j] + agg[2] * wu[8 + j] + agg[3] * wu[12 + j]) * g[j];
    return make_uint2(pack_bf16(o[1], o[0]), pack_bf16(o[3], o[2]));
}
__device__ __forceinline__ uint2 down_row(const float* wd, uint32_t x, uint32_t y) {
    const float a[4] = {bf_lo(x), bf_hi(x), bf_lo(y), bf_hi(y)};
    float d[4];
#pragma unroll
    for (int j = 0; j < 4; j++) d[j] = a[0] * wd[j] + a[1] * wd[4 + j] + a[2] * wd[8 + j] + a[3] * wd[12 + j];
    return make_uint2(pack_bf16(d[1], d[0]), pack_bf16(d[3], d[2]));
}

__device__ __forceinline__ void down_load(const Prm& p, int pc) {
    const int r0 = pc * PC_ROWS / 2, nr = max(min((pc + 1) * PC_ROWS, p.E) / 2 - r0, 0);
    const uint32_t bar = SB + S_MISC + 248;
    mbar_init(bar, 1);
    asm volatile("fence.proxy.async.shared::cta;" ::: "memory");
    asm volatile("mbarrier.arrive.expect_tx.shared.b64 _, [%0], %1;" ::"r"(bar), "r"(nr * 16) : "memory");
    for (int o = 0; o < nr; o += 640)
        asm volatile("cp.async.bulk.shared::cluster.global.mbarrier::complete_tx::bytes [%0], [%1], %2, [%3];"
                     ::"r"(SB + S_PC + o * 16), "l"((const uint4*)p.m + r0 + o), "r"(min(640, nr - o) * 16), "r"(bar) : "memory");
}
__device__ __forceinline__ void down_piece(const Prm& p, int pc, const float* wd) {
    const int tid = threadIdx.x, lane = tid & 31, w = tid >> 5;
    const int r0 = pc * PC_ROWS / 2, nr = max(min((pc + 1) * PC_ROWS, p.E) / 2 - r0, 0);
    mbar_wait(SB + S_MISC + 248, 0);
    uint32_t mx0 = 0, mx1 = 0; float ss[4] = {0.f, 0.f, 0.f, 0.f};
    for (int r = tid; r < nr; r += THREADS) {
        const uint4 v = ((const uint4*)(smem + S_PC))[r];
        const uint2 a = down_row(wd, v.x, v.y), b = down_row(wd, v.z, v.w);
        ((uint2*)g_md[0])[r0 + r] = make_uint2(a.x, b.x); ((uint2*)g_md[1])[r0 + r] = make_uint2(a.y, b.y);
        mx0 = __vimax3_u16x2(mx0, a.x & 0x7fff7fffu, b.x & 0x7fff7fffu); mx1 = __vimax3_u16x2(mx1, a.y & 0x7fff7fffu, b.y & 0x7fff7fffu);
        ss[0] += bf_lo(a.x) * bf_lo(a.x) + bf_lo(b.x) * bf_lo(b.x); ss[1] += bf_hi(a.x) * bf_hi(a.x) + bf_hi(b.x) * bf_hi(b.x);
        ss[2] += bf_lo(a.y) * bf_lo(a.y) + bf_lo(b.y) * bf_lo(b.y); ss[3] += bf_hi(a.y) * bf_hi(a.y) + bf_hi(b.y) * bf_hi(b.y);
    }
    uint32_t st[4] = {mx0 << 16, mx0 & 0xffff0000u, mx1 << 16, mx1 & 0xffff0000u};
    uint4* red = (uint4*)(smem + S_PC + PC_ROWS * 8);
    for (int pass = 0; pass < 2; pass++) {
#pragma unroll
        for (int ch = 0; ch < 4; ch++) {
            st[ch] = __reduce_max_sync(0xffffffffu, st[ch]);
#pragma unroll
            for (int o = 16; o; o >>= 1) ss[ch] += __shfl_xor_sync(0xffffffffu, ss[ch], o);
        }
        uint4* dst = pass ? (uint4*)g_ctl.stat[pc] : red + 2 * w;
        if (lane == 0) { dst[0] = make_uint4(st[0], st[1], st[2], st[3]); dst[1] = make_uint4(__float_as_uint(ss[0]), __float_as_uint(ss[1]), __float_as_uint(ss[2]), __float_as_uint(ss[3])); }
        if (pass) break;
        __syncthreads();
        const uint4 a = lane < NW ? red[2 * lane] : make_uint4(0, 0, 0, 0), b = lane < NW ? red[2 * lane + 1] : make_uint4(0, 0, 0, 0);
        __syncthreads();
        if (w != NW - 1) return;
        st[0] = a.x; st[1] = a.y; st[2] = a.z; st[3] = a.w;
        ss[0] = __uint_as_float(b.x); ss[1] = __uint_as_float(b.y); ss[2] = __uint_as_float(b.z); ss[3] = __uint_as_float(b.w);
    }
    if (lane == 0) { fence_release(); red_add(&g_ctl.pieces_done, 1); }
    __syncwarp();
}

__device__ __forceinline__ void get_scales(const Prm& p, float sc[4], bool& bad) {
    const int lane = threadIdx.x & 31;
    uint32_t mxb[4] = {0, 0, 0, 0};
    float ss[4] = {0.f, 0.f, 0.f, 0.f};
#pragma unroll
    for (int k = 0; k < (NPC + 31) / 32; k++) {
        if (lane + 32 * k < NPC) {
            const uint4 a = ld_relaxed4(&g_ctl.stat[lane + 32 * k][0]), b = ld_relaxed4(&g_ctl.stat[lane + 32 * k][4]);
            mxb[0] = max(mxb[0], a.x); mxb[1] = max(mxb[1], a.y); mxb[2] = max(mxb[2], a.z); mxb[3] = max(mxb[3], a.w);
            ss[0] += __uint_as_float(b.x); ss[1] += __uint_as_float(b.y); ss[2] += __uint_as_float(b.z); ss[3] += __uint_as_float(b.w);
        }
    }
    bad = false;
    const float kdeg = fminf(3.5f * sqrtf(fmaxf(0.5f * (float)p.T / (float)p.E, 1.0f)), 128.f);
#pragma unroll
    for (int ch = 0; ch < 4; ch++) {
        float mx = __uint_as_float(__reduce_max_sync(0xffffffffu, mxb[ch]));
#pragma unroll
        for (int o = 16; o; o >>= 1) ss[ch] += __shfl_xor_sync(0xffffffffu, ss[ch], o);
        float rms = sqrtf(ss[ch] / (float)p.E);
        float range = fmaxf(4.002f * mx, kdeg * rms);
        if (!(mx <= 1e15f) || !(range <= 128.f * rms) || (mx > 0.f && mx < 1e-15f)) bad = true;
        sc[ch] = range > 0.f ? 32767.f / range : 0.f;
    }
}

constexpr int PER = 40;
__host__ __device__ constexpr uint32_t bar_done(uint32_t s) { return SB + P_BAR + (s % NBUF) * 16; }
__host__ __device__ constexpr uint32_t bar_free(uint32_t m) { return bar_done(m + NBUF - (GR - 1)) + 8; }
struct __align__(16) PTab { uint32_t e[PER][4]; };
constexpr PTab make_ptab() {
    PTab t = {};
    for (int s = 0; s < PER; s++) {
        for (int d = 0; d < GR; d++) {
            int gi = (s + d) % GR, buf = (s + d) % NBUF, X = gi & 1, g = gi >> 1;
            t.e[s][X] |= (uint32_t)(4 * UN * buf - g - 4 * X + 7) << (8 * g);
        }
        t.e[s][2] = bar_done(s);
        t.e[s][3] = (((s + GR - 1) / NBUF) & 1) ^ 1;
    }
    return t;
}
__constant__ PTab c_ptab = make_ptab();
constexpr int BIAS = 7 * NCP;
static_assert(NG == 4 && CPS >= FW, "group selection");

struct PCtx { uint32_t a0, a1; };
struct PElem { uint32_t b4, aw, ol, r2; };

__device__ __forceinline__ void p_bin(const PCtx& c, PElem& e, uint32_t i, uint32_t o) {
    uint32_t ib = __umulhi(i, MAG_I), ob = __umulhi(o, MAG_O), sel = ib & 3;
    asm("{.reg .pred p; setp.ge.u32 p, %1, %2; @p add.u32 %0, %0, 4;}" : "+r"(sel) : "r"(o), "n"(HALF_O));
    e.b4 = __dp4a(prmt(c.a0, c.a1, sel), (uint32_t)NCP, ib * NCP + ob * 4);
    e.aw = i - ib * ROWS_I;
    e.ol = o - ob * ROWS_O;
}
__device__ __forceinline__ void p_rank(PElem& e) {
    asm volatile("atom.shared.add.u32 %0, [%1+%2], 2;" : "=r"(e.r2) : "r"(e.b4), "n"(SB + P_CNT - BIAS) : "memory");
}
__device__ __forceinline__ void p_store(const PElem& e) {
    const uint32_t ab = e.b4 * (KS / 2) + e.r2;
    asm volatile("{.reg .pred p; setp.lt.u32 p, %4, %5; @p st.shared.u32 [%0+%6], %1; @p st.shared.u16 [%2+%7], %3;}"
                 ::"r"(ab * 2), "r"(e.aw), "r"(ab), "h"((uint16_t)e.ol), "r"(e.r2), "n"(KS * 2),
                   "n"(SB + P_A - BIAS * KS), "n"(SB + P_B - BIAS * (KS / 2)) : "memory");
}
__device__ __forceinline__ uint32_t cos2(uint32_t x) {
    x = __vminu2(x, 0x42804280u);
    return pack_bf16(__cosf(bf_hi(x)), __cosf(bf_lo(x)));
}

#define PD_ 2
#define CB_ 8
constexpr int CB = CB_;
struct PIn { uint4 i, o; uint2 a; };

struct PFill {
    PCtx c;
    uint32_t qb, qt, lt, f2, bar, par, xmax;
    uint32_t s0, lane, vb;
    bool open;
    __device__ __forceinline__ void fetch(const Prm& p, PIn& x, uint32_t ch) {
        const int v = ((ch & ~(CB - 1u)) * (NP - 1) + ch) * 32 + vb;
        asm volatile("{.reg .b32 d0, d1; tex.1d.v4.u32.s32 {%0,%1,d0,d1}, [%2, {%3}];}" : "=r"(x.a.x), "=r"(x.a.y) : "l"(p.t_ang), "r"(v));
        asm volatile("tex.1d.v4.u32.s32 {%0,%1,%2,%3}, [%4, {%5}];" : "=r"(x.i.x), "=r"(x.i.y), "=r"(x.i.z), "=r"(x.i.w) : "l"(p.t_in), "r"(v));
        asm volatile("tex.1d.v4.u32.s32 {%0,%1,%2,%3}, [%4, {%5}];" : "=r"(x.o.x), "=r"(x.o.y), "=r"(x.o.z), "=r"(x.o.w) : "l"(p.t_out), "r"(v));
    }
    __device__ __forceinline__ uint32_t ticket(uint32_t zero) {
        uint32_t t;
        asm volatile("atom.shared.add.u32 %0, [%1+%2], %3;" : "=r"(t) : "r"(lane * 4), "n"(SB + P_TKT), "r"((~lt & 1) | zero) : "memory");
        return t;
    }
    __device__ __forceinline__ uint32_t use_ticket(uint32_t t) {
        t = __reduce_or_sync(0xffffffffu, t);
        begin(t / CPS);
        return t + PD_ * FW;
    }
    __device__ __forceinline__ void begin(uint32_t step) {
        const uint4 t = ((const uint4*)c_ptab.e)[(step + s0) % PER];
        c.a0 = t.x; c.a1 = t.y; bar = t.z; par = t.w;
        open = mbar_test(bar + 8, par);
    }
    __device__ __forceinline__ void enter() { if (!open) mbar_wait(bar + 8, par); }
    __device__ __forceinline__ void end() {
        __syncwarp();
        asm volatile("{.reg .pred p; setp.eq.u32 p, %1, 0; @p mbarrier.arrive.shared.b64 _, [%0];}" ::"r"(bar), "r"(lt) : "memory");
    }
    __device__ __forceinline__ void push(bool f, uint32_t x, uint32_t y) {
        const uint32_t mask = __ballot_sync(0xffffffffu, f);
        asm volatile("{.reg .pred p; setp.ne.u32 p, %3, 0; @p st.shared.v2.u32 [%0], {%1,%2};}"
                     ::"r"(min(qt + __popc(mask & lt) * 8, qb + (QN - 1) * 8)), "r"(x), "r"(y), "r"((uint32_t)f) : "memory");
        qt += __popc(mask) * 8;
    }
    __device__ __forceinline__ void push3(bool f, uint32_t i, uint32_t o, uint32_t aw) { push(f, prmt(i, aw, 0x6210), prmt(o, aw, 0x7210)); }
    __device__ __forceinline__ uint32_t chunk(const PIn& x) {
        uint32_t x0, x1;
        const uint32_t tk = use_ticket(ticket(x.o.x >> 31));
        PElem e0, e1, e2, e3;
        p_bin(c, e0, x.i.x, x.o.x); p_bin(c, e1, x.i.y, x.o.y); p_bin(c, e2, x.i.z, x.o.z); p_bin(c, e3, x.i.w, x.o.w);
        asm volatile("" : "+r"(e0.b4), "+r"(e1.b4), "+r"(e2.b4), "+r"(e3.b4));
        enter();
        p_rank(e0); p_rank(e1); p_rank(e2); p_rank(e3);
        asm volatile("mul.rn.bf16x2 %0, %1, %2;" : "=r"(x0) : "r"(x.a.x), "r"(f2));
        asm volatile("mul.rn.bf16x2 %0, %1, %2;" : "=r"(x1) : "r"(x.a.y), "r"(f2));
        x0 &= 0x7fff7fffu; x1 &= 0x7fff7fffu;
        xmax = __vimax3_u16x2(xmax, x0, x1);
        const uint32_t c0 = cos2(x0), c1 = cos2(x1);
        e0.aw = prmt(e0.aw, c0, 0x5410); e1.aw = prmt(e1.aw, c0, 0x7610); e2.aw = prmt(e2.aw, c1, 0x5410); e3.aw = prmt(e3.aw, c1, 0x7610);
        p_store(e0); p_store(e1); p_store(e2); p_store(e3);
        if (qt - qb >= QTRIG * 8) retry(32);
        end();
        const uint32_t r01 = e0.r2 | e1.r2, r23 = e2.r2 | e3.r2;
        const bool f = (r01 | r23) >= KS * 2;
        if (__any_sync(0xffffffffu, f)) {
            const bool f0 = e0.r2 >= KS * 2, f1 = e1.r2 >= KS * 2, f2_ = e2.r2 >= KS * 2, f3 = e3.r2 >= KS * 2, f01 = r01 >= KS * 2;
            push3(f, f01 ? (f0 ? x.i.x : x.i.y) : (f2_ ? x.i.z : x.i.w), f01 ? (f0 ? x.o.x : x.o.y) : (f2_ ? x.o.z : x.o.w),
                  f01 ? (f0 ? e0.aw : e1.aw) : (f2_ ? e2.aw : e3.aw));
            const uint32_t s2 = max(max(min(e0.r2, e1.r2), min(e2.r2, e3.r2)), min(r01, r23));
            if (__any_sync(0xffffffffu, s2 >= KS * 2)) {
                push3(f1 && f0, x.i.y, x.o.y, e1.aw); push3(f2_ && f01, x.i.z, x.o.z, e2.aw); push3(f3 && (f01 || f2_), x.i.w, x.o.w, e3.aw);
            }
        }
        return tk;
    }
    __device__ __forceinline__ void retry(uint32_t take) {
        if (qt - qb > QN * 8) { st_relaxed(&g_ctl.bad, 1); qt = qb + QN * 8; }
        uint2 e, r, r1;
        __syncwarp();
        asm volatile("ld.shared.v2.u32 {%0,%1}, [%2];" : "=r"(e.x), "=r"(e.y) : "r"(qb + lane * 8) : "memory");
        asm volatile("ld.shared.v2.u32 {%0,%1}, [%2];" : "=r"(r.x), "=r"(r.y) : "r"(qb + (lane + take) * 8) : "memory");
        qt -= take * 8;
        const bool more = qt - qb > 256;
        if (more) asm volatile("ld.shared.v2.u32 {%0,%1}, [%2];" : "=r"(r1.x), "=r"(r1.y) : "r"(qb + (lane + take) * 8 + 256) : "memory");
        __syncwarp();
        if (more && qb + lane * 8 + 256 < qt) asm volatile("st.shared.v2.u32 [%0], {%1,%2};" ::"r"(qb + lane * 8 + 256), "r"(r1.x), "r"(r1.y) : "memory");
        if (qb + lane * 8 < qt) asm volatile("st.shared.v2.u32 [%0], {%1,%2};" ::"r"(qb + lane * 8), "r"(r.x), "r"(r.y) : "memory");
        PElem el;
        el.r2 = 0;
        if (take == 32 || lane < take) {
            p_bin(c, el, e.x & 0xffffffu, e.y & 0xffffffu);
            el.aw = prmt(el.aw, prmt(e.x, e.y, 0x0073), 0x5410);
            p_rank(el);
            p_store(el);
        }
        push(el.r2 >= KS * 2, e.x, e.y);
    }
};

__device__ __forceinline__ void p_filler(const Prm& p, int q, int w) {
    PFill F;
    const int lane = threadIdx.x & 31;
    const uint32_t NS = p.NS, cend = p.T >> 7, nv = NS * CPS, nc = cend / (NP * CB) * CB + min(max((int)(cend % (NP * CB)) - q * CB, 0), CB);
    static_assert(QN <= 96, "retry moves two batches");
    F.lt = __shfl_sync(0xffffffffu, (1u << lane) - 1u, lane);
    F.lane = __shfl_sync(0xffffffffu, lane, lane);
    F.vb = __shfl_sync(0xffffffffu, q * (32 * CB) + lane, lane);
    F.f2 = __shfl_sync(0xffffffffu, __bfloat16_as_ushort(p.freq[0]) * 0x10001u, 0);
    F.qb = F.qt = SB + P_Q + w * (QN * 8);
    F.s0 = q % GR; F.xmax = 0;
    uint32_t c0 = w, c1 = w + FW;
    PIn x0, x1;
    F.fetch(p, x0, c0);
#pragma unroll 1
    while (c0 < nc) {
        F.fetch(p, x1, c1);
        c0 = F.chunk(x0);
        if (c1 >= nc) break;
        F.fetch(p, x0, c0);
        c1 = F.chunk(x1);
    }
    int left = (c0 < nv) + (c1 < nv);
#pragma unroll 1
    while (left > 0) { left -= F.use_ticket(F.ticket(0)) >= nv; F.enter(); F.end(); }
    if (q == 0 && w < 8) {
        const int t = cend * 128 + w * 16 + lane;
        const bool f = t < p.T && lane < 16;
        uint32_t i = 0, o = 0, x = 0;
        if (f) { i = p.idx_in[t]; o = p.idx_out[t]; asm("mul.rn.bf16x2 %0, %1, %2;" : "=r"(x) : "r"(__bfloat16_as_ushort(p.angle[t]) * 0x10001u), "r"(F.f2)); }
        F.xmax = __vmaxu2(F.xmax, x & 0x7fff7fffu);
        if (F.qt - F.qb >= 32 * 8) { F.begin(NS); F.enter(); F.retry(32); }
        F.push3(f, i, o, cos2(x & 0x7fff7fffu));
    }
#pragma unroll 1
    for (uint32_t n = NS; n <= NS + GR; n++) {
        F.begin(n); F.enter();
        for (uint32_t nq = min((F.qt - F.qb) >> 3, (uint32_t)QN); nq > 0;) { uint32_t take = min(nq, 32u); F.retry(take); nq -= take; }
        F.end();
        if (CPS > FW && w < CPS - FW) F.end();
    }
    if (F.qt != F.qb || ((F.xmax + 0x3d803d80u) & 0x80008000u)) st_relaxed(&g_ctl.bad, 1);
}

template <int N> __device__ __forceinline__ void p_stamp(const uint32_t (&st)[N], uint32_t off, uint32_t bit, bool set) {
    if (set) {
#pragma unroll
        for (int j = 0; j < N; j++) asm volatile("red.shared.or.b32 [%0], %1;" ::"r"(st[j] + off), "r"(bit) : "memory");
    } else {
#pragma unroll
        for (int j = 0; j < N; j++) asm volatile("red.shared.and.b32 [%0], %1;" ::"r"(st[j] + off), "r"(~bit) : "memory");
    }
}
__device__ __forceinline__ void bulk_store(void* dst, uint32_t src, uint32_t bytes) {
    asm volatile("cp.async.bulk.global.shared::cta.bulk_group [%0], [%1], %2;" ::"l"(dst), "r"(src), "r"(bytes) : "memory");
}
#define ROUNDS_ 1
__device__ __forceinline__ void p_flusher(const Prm& p, unsigned char* ring, uint32_t pagebits, int q, int f) {
    const int lane = threadIdx.x & 31;
    const uint32_t NS = p.NS, NT = NS + 2 * GR, s0 = q % GR;
    uint32_t sta[5], stb[7];
#pragma unroll
    for (int j = 0; j < 7; j++) {
        const int bin = min(8 * j + (lane >> 2), NB - 1);
        const int ps = j < 4 ? 4 * (j >> 1) + (lane >> 3) : 8, l = j < 4 ? 2 * (j & 1) + ((lane >> 2) & 1) : (lane >> 2) & 3;
        stb[j] = SB + P_B + bin * 128 + (lane & 3) * 32 + ((bin % NCP) & 3) * 8;
        if (j < 5) sta[j] = SB + P_A + ps * 512 + l * 128 + (l & 1) * 16 + (lane & 3) * 32 + (ps & 3) * 4;
    }
    const uint32_t pfo = OFF_PF + (lane / 6) * 32 + (lane & 1) * 16 + ((lane % 6) >> 1) * 4, pfc = (lane >> 1) * 6 + (lane & 1);
    const uint32_t wto = lane < NCP ? OFF_REL + lane * 4 : OFF_RDY + (lane % 6) * 4;
    PROF_DECL
#pragma unroll 1
    for (uint32_t n = f; n < NT; n += NF) {
        const uint32_t buf = (n + s0) % NBUF, h = n >> 1, lap = h / RB;
        const uint32_t qb = q_base(q, pagebits) ^ (((n + q) & 1) << 12), bb = qb ^ slot_off(h % RB);
        if (h >= RA && !DEV_FREE) {
            const uint32_t hw = lane < NCP ? h : h + RB - RA;
            wait_all_ge(ring + (qb ^ slot_off(hw % RB) ^ wto), (hw / RB) << (lane < NCP ? 0 : 1));
        }
        PROF(0);
#pragma unroll
        for (int d = 2; d >= 0; d--) {
            const int nl = (int)min(n, NS + GR) - d;
            if (nl >= 0) mbar_wait(bar_done(nl + s0), ((nl + s0) / NBUF) & 1);
        }
        PROF(1);
        uint32_t* cnt = (uint32_t*)(smem + P_CNT) + buf * NB;
        bool any = true;
        if (n >= NS) any = __any_sync(0xffffffffu, lane < NCP && (cnt[lane] | cnt[NCP + lane] | cnt[2 * NCP + lane]));
        if (any) {
            const uint32_t oa = buf * (NB * KS * 4), ob = buf * (NB * KS * 2);
            unsigned char* da = ring + (qb ^ slot_off(h % RA) ^ R_A);
            unsigned char* db = ring + (bb ^ R_B);
            int sent = 0;
#pragma unroll
            for (int u = 0; u <= UN; u++) {
                if (u < UN) p_stamp(sta, oa + u * (NCP * KS * 4), 0x40000000u, (h / RA) & 1);
                else p_stamp(stb, ob, 0x8000u, lap & 1);
                if (u == UN || (ROUNDS_ >= 2 && u == 0) || (ROUNDS_ >= 3 && u == 2)) {
                    __syncwarp();
                    if (elect_one()) {
                        asm volatile("fence.proxy.async.shared::cta;" ::: "memory");
#pragma unroll
                        for (int v = sent; v <= u; v++) {
                            if (v < UN) {
                                bulk_store(da + v * R_UNIT, SB + P_A + oa + v * (NCP * KS * 4), 8 * KS * 4);
                                bulk_store(da + v * R_UNIT + 0x40000, SB + P_A + oa + (v * NCP + 8) * (KS * 4), (NCP - 8) * KS * 4);
                            } else {
#pragma unroll
                                for (int k = 0; k < UN; k++) bulk_store(db + k * R_UNIT, SB + P_B + ob + k * (NCP * KS * 2), NCP * KS * 2);
                            }
                        }
                    }
                    __syncwarp();
                    sent = u + 1;
                }
            }
        }
        uint32_t wm = ((lap + 1) << 22) | ((uint32_t)any << 21);
        if (lane < NCP) {
#pragma unroll
            for (int u = 0; u < 3; u++) wm |= min(cnt[pfc + 2 * u] >> 1, (uint32_t)KS) << (7 * u);
        }
        __syncwarp();
        if (lane < NB / 2) ((uint2*)cnt)[lane] = make_uint2(0, 0);
        PROF(3);
        asm volatile("cp.async.bulk.commit_group;" ::: "memory");
        asm volatile("cp.async.bulk.wait_group 0;" ::: "memory");
        __syncwarp();
        PROF(2);
        const bool safe = h < RB || n >= NS;
        if (!safe && lane < NCP) st_relaxed(ring + (bb ^ pfo), wm);
        if (n > 0) mbar_wait(bar_free(n - 1 + s0), ((n - 1 + s0) / NBUF) & 1);
        if (lane == 0) mbar_arrive(bar_free(buf));
        if (safe) {
            if (any) fence_release();
            if (lane < NCP) st_relaxed(ring + (bb ^ pfo), wm);
        }
        PROF(4);
    }
    PROF_END;
}
__device__ __forceinline__ void p_cleanup(unsigned char* ring, int q) {
    const int k = threadIdx.x / 24;
    if (k < 2 * RB) *(uint4*)(ring + ((q << 20) ^ ((k & 1) << 12) ^ slot_off(k >> 1) ^ OFF_PF) + (threadIdx.x % 24) * 16) = make_uint4(0, 0, 0, 0);
}

__device__ __forceinline__ void m_role(const Prm& p, unsigned char* ring, int X, int id) {
    const int tid = threadIdx.x, lane = tid & 31, w = __shfl_sync(0xffffffffu, tid >> 5, 0);
    const int ib = id >> 1, ty = id & 1;
    float* scs = (float*)(smem + S_MISC);
    if (w == 0) {
        const uint32_t bar = SB + S_AUX;
        if (lane == 0) mbar_init(bar, 1);
        wait_ge(&g_ctl.pieces_done, NPC);
        fence_acquire();
        if (lane == 0) {
            asm volatile("fence.proxy.async.global;" ::: "memory");
            asm volatile("fence.proxy.async.shared::cta;" ::: "memory");
            asm volatile("mbarrier.arrive.expect_tx.shared.b64 _, [%0], %1;" ::"r"(bar), "r"(ROWS_I * 4) : "memory");
            constexpr uint32_t PART = (ROWS_I * 4 / 8 + 127) / 128 * 128;
            for (uint32_t o = 0; o < ROWS_I * 4; o += PART)
                asm volatile("cp.async.bulk.shared::cluster.global.mbarrier::complete_tx::bytes [%0], [%1], %2, [%3];"
                             ::"r"(SB + o), "l"((const char*)(g_md[ty] + ib * ROWS_I) + o), "r"(min(PART, ROWS_I * 4 - o)), "r"(bar) : "memory");
        }
        __syncwarp();
            float sc[4]; bool bad;
        get_scales(p, sc, bad);
            if (bad) { st_relaxed(&g_ctl.bad, 1); sc[0] = sc[1] = sc[2] = sc[3] = 0.f; }
        int it = 0; uint32_t pb;
        while (!((pb = ld_relaxed(&g_ctl.pagebits)) >> 31)) backoff(it);
        if (lane == 0) { scs[0] = sc[0]; scs[1] = sc[1]; scs[2] = sc[2]; scs[3] = sc[3]; ((uint32_t*)scs)[4] = X ? ~pb : pb; ((uint32_t*)scs)[5] = bad; }
        mbar_wait(bar, 0);
    }
    __syncthreads();
    if (((uint32_t*)scs)[5]) {
        for (int k = tid; k < (int)ROWS_I; k += THREADS) ((uint32_t*)smem)[k] = 0;
        __syncthreads();
    }
    const uint32_t NT = p.NS + 2 * GR;
    if (w >= MW) return;
    const uint32_t pagebits = ((uint32_t*)scs)[4];
    const int half = lane >> 4, k4 = (lane & 15) * 4;
    const float s_lo = scs[2 * ty], s_hi = scs[2 * ty + 1];
    const float MAG_LO = 12582912.f, MAG_HI = 12582912.f - 19264.f;
    const int il = ib / NG, gi = (ib % NG) * 2 + X;
    const uint32_t a_off = R_A + il * R_UNIT + lane * 16, v_off = ty * R_V1 + il * R_UNIT + lane * 16;
    const uint32_t f_off = OFF_PF + il * 32 + half * 16, r_off = OFF_REL + (lane % NCP) * 4;
    const uint32_t j = w % (NP / GR);
    PROF_DECL
#pragma unroll 1
    for (uint32_t n = w / (NP / GR); n < NT; n += MW / (NP / GR)) {
        const uint32_t q = ((gi - n) & (GR - 1)) + GR * j, h = n >> 1;
        const uint32_t qb = q_base(q, pagebits), bb = qb ^ slot_off(h % RB);
        const uint32_t tag = (h / RB + 1) << 22;
        uint4 cw; int it = 0;
        while (true) {
            cw = ld_relaxed4(ring + (bb ^ f_off));
            if (__all_sync(0xffffffffu, min(min(cw.x, cw.y), cw.z) >= tag)) break;
            if (DEV_FREE) { cw.x = (cw.x & 1) + (63 | 57 << 7 | 50 << 14 | 1 << 21); cw.y = (cw.y & 1) + (53 | 61 << 7 | 57 << 14); cw.z = (cw.z & 1) + (59 | 52 << 7 | 57 << 14); break; }
            backoff(it);
        }
        PROF(0);
        if (__any_sync(0xffffffffu, cw.x & (1u << 21))) {
            const unsigned char* pa = ring + (qb ^ slot_off(h % RA) ^ a_off);
            unsigned char* pv = ring + (qb ^ slot_off(h % RV) ^ v_off);
            const uint32_t hv = h + RB - RV;
            const unsigned char* prel = ring + (qb ^ slot_off(hv % RB) ^ r_off);
            const uint32_t rel = ld_relaxed(prel);
            const uint32_t vlap = h / RV;
            const float mag_lo0 = MAG_LO + (float)(8192 + (vlap & 3) * 16384), mag_hi0 = MAG_HI + (float)(8192 + ((vlap >> 2) & 3) * 16384);
            const uint32_t stamp = ((h / RA) & ~(lane ^ (lane >> 3)) & 1) << 30;
            uint4 a[9];
#define M_LOAD(ps) a[ps] = ld_relaxed4(pa + (ps) * 512 + ((ps) < 4 ? 0 : R_HI))
#pragma unroll
            for (int ps = 0; ps < MPF; ps++) M_LOAD(ps);
            if (!__all_sync(0xffffffffu, rel >= hv / RB) && !DEV_FREE) wait_all_ge(prel, hv / RB);
            PROF(3);
#pragma unroll
            for (int ps = 0; ps < 9; ps++) {
                const int rem = (int)(((ps < 3 ? cw.x : ps < 6 ? cw.y : cw.z) >> (7 * (ps % 3))) & 0x7f) - k4;
                if (ps % 3 == 0) {
#define M_STAMP(ps) (((ps) & 3) == 0 ? a[ps].x : ((ps) & 3) == 1 ? a[ps].y : ((ps) & 3) == 2 ? a[ps].z : a[ps].w)
                    while (true) {
                        M_STAMP(ps) ^= stamp; M_STAMP(ps + 1) ^= stamp; M_STAMP(ps + 2) ^= stamp;
                        if (!__any_sync(0xffffffffu, (M_STAMP(ps) | M_STAMP(ps + 1) | M_STAMP(ps + 2)) & 0x40000000u)) break;
                        if (DEV_FREE) { M_STAMP(ps) &= 0xbfffffffu; M_STAMP(ps + 1) &= 0xbfffffffu; M_STAMP(ps + 2) &= 0xbfffffffu; break; }
                        if (++it > SPIN_MAX) __trap();
                        M_LOAD(ps); M_LOAD(ps + 1); M_LOAD(ps + 2);
                    }
                }
                uint32_t aw[4] = {a[ps].x, a[ps].y, a[ps].z, a[ps].w}, mv[4], vw[4];
#pragma unroll
                for (int e = 0; e < 4; e++) { mv[e] = 0; lds_lt(mv[e], __dp2a_lo(aw[e], 4u, (uint32_t)SB), e, rem); }
#pragma unroll
                for (int e = 0; e < 4; e++) {
                    float c = bf_hi(aw[e]);
                    float lo = fmaf(bf_lo(mv[e]), c * s_lo, e ? MAG_LO : mag_lo0), hi = fmaf(bf_hi(mv[e]), c * s_hi, e ? MAG_HI : mag_hi0);
                    vw[e] = (__float_as_uint(hi) << 16) + __float_as_uint(lo);
                }
                asm volatile("st.global.v4.u32 [%0], {%1,%2,%3,%4};" ::"l"(pv + ps * 512 + (ps < 4 ? 0 : R_HI)), "r"(vw[0]), "r"(vw[1]), "r"(vw[2]), "r"(vw[3]) : "memory");
                if (ps + MPF < 9) M_LOAD(ps + MPF);
            }
            if (vlap == 0 || n >= p.NS) fence_release();
        }
        st_lane0(ring + (bb ^ (OFF_RDY + (2 * il + ty) * 4)), cw.x >> 21, lane);
        PROF(1);
    }
    PROF_END;
}

__device__ __noinline__ void c_wrap(uint32_t row, int par, uint32_t old, uint32_t w) {
    const uint32_t nw = old + w, ov = ~(old ^ w) & (old ^ nw);
    int d = 0;
    if (ov & 0x8000u) d += (w & 0x8000u) ? -1 : 1;
    if (ov & 0x80000000u) d += (w & 0x80000000u) ? -16 : 16;
    if (d != 0) {
        uint32_t c;
        asm volatile("atom.shared.add.u32 %0, [%1], %2;" : "=r"(c) : "r"(SB + C_WRAP + row * 4), "r"(d << (8 * par)) : "memory");
        c = (c >> (8 * par)) + d;
        if (((c + 1) & 0xe) == 0 || ((c + 16) & 0xe0) == 0) st_relaxed(&g_ctl.bad, 1);
    }
}

#define CGRP 4
struct CTask { uint4 v[3]; uint2 b[3]; };
struct CWork {
    unsigned char* ring;
    uint32_t v_off, b_off, f_off, r_off, acc;
    uint32_t lap1, sv, sb, vtag, fw, stamp;
    int lane, dev_free;
    template <int ODD> __device__ __forceinline__ bool issue(CTask& t) {
        if (!__all_sync(0xffffffffu, fw >= 2 * lap1)) {
            int it = 0;
            do {
                if (dev_free) { fw = 1; break; }
                backoff(it);
                fw = ld_relaxed(ring + (f_off ^ slot_off(sb) ^ (ODD << 20)));
            } while (!__all_sync(0xffffffffu, fw >= 2 * lap1));
        }
        const bool data = __any_sync(0xffffffffu, fw & 1);
        if (data) {
            const unsigned char* pv = ring + (v_off ^ slot_off(sv) ^ (ODD << 20));
            const unsigned char* pb = ring + (b_off ^ slot_off(sb) ^ (ODD << 20));
#pragma unroll
            for (int ps = 0; ps < 3; ps++) {
                t.v[ps] = ld_relaxed4(pv + ps * R_UNIT);
                t.b[ps] = ld_relaxed2(pb + ps * R_UNIT);
            }
        }
        fw = ld_relaxed(ring + (f_off ^ slot_off(ODD ? (sb + 1 == RB ? 0 : sb + 1) : sb) ^ (!ODD << 20)));
        return data;
    }
    template <int ODD> __device__ __forceinline__ void arrive(CTask& t, bool data) {
        if (data) {
            int it = 0;
            while (true) {
#pragma unroll
                for (int ps = 0; ps < 3; ps++) t.b[ps].x ^= stamp;
                if (!__any_sync(0xffffffffu, (((t.v[0].x ^ vtag) | (t.v[1].x ^ vtag) | (t.v[2].x ^ vtag)) & 0xc000c000u) | ((t.b[0].x | t.b[1].x | t.b[2].x) & 0x8000u))) break;
                if (dev_free) { for (int ps = 0; ps < 3; ps++) { t.v[ps].x = (t.v[ps].x & 0x3fff3fffu) | (vtag & 0xc000c000u); t.b[ps].x &= 0xffff7fffu; } break; }
                if (++it > SPIN_MAX) __trap();
#pragma unroll
                for (int ps = 0; ps < 3; ps++) {
                    t.v[ps] = ld_relaxed4(ring + (v_off ^ slot_off(sv) ^ (ODD << 20)) + ps * R_UNIT);
                    t.b[ps] = ld_relaxed2(ring + (b_off ^ slot_off(sb) ^ (ODD << 20)) + ps * R_UNIT);
                }
            }
#pragma unroll
            for (int ps = 0; ps < 3; ps++) t.v[ps].x -= vtag;
        }
        st_lane0(ring + (r_off ^ slot_off(sb) ^ (ODD << 20)), lap1, lane);
        if (ODD) {
            if (++sv == RV) { sv = 0; vtag += 0x4000u; if (vtag & 0x10000u) vtag += 0x3fff0000u; }
            if (++sb == RB) { sb = 0; lap1++; stamp ^= (((b_off >> 3) ^ (b_off >> 7)) & 3) == 0 ? 0x8000u : 0u; }
        }
    }
    __device__ __forceinline__ void add(const CTask& t, bool data) {
        if (!data) return;
        const uint32_t vw[12] = {t.v[0].x, t.v[0].y, t.v[0].z, t.v[0].w, t.v[1].x, t.v[1].y, t.v[1].z, t.v[1].w, t.v[2].x, t.v[2].y, t.v[2].z, t.v[2].w};
        const uint32_t bw[6] = {t.b[0].x, t.b[0].y, t.b[1].x, t.b[1].y, t.b[2].x, t.b[2].y};
#pragma unroll
        for (int g = 0; g < 12; g += CGRP) {
            uint32_t old[CGRP], ov = 0;
#pragma unroll
            for (int e = g; e < g + CGRP; e++)
                asm volatile("atom.shared.add.u32 %0, [%1], %2;" : "=r"(old[e - g]) : "r"((e & 1) ? __dp2a_hi(bw[e >> 1], 0x08000008u, acc) : __dp2a_lo(bw[e >> 1], 0x08000008u, acc)), "r"(vw[e]) : "memory");
#pragma unroll
            for (int e = g; e < g + CGRP; e++) ov |= ~(old[e - g] ^ vw[e]) & (old[e - g] ^ (old[e - g] + vw[e]));
            if (__any_sync(0xffffffffu, ov & 0x80008000u)) {
#pragma unroll
                for (int e = g; e < g + CGRP; e++) c_wrap((e & 1) ? bw[e >> 1] >> 16 : bw[e >> 1] & 0xffffu, lane >> 4, old[e - g], vw[e]);
            }
        }
    }
};

__device__ __forceinline__ void c_role(const Prm& p, unsigned char* ring, int X, int c) {
    const int tid = threadIdx.x, lane = tid & 31, w = __shfl_sync(0xffffffffu, tid >> 5, 0);
    uint32_t* misc = (uint32_t*)(smem + S_MISC);
    Wts* wt = (Wts*)(smem + S_AUX);
    load_wts(p, wt);
    if (tid == 0) misc[6] = TAB_N;
    __syncthreads();
    if (w == 0) {
        float sc[4]; bool bad;
        wait_ge(&g_ctl.pieces_done, NPC);
        fence_acquire();
        get_scales(p, sc, bad);
        const float s = (lane & 2) ? ((lane & 1) ? sc[3] : sc[2]) : ((lane & 1) ? sc[1] : sc[0]);
        wt->ws[lane] *= s > 0.f ? 1.f / s : 0.f;
        int it = 0; uint32_t pb;
        while (!((pb = ld_relaxed(&g_ctl.pagebits)) >> 31)) backoff(it);
        misc[4] = X ? ~pb : pb;
    } else {
        const int r0 = (X * NCP + c) * ROWS_O, nr = min((int)ROWS_O, p.E - r0);
#pragma unroll 4
        for (int r = tid - 32; r < (int)ROWS_O / 2; r += THREADS - 32) {
            const uint32_t d2 = 2 * r < nr ? __ldg((const uint32_t*)(p.dist + r0) + r) : TAB_LO * 0x10001u;
            uint32_t e[2] = {(d2 & 0xffff) - TAB_LO, (d2 >> 16) - TAB_LO};
#pragma unroll
            for (int k = 0; k < 2; k++)
                if (e[k] >= TAB_N) {
                    const uint32_t d = e[k] + TAB_LO;
                    if ((d & 0x7f80) == 0x7f80) st_relaxed(&g_ctl.bad, 1);
                    e[k] = min(atomicAdd(&misc[6], 1u), 0xffffu);
                    if (e[k] < TAB_N + TAB_X) ((uint32_t*)(smem + C_TAB))[e[k] * 4] = d;
                }
            ((uint2*)(smem + C_WRAP))[r] = make_uint2(e[0] << 16 | 0x8888u, e[1] << 16 | 0x8888u);
        }
    }
    __syncthreads();
    if (w >= NP / 2) {
        const int nt = min(misc[6], (uint32_t)(TAB_N + TAB_X));
        for (int k = tid - NP * 16; k < nt; k += THREADS - NP * 16)
            ((uint4*)(smem + C_TAB))[k] = radial_bf16(wt, k < TAB_N ? TAB_LO + k : ((uint32_t*)(smem + C_TAB))[k * 4]);
        if (tid == THREADS - 1 && !DEV_FREE) {
            const uint32_t h = p.NS >> 1;
            const unsigned char* f = ring + (q_base(X, misc[4]) ^ slot_off(h % RB) ^ (OFF_REL + c * 4));
            for (int it = 0; ld_relaxed(f) < h / RB; it++) { __nanosleep(2000); if (it > SPIN_MAX) __trap(); }
            const int r0 = (X * NCP + c) * ROWS_O, nr = min((int)ROWS_O, p.E - r0);
            if (nr > 0) asm volatile("cp.async.bulk.prefetch.L2.global [%0], %1;" ::"l"(p.m + r0), "r"(nr * 8) : "memory");
        }
    }
    const uint32_t pagebits = misc[4];
    if (w >= NP / 2) return;
    CWork W;
    const int par = lane >> 4;
    W.ring = ring; W.lane = __shfl_sync(0xffffffffu, lane, lane); W.dev_free = DEV_FREE;
    const uint32_t qb = q_base(2 * w + X, pagebits), k = lane & 15;
    W.acc = __shfl_sync(0xffffffffu, SB + par * 4, lane);
    W.v_off = __shfl_sync(0xffffffffu, qb ^ (par * R_V1 + (c < 8 ? 0 : R_HI) + c * 256 + k * 16), lane);
    W.b_off = __shfl_sync(0xffffffffu, qb ^ (R_B + c * 128 + k * 8), lane);
    W.f_off = __shfl_sync(0xffffffffu, qb ^ (OFF_RDY + (lane % 6) * 4), lane);
    W.r_off = qb ^ (OFF_REL + c * 4);
    W.lap1 = 1; W.sv = W.sb = W.fw = W.stamp = 0; W.vtag = 0x20002000u;
    const uint32_t NT = p.NS + 2 * GR;
    CTask A, B;
    PROF_DECL
    bool da = W.issue<0>(A), db;
#pragma unroll 1
    for (uint32_t n = 2;; n += 2) {
        W.arrive<0>(A, da); PROF(1); db = W.issue<1>(B); PROF(0); W.add(A, da);
        W.arrive<1>(B, db);
        if (n >= NT) break;
        PROF(1); da = W.issue<0>(A); PROF(0); W.add(B, db);
    }
    W.add(B, db);
    PROF_END;
}

__device__ __forceinline__ uint32_t bf2_mul(uint32_t a, uint32_t b) { uint32_t r; asm("mul.rn.bf16x2 %0, %1, %2;" : "=r"(r) : "r"(a), "r"(b)); return r; }
__device__ __forceinline__ uint32_t bf2_fma(uint32_t a, uint32_t b, uint32_t c) { uint32_t r; asm("fma.rn.bf16x2 %0, %1, %2, %3;" : "=r"(r) : "r"(a), "r"(b), "r"(c)); return r; }
__device__ __forceinline__ uint32_t c_agg(uint32_t a, uint32_t s, uint32_t wr, bool wrapped) {
    int x0 = (short)a, x1 = ((int)a >> 16) + ((a >> 15) & 1);
    if (wrapped) { const int w0 = (int)(wr & 15) - 8, w1 = (int)((wr >> 4) & 15) - 8; x0 += 65536 * w0; x1 += 65536 * w1 - w0; }
    return pack_bf16((float)x1 * bf_hi(s), (float)x0 * bf_lo(s));
}
__device__ __forceinline__ void c_epilogue(const Prm& p, int X, int c) {
    const int tid = threadIdx.x, lane = tid & 31;
    const Wts* wt = (const Wts*)(smem + S_AUX);
    uint32_t bw[4];
#pragma unroll
    for (int k = 0; k < 4; k++) {
        const int col = (k >> 1) * 2 + ((lane >> 2) & 1), row = (k & 1) * 2;
        bw[k] = (lane >> 3) == (lane & 3) ? pack_bf16(wt->wu[(row + 1) * 4 + col], wt->wu[row * 4 + col]) : 0u;
    }
    const int r0 = (X * NCP + c) * ROWS_O, np = max(min((int)ROWS_O, p.E - r0), 0) / 2;
    const uint4* mp = (const uint4*)(p.m + r0);
    uint4* op = (uint4*)(p.out + r0);
    constexpr int EB = 5;
#pragma unroll 1
    for (int rb = tid; rb - lane < np; rb += EB * THREADS) {
        uint4 mr[EB];
#pragma unroll
        for (int k = 0; k < EB; k++) mr[k] = __ldg(mp + min(rb + k * THREADS, np - 1));
#pragma unroll
        for (int k = 0; k < EB; k++) {
            const int r = min(rb + k * THREADS, np - 1);
            const uint4 a = ((const uint4*)smem)[r];
            const uint2 wr = ((const uint2*)(smem + C_WRAP))[r];
            const uint4 t0 = ((const uint4*)(smem + C_TAB))[min(wr.x >> 16, (uint32_t)(TAB_N + TAB_X - 1))];
            const uint4 t1 = ((const uint4*)(smem + C_TAB))[min(wr.y >> 16, (uint32_t)(TAB_N + TAB_X - 1))];
            const bool wrapped = __any_sync(0xffffffffu, prmt(wr.x, wr.y, 0x5410) != 0x88888888u);
            uint32_t a0, a1, a2, a3;
            if (wrapped) { a0 = c_agg(a.x, t0.x, wr.x, true); a2 = c_agg(a.y, t0.y, wr.x >> 8, true); a1 = c_agg(a.z, t1.x, wr.y, true); a3 = c_agg(a.w, t1.y, wr.y >> 8, true); }
            else { a0 = c_agg(a.x, t0.x, 0, false); a2 = c_agg(a.y, t0.y, 0, false); a1 = c_agg(a.z, t1.x, 0, false); a3 = c_agg(a.w, t1.y, 0, false); }
            float u[8];
#pragma unroll
            for (int h = 0; h < 2; h++)
                asm("mma.sync.aligned.m16n8k16.row.col.f32.bf16.bf16.f32 {%0,%1,%2,%3}, {%4,%5,%6,%7}, {%8,%9}, {%10,%10,%10,%10};"
                    : "=f"(u[4 * h]), "=f"(u[4 * h + 1]), "=f"(u[4 * h + 2]), "=f"(u[4 * h + 3])
                    : "r"(a0), "r"(a1), "r"(a2), "r"(a3), "r"(bw[2 * h]), "r"(bw[2 * h + 1]), "f"(0.f));
            const uint4 o = make_uint4(bf2_fma(pack_bf16(u[1], u[0]), t0.z, mr[k].x), bf2_fma(pack_bf16(u[5], u[4]), t0.w, mr[k].y),
                                       bf2_fma(pack_bf16(u[3], u[2]), t1.z, mr[k].z), bf2_fma(pack_bf16(u[7], u[6]), t1.w, mr[k].w));
            if (rb + k * THREADS < np) op[r] = o;
        }
    }
    if (((const uint32_t*)(smem + S_MISC))[6] > TAB_N + TAB_X) {
        for (int r = 2 * tid; r < 2 * np; r += (r & 1) ? 2 * THREADS - 1 : 1) {
            const uint32_t wr = ((const uint32_t*)(smem + C_WRAP))[r];
            if ((wr >> 16) < TAB_N + TAB_X) continue;
            const uint4 t = radial_bf16(wt, __bfloat16_as_ushort(p.dist[r0 + r]));
            const uint2 a = ((const uint2*)smem)[r];
            const uint32_t a0 = c_agg(a.x, t.x, wr, true), a1 = c_agg(a.y, t.y, wr >> 8, true);
            const float agg[4] = {bf_lo(a0), bf_hi(a0), bf_lo(a1), bf_hi(a1)}, g[4] = {bf_lo(t.z), bf_hi(t.z), bf_lo(t.w), bf_hi(t.w)};
            p.out[r0 + r] = finish_row(wt->wu, agg, g, p.m[r0 + r]);
        }
    }
}

__device__ __forceinline__ void grid_bar(unsigned* ctr) {
    __syncthreads();
    if (threadIdx.x == 0) { fence_gpu(); red_add(ctr, 1); wait_ge(ctr, gridDim.x); fence_gpu(); }
    __syncthreads();
}
__device__ __noinline__ void fallback(const Prm& p) {
    const int gt = blockIdx.x * THREADS + threadIdx.x, gs = gridDim.x * THREADS;
    Wts* wt = (Wts*)smem;
    __syncthreads();
    load_wts(p, wt);
    for (int e = gt; e < p.E; e += gs) g_acc[e] = make_float4(0.f, 0.f, 0.f, 0.f);
    grid_bar(&g_ctl.bar[0]);
    const float f = __bfloat162float(p.freq[0]);
    for (int t = gt; t < p.T; t += gs) {
        uint2 r = __ldg(p.m + p.idx_in[t]);
        float c = rbf16(cosf(rbf16(f * __bfloat162float(p.angle[t]))));
        asm volatile("red.global.add.v4.f32 [%0], {%1,%2,%3,%4};" ::"l"(g_acc + p.idx_out[t]), "f"(bf_lo(r.x) * c),
                     "f"(bf_hi(r.x) * c), "f"(bf_lo(r.y) * c), "f"(bf_hi(r.y) * c) : "memory");
    }
    grid_bar(&g_ctl.bar[1]);
    for (int e = gt; e < p.E; e += gs) {
        float4 a4 = __ldcg(g_acc + e);
        float a[4] = {a4.x, a4.y, a4.z, a4.w}, s[4], g[4];
        radial(wt, __bfloat162float(p.dist[e]), s, g);
        float agg[4];
#pragma unroll
        for (int j = 0; j < 4; j++) agg[j] = s[j] * (a[0] * wt->wd[j] + a[1] * wt->wd[4 + j] + a[2] * wt->wd[8 + j] + a[3] * wt->wd[12 + j]);
        p.out[e] = finish_row(wt->wu, agg, g, p.m[e]);
    }
}

__device__ __forceinline__ void smem_init(bool isp, int from, int to) {
    for (int k = from / 16 + threadIdx.x; k < to / 16; k += THREADS) {
        const bool b = isp && k >= P_B / 16 && k < P_Q / 16;
        const uint32_t z = b ? (k & 7) * 0x20002u : 0u, y = b ? z + 0x10001u : 0u;
        ((uint4*)smem)[k] = make_uint4(z, z, y, y);
    }
}

__global__ void __launch_bounds__(THREADS, 1) gemnet_kernel(const __grid_constant__ Prm p) {
    const int tid = threadIdx.x, lane = tid & 31, w = __shfl_sync(0xffffffffu, tid >> 5, 0);
    uint32_t* misc = (uint32_t*)(smem + S_MISC);
    bool run_fallback = true;
    if (!p.force_bad && __cvta_generic_to_shared(smem) == SB) {
        unsigned char* const ring = p.ring;
        uint32_t smid; asm("mov.u32 %0, %%smid;" : "=r"(smid));
        const int cls = smid < NM ? 0 : (smid < NM + NP - 4 || (smid >= 124 && smid < 128)) ? 2 : 1;
        if (lane == 0) {
            if (w < 2 && (cls != 2 || blockIdx.x == 0)) misc[16 + w] = probe(ring + OFF_PROBE + w * 4096 + ((blockIdx.x >> 7) << 20) + (blockIdx.x & 127) * 32);
            else if (blockIdx.x == 0 && w <= NPAGES) misc[16 + w] = probe(ring + ((size_t)(w - 1) << 21) + OFF_PROBE);
        }
        float wd[16];
        if (cls != 2 || blockIdx.x == 0) __syncthreads();
        if (tid == 0) {
            int pool = cls == 2 ? 4 : cls * 2 + (misc[16] > misc[17]), id = 0;
            for (int k = 0; k < 7; k++) {
                int cap = pool < 2 ? NMP : pool < 4 ? NCP : NP;
                id = atomicAdd(&g_ctl.ticket[pool], 1);
                if (id < cap) break;
                pool = k == 0 ? (pool == 4 ? 0 : pool ^ 1) : k - 1;
            }
            misc[8] = pool; misc[9] = id;
            if (pool != 4) down_load(p, pool < 2 ? pool * NMP + id : NM + (pool - 2) * NCP + id);
        }
        if (blockIdx.x == 0 && tid == 32) {
            uint32_t pb = 0x80000000u;
            for (int k = 1; k < NPAGES; k++) pb |= (uint32_t)((2 * misc[17 + k] > misc[16] + misc[17]) != (misc[16] > misc[17])) << k;
            st_relaxed(&g_ctl.pagebits, pb);
        }
#pragma unroll
        for (int k = 0; k < 16; k++) wd[k] = __bfloat162float(p.w_down[k]);
        if (cls == 2) smem_init(true, 0, S_PC);
        __syncthreads();
        const int pool = misc[8], id = misc[9];
        if (pool >= 2 && (pool < 4 || cls != 2)) smem_init(pool == 4, 0, S_PC);
        if (pool != 4) down_piece(p, pool < 2 ? pool * NMP + id : NM + (pool - 2) * NCP + id, wd);
        if (DEV_FREE && !(DEV_FREE & (pool == 4 ? 1 : pool < 2 ? 2 : 4))) {
        } else if (pool == 4) {
            smem_init(true, S_PC, S_MISC);
            __syncthreads();
            if (tid < 2 * NBUF) {
                const uint32_t a = tid < NBUF ? bar_done(tid) : bar_free(tid), cnt = tid < NBUF ? CPS : 1;
                mbar_init(a, cnt);
                if (tid % NBUF < id % GR) asm volatile("mbarrier.arrive.shared.b64 _, [%0], %1;" ::"r"(a), "r"(cnt) : "memory");
            }
            __syncthreads();
            if (w < FW) p_filler(p, id, w);
            else if (w < FW + NF) {
                int it = 0; uint32_t pb;
                while (!((pb = ld_relaxed(&g_ctl.pagebits)) >> 31)) backoff(it);
                p_flusher(p, ring, __shfl_sync(0xffffffffu, pb, 0), id, w - FW);
            }
        } else if (pool < 2) {
            m_role(p, ring, pool, id);
        } else {
            c_role(p, ring, pool - 2, id);
        }
        __syncthreads();
        if (tid == 0) { fence_gpu(); red_add(&g_ctl.fin, 1); }
        if ((pool == 2 || pool == 3) && !DEV_FREE) c_epilogue(p, pool - 2, id);
        if (tid == 0) { wait_ge(&g_ctl.fin, NCTA); fence_gpu(); misc[10] = ld_relaxed(&g_ctl.bad); }
        __syncthreads();
        if (pool == 4) p_cleanup(ring, id);
        run_fallback = misc[10] && !DEV_FREE;
    }
    if (run_fallback) fallback(p);
    if (tid == 0) {
        fence_gpu();
        if (atomicAdd(&g_ctl.exited, 1) == gridDim.x - 1) {
            uint32_t* c = (uint32_t*)&g_ctl;
            for (int k = 0; k < 32; k++) c[k] = 0;
        }
    }
}

cudaTextureObject_t make_tex(const void* ptr, size_t bytes, int words) {
    cudaResourceDesc rd = {};
    rd.resType = cudaResourceTypeLinear;
    rd.res.linear.devPtr = (void*)ptr;
    rd.res.linear.desc = words == 4 ? cudaCreateChannelDesc<uint4>() : cudaCreateChannelDesc<uint2>();
    rd.res.linear.sizeInBytes = bytes;
    cudaTextureDesc td = {};
    td.readMode = cudaReadModeElementType;
    cudaTextureObject_t t = 0;
    if (cudaCreateTextureObject(&t, &rd, &td, nullptr) != cudaSuccess) { cudaGetLastError(); return 0; }
    return t;
}

}

extern "C" void kernel_launch(void* const* d_in, const int* in_sizes, int n_in, void* d_out, int out_size) {
    static Prm p = {};
    static int grid = 0;
    const int E = in_sizes[3], T = in_sizes[1];
    if (grid == 0 || p.idx_in != d_in[1] || p.idx_out != d_in[2] || p.angle != d_in[4] || p.E != E || p.T != T) {
        int dev = 0, sms = 0;
        cudaGetDevice(&dev);
        cudaDeviceGetAttribute(&sms, cudaDevAttrMultiProcessorCount, dev);
        cudaFuncSetAttribute(gemnet_kernel, cudaFuncAttributeMaxDynamicSharedMemorySize, SMEM_BYTES);
        p.E = E; p.T = T;
        p.NS = ((((T / 128 + NP * CB - 1) / (NP * CB)) * CB + CPS - 1) / CPS + 1) & ~1;
        void* rp = nullptr;
        cudaGetSymbolAddress(&rp, g_ring);
        p.ring = (unsigned char*)(((uintptr_t)rp + ((2u << 20) - 1)) & ~(uintptr_t)((2u << 20) - 1));
        bool fast = sms >= NCTA && E <= (int)FAST_E && (E & 1) == 0 && T >= 128 && T <= (1 << 29);
        if (fast) {
            p.t_in = make_tex(d_in[1], (size_t)(T / 128) * 512, 4);
            p.t_out = make_tex(d_in[2], (size_t)(T / 128) * 512, 4);
            p.t_ang = make_tex(d_in[4], (size_t)(T / 128) * 256, 2);
            fast = p.t_in && p.t_out && p.t_ang;
        }
        p.force_bad = !fast;
        grid = fast ? NCTA : sms;
    }
    p.m = (const uint2*)d_in[0];
    p.idx_in = (const int*)d_in[1];
    p.idx_out = (const int*)d_in[2];
    p.dist = (const __nv_bfloat16*)d_in[3];
    p.angle = (const __nv_bfloat16*)d_in[4];
    p.centers = (const __nv_bfloat16*)d_in[5];
    p.freq = (const __nv_bfloat16*)d_in[6];
    p.w_rbf = (const __nv_bfloat16*)d_in[7];
    p.w_sbf = (const __nv_bfloat16*)d_in[8];
    p.w_down = (const __nv_bfloat16*)d_in[9];
    p.w_up = (const __nv_bfloat16*)d_in[10];
    p.out = (uint2*)d_out;
    gemnet_kernel<<<grid, THREADS, SMEM_BYTES>>>(p);
}
```

```cpp
#include <cuda_runtime.h>
#include <cuda_bf16.h>
#include <stdint.h>

namespace {

constexpr int NI = 12;
constexpr int UN = 3;
constexpr int NG = NI / UN;
constexpr int GR = 2 * NG;
constexpr int NCP = 18;
constexpr int NO = 2 * NCP;
constexpr int KS = 64;
constexpr int NB = UN * NCP;
constexpr int NBUF = 10;
constexpr int NMP = 2 * NI;
constexpr int NP = 48, NM = 2 * NMP, NC = NO, NCTA = NP + NM + NC;
#define CPS_ 25
constexpr int CPS = CPS_;
#define FW_ 24
constexpr int FW = FW_;
constexpr int NF = 4;
#define RA_ 3
#define RV_ 3
#define RB_ 4
constexpr int RA = RA_, RV = RV_, RB = RB_;
#define QN_ 96
#define QTRIG_ 48
constexpr int QN = QN_, QTRIG = QTRIG_;
#define MW_ 18
constexpr int MW = MW_;
#define MPF_ 6
constexpr int MPF = MPF_;
constexpr int THREADS = 896, NW = THREADS / 32;
#define DEV_FREE 0
#define SLEEP_ 50

constexpr int RING_BYTES = NP << 20;
constexpr int NPAGES = RING_BYTES >> 21;
constexpr int MAX_E = 1 << 20;
constexpr int SMEM_BYTES = 232448;

constexpr int SB = 1024;

constexpr int P_CNT = 0;
constexpr int P_BAR = P_CNT + NBUF * NB * 4;
constexpr int P_TKT = P_BAR + 2 * NBUF * 8;
constexpr int P_B = (P_TKT + 128 + 127) / 128 * 128;
constexpr int P_Q = P_B + NBUF * NB * KS * 2;
constexpr int P_A = SMEM_BYTES - 256 - NBUF * NB * KS * 4;
static_assert(P_Q + FW * QN * 8 + 512 <= P_A && P_A % 128 == 0, "P smem");
constexpr int S_MISC = SMEM_BYTES - 256;
constexpr int S_AUX = S_MISC - 512;

constexpr unsigned FAST_E = 640000;
constexpr unsigned magic_of(unsigned long long d) { return (unsigned)(((1ull << 32) + d - 1) / d); }
constexpr bool magic_ok(unsigned long long d) { return (magic_of(d) * d - (1ull << 32)) * FAST_E < (1ull << 32); }
constexpr unsigned pick_rows(unsigned lo) {
    unsigned d = (lo + 3) & ~3u;
    while (!magic_ok(d)) d += 4;
    return d;
}
constexpr unsigned ROWS_I = pick_rows((FAST_E + NI - 1) / NI), ROWS_O = pick_rows((FAST_E + NO - 1) / NO);
constexpr unsigned MAG_I = magic_of(ROWS_I), MAG_O = magic_of(ROWS_O), HALF_O = ROWS_O * NCP;
constexpr int C_WRAP = ROWS_O * 8, C_TAB = ROWS_O * 12, TAB_N = 1025, TAB_LO = 0x3f80 - 1024, TAB_X = (S_AUX - C_TAB) / 16 - TAB_N;
static_assert(ROWS_I * 4 <= S_AUX && TAB_X >= 100 && ROWS_I <= 65536 && ROWS_O <= 32768, "tables");

constexpr int NPC = NM + NC;
constexpr int PC_ROWS = ((FAST_E + NPC - 1) / NPC + 3) & ~3;
constexpr int S_PC = C_WRAP + 128 - C_WRAP % 128;
static_assert(S_PC + PC_ROWS * 8 + 1024 <= S_AUX, "pre-pass");
struct __align__(128) Ctl {
    unsigned ticket[5];
    unsigned pagebits;
    unsigned pieces_done, unused;
    unsigned bad;
    unsigned fin;
    unsigned bar[3];
    unsigned exited;
    unsigned pad[18];
    float stat[NPC][8];
};

struct Prm {
    const uint2* m; const int* idx_in; const int* idx_out; const __nv_bfloat16* dist; const __nv_bfloat16* angle;
    const __nv_bfloat16* centers; const __nv_bfloat16* freq; const __nv_bfloat16* w_rbf; const __nv_bfloat16* w_sbf;
    const __nv_bfloat16* w_down; const __nv_bfloat16* w_up; uint2* out;
    cudaTextureObject_t t_in, t_out, t_ang;
    int E, T;
    unsigned char* ring;
    int NS;
    int force_bad;
};

__device__ __align__(128) unsigned char g_ring[RING_BYTES + (2 << 20)];
__device__ Ctl g_ctl;
__device__ float4 g_acc[MAX_E];
__device__ __align__(128) uint32_t g_md[2][NI * ROWS_I];
#define TS(k)
#define PROF_DECL
#define PROF(k)
#define PROF_END

extern __shared__ __align__(128) unsigned char smem[];

__device__ __forceinline__ float bf_lo(uint32_t w) { return __uint_as_float(w << 16); }
__device__ __forceinline__ float bf_hi(uint32_t w) { return __uint_as_float(w & 0xffff0000u); }
__device__ __forceinline__ float rbf16(float x) { return __bfloat162float(__float2bfloat16_rn(x)); }
__device__ __forceinline__ uint32_t pack_bf16(float hi, float lo) {
    uint32_t r; asm("cvt.rn.bf16x2.f32 %0, %1, %2;" : "=r"(r) : "f"(hi), "f"(lo)); return r;
}
__device__ __forceinline__ uint32_t prmt(uint32_t a, uint32_t b, uint32_t c) {
    uint32_t r; asm("prmt.b32 %0, %1, %2, %3;" : "=r"(r) : "r"(a), "r"(b), "r"(c)); return r;
}
__device__ __forceinline__ uint32_t ld_relaxed(const void* p) {
    uint32_t v; asm volatile("ld.relaxed.gpu.global.u32 %0, [%1];" : "=r"(v) : "l"(p) : "memory"); return v;
}
__device__ __forceinline__ uint2 ld_relaxed2(const void* p) {
    uint2 v; asm volatile("ld.relaxed.gpu.global.v2.u32 {%0,%1}, [%2];" : "=r"(v.x), "=r"(v.y) : "l"(p) : "memory"); return v;
}
__device__ __forceinline__ uint4 ld_relaxed4(const void* p) {
    uint4 v; asm volatile("ld.relaxed.gpu.global.v4.u32 {%0,%1,%2,%3}, [%4];" : "=r"(v.x), "=r"(v.y), "=r"(v.z), "=r"(v.w) : "l"(p) : "memory"); return v;
}
__device__ __forceinline__ void st_relaxed(void* p, uint32_t v) { asm volatile("st.relaxed.gpu.global.u32 [%0], %1;" ::"l"(p), "r"(v) : "memory"); }
__device__ __forceinline__ void st_relaxed16(void* p, uint32_t v) { asm volatile("st.relaxed.gpu.global.u16 [%0], %1;" ::"l"(p), "h"((uint16_t)v) : "memory"); }
__device__ __forceinline__ void red_add(void* p, uint32_t v) { asm volatile("red.relaxed.gpu.global.add.u32 [%0], %1;" ::"l"(p), "r"(v) : "memory"); }
__device__ __forceinline__ void fence_gpu() { asm volatile("fence.acq_rel.gpu;" ::: "memory"); }
__device__ __forceinline__ void fence_acquire() { asm volatile("fence.acquire.gpu;" ::: "memory"); }
__device__ __forceinline__ void fence_release() { asm volatile("fence.release.gpu;" ::: "memory"); }
__device__ __forceinline__ void mbar_init(uint32_t a, uint32_t n) { asm volatile("mbarrier.init.shared.b64 [%0], %1;" ::"r"(a), "r"(n) : "memory"); }
__device__ __forceinline__ void mbar_arrive(uint32_t a) { asm volatile("mbarrier.arrive.shared.b64 _, [%0];" ::"r"(a) : "memory"); }
__device__ __forceinline__ bool mbar_try(uint32_t a, uint32_t ph) {
    uint32_t ok;
    asm volatile("{.reg .pred p; mbarrier.try_wait.parity.shared.b64 p, [%1], %2, %3; selp.u32 %0, 1, 0, p;}" : "=r"(ok) : "r"(a), "r"(ph), "r"(2000) : "memory");
    return ok;
}
__device__ __forceinline__ bool mbar_test(uint32_t a, uint32_t ph) {
    uint32_t ok;
    asm volatile("{.reg .pred p; mbarrier.test_wait.parity.shared.b64 p, [%1], %2; selp.u32 %0, 1, 0, p;}" : "=r"(ok) : "r"(a), "r"(ph) : "memory");
    return ok;
}
constexpr int SPIN_MAX = 1 << 22;
__device__ __forceinline__ void mbar_wait(uint32_t a, uint32_t ph) {
    int it = 0;
    while (!mbar_try(a, ph)) { if (++it > SPIN_MAX) __trap(); }
}
__device__ __forceinline__ void backoff(int& it) { __nanosleep(SLEEP_); if (++it > SPIN_MAX) __trap(); }
__device__ __forceinline__ void wait_ge(const void* p, uint32_t v) {
    int it = 0;
    while (ld_relaxed(p) < v) backoff(it);
}

__device__ __forceinline__ bool elect_one() {
    uint32_t r; asm volatile("{.reg .pred p; elect.sync _|p, 0xffffffff; selp.u32 %0, 1, 0, p;}" : "=r"(r)); return r;
}
__device__ __forceinline__ void st_lane0(void* p, uint32_t v, int lane) {
    asm volatile("{.reg .pred p; setp.eq.s32 p, %2, 0; @p st.relaxed.gpu.global.u32 [%0], %1;}" ::"l"(p), "r"(v), "r"(lane) : "memory");
}
__device__ __forceinline__ void wait_all_ge(const void* p, uint32_t v) {
    int it = 0;
    while (!__all_sync(0xffffffffu, ld_relaxed(p) >= v)) backoff(it);
}
__device__ __forceinline__ void lds_lt(uint32_t& v, uint32_t ad, int a, int b) {
    asm volatile("{.reg .pred p; setp.lt.s32 p, %2, %3; @p ld.shared.u32 %0, [%1];}" : "+r"(v) : "r"(ad), "r"(a), "r"(b));
}

constexpr uint32_t R_V1 = 0x03000, R_A = 0x81000, R_B = 0x82000, R_UNIT = 0x4000, R_HI = 0x40000 - 8 * 256;
__device__ __forceinline__ uint32_t q_base(uint32_t q, uint32_t pagebits_x) { return (q << 20) | (((pagebits_x >> (q >> 1)) & 1u) << 12); }
__device__ __forceinline__ uint32_t slot_off(uint32_t s) { return (s << 16) | (((s + 1) & 2) << 11); }
constexpr uint32_t OFF_PF = R_B + 3 * R_UNIT, OFF_RDY = OFF_PF + 128, OFF_REL = OFF_PF + 256;
constexpr uint32_t OFF_PROBE = 3 * R_UNIT;
static_assert(RA <= 4 && RV <= 4 && RB <= 8 && RA <= RB && RV <= RB, "ring");

__device__ __forceinline__ uint32_t probe(unsigned char* p) {
    volatile uint32_t* sink = (volatile uint32_t*)(smem + S_MISC + 240);
    asm volatile("st.global.v4.u32 [%0], {%1,%1,%1,%1};" ::"l"(p), "r"(0) : "memory");
    asm volatile("st.global.v4.u32 [%0], {%1,%1,%1,%1};" ::"l"(p + 16), "r"(0) : "memory");
    uint32_t best = 0xffffffffu;
#pragma unroll 1
    for (int r = 0; r < 3; r++) {
        uint32_t t0, t1, v;
        asm volatile("mov.u32 %0, %%clock;" : "=r"(t0)::"memory");
        asm volatile("atom.relaxed.gpu.global.add.u32 %0, [%1], 1;" : "=r"(v) : "l"(p) : "memory");
        *sink = v;
        asm volatile("mov.u32 %0, %%clock;" : "=r"(t1)::"memory");
        best = min(best, t1 - t0);
    }
    return best;
}

struct Wts { float c[8], wr[32], ws[32], wd[16], wu[16]; };
__device__ __forceinline__ void load_wts(const Prm& p, Wts* w) {
    int t = threadIdx.x;
    if (t < 8) w->c[t] = __bfloat162float(p.centers[t]);
    if (t < 32) { w->wr[t] = __bfloat162float(p.w_rbf[t]); w->ws[t] = __bfloat162float(p.w_sbf[t]); }
    if (t < 16) { w->wd[t] = __bfloat162float(p.w_down[t]); w->wu[t] = __bfloat162float(p.w_up[t]); }
}
__device__ __forceinline__ void radial(const Wts* w, float d, float s[4], float g[4]) {
#pragma unroll
    for (int j = 0; j < 4; j++) s[j] = g[j] = 0.f;
#pragma unroll
    for (int r = 0; r < 8; r++) {
        float x = rbf16(d - w->c[r]);
        float b = rbf16(__expf(rbf16(-10.0f * rbf16(x * x))));
#pragma unroll
        for (int j = 0; j < 4; j++) { s[j] += b * w->ws[r * 4 + j]; g[j] += b * w->wr[r * 4 + j]; }
    }
}
__device__ __noinline__ uint4 radial_bf16(const Wts* w, uint32_t dbits) {
    float s[4], g[4];
    radial(w, __uint_as_float(dbits << 16), s, g);
    return make_uint4(pack_bf16(s[1], s[0]), pack_bf16(s[3], s[2]), pack_bf16(g[1], g[0]), pack_bf16(g[3], g[2]));
}
__device__ __forceinline__ uint2 finish_row(const float* wu, const float agg[4], const float g[4], uint2 r) {
    float o[4];
    const float mm[4] = {bf_lo(r.x), bf_hi(r.x), bf_lo(r.y), bf_hi(r.y)};
#pragma unroll
    for (int j = 0; j < 4; j++) o[j] = mm[j] + (agg[0] * wu[j] + agg[1] * wu[4 + j] + agg[2] * wu[8 + j] + agg[3] * wu[12 + j]) * g[j];
    return make_uint2(pack_bf16(o[1], o[0]), pack_bf16(o[3], o[2]));
}
__device__ __forceinline__ uint2 down_row(const float* wd, uint32_t x, uint32_t y) {
    const float a[4] = {bf_lo(x), bf_hi(x), bf_lo(y), bf_hi(y)};
    float d[4];
#pragma unroll
    for (int j = 0; j < 4; j++) d[j] = a[0] * wd[j] + a[1] * wd[4 + j] + a[2] * wd[8 + j] + a[3] * wd[12 + j];
    return make_uint2(pack_bf16(d[1], d[0]), pack_bf16(d[3], d[2]));
}

__device__ __forceinline__ void down_load(const Prm& p, int pc) {
    const int r0 = pc * PC_ROWS / 2, nr = max(min((pc + 1) * PC_ROWS, p.E) / 2 - r0, 0);
    const uint32_t bar = SB + S_MISC + 248;
    mbar_init(bar, 1);
    asm volatile("fence.proxy.async.shared::cta;" ::: "memory");
    asm volatile("mbarrier.arrive.expect_tx.shared.b64 _, [%0], %1;" ::"r"(bar), "r"(nr * 16) : "memory");
    for (int o = 0; o < nr; o += 640)
        asm volatile("cp.async.bulk.shared::cluster.global.mbarrier::complete_tx::bytes [%0], [%1], %2, [%3];"
                     ::"r"(SB + S_PC + o * 16), "l"((const uint4*)p.m + r0 + o), "r"(min(640, nr - o) * 16), "r"(bar) : "memory");
}
__device__ __forceinline__ void down_piece(const Prm& p, int pc, const float* wd) {
    const int tid = threadIdx.x, lane = tid & 31, w = tid >> 5;
    const int r0 = pc * PC_ROWS / 2, nr = max(min((pc + 1) * PC_ROWS, p.E) / 2 - r0, 0);
    mbar_wait(SB + S_MISC + 248, 0);
    uint32_t mx0 = 0, mx1 = 0; float ss[4] = {0.f, 0.f, 0.f, 0.f};
    for (int r = tid; r < nr; r += THREADS) {
        const uint4 v = ((const uint4*)(smem + S_PC))[r];
        const uint2 a = down_row(wd, v.x, v.y), b = down_row(wd, v.z, v.w);
        ((uint2*)g_md[0])[r0 + r] = make_uint2(a.x, b.x); ((uint2*)g_md[1])[r0 + r] = make_uint2(a.y, b.y);
        mx0 = __vimax3_u16x2(mx0, a.x & 0x7fff7fffu, b.x & 0x7fff7fffu); mx1 = __vimax3_u16x2(mx1, a.y & 0x7fff7fffu, b.y & 0x7fff7fffu);
        ss[0] += bf_lo(a.x) * bf_lo(a.x) + bf_lo(b.x) * bf_lo(b.x); ss[1] += bf_hi(a.x) * bf_hi(a.x) + bf_hi(b.x) * bf_hi(b.x);
        ss[2] += bf_lo(a.y) * bf_lo(a.y) + bf_lo(b.y) * bf_lo(b.y); ss[3] += bf_hi(a.y) * bf_hi(a.y) + bf_hi(b.y) * bf_hi(b.y);
    }
    uint32_t st[4] = {mx0 << 16, mx0 & 0xffff0000u, mx1 << 16, mx1 & 0xffff0000u};
    uint4* red = (uint4*)(smem + S_PC + PC_ROWS * 8);
    for (int pass = 0; pass < 2; pass++) {
#pragma unroll
        for (int ch = 0; ch < 4; ch++) {
            st[ch] = __reduce_max_sync(0xffffffffu, st[ch]);
#pragma unroll
            for (int o = 16; o; o >>= 1) ss[ch] += __shfl_xor_sync(0xffffffffu, ss[ch], o);
        }
        uint4* dst = pass ? (uint4*)g_ctl.stat[pc] : red + 2 * w;
        if (lane == 0) { dst[0] = make_uint4(st[0], st[1], st[2], st[3]); dst[1] = make_uint4(__float_as_uint(ss[0]), __float_as_uint(ss[1]), __float_as_uint(ss[2]), __float_as_uint(ss[3])); }
        if (pass) break;
        __syncthreads();
        const uint4 a = lane < NW ? red[2 * lane] : make_uint4(0, 0, 0, 0), b = lane < NW ? red[2 * lane + 1] : make_uint4(0, 0, 0, 0);
        __syncthreads();
        if (w != NW - 1) return;
        st[0] = a.x; st[1] = a.y; st[2] = a.z; st[3] = a.w;
        ss[0] = __uint_as_float(b.x); ss[1] = __uint_as_float(b.y); ss[2] = __uint_as_float(b.z); ss[3] = __uint_as_float(b.w);
    }
    if (lane == 0) { fence_release(); red_add(&g_ctl.pieces_done, 1); }
    __syncwarp();
}

__device__ __forceinline__ void get_scales(const Prm& p, float sc[4], bool& bad) {
    const int lane = threadIdx.x & 31;
    uint32_t mxb[4] = {0, 0, 0, 0};
    float ss[4] = {0.f, 0.f, 0.f, 0.f};
#pragma unroll
    for (int k = 0; k < (NPC + 31) / 32; k++) {
        if (lane + 32 * k < NPC) {
            const uint4 a = ld_relaxed4(&g_ctl.stat[lane + 32 * k][0]), b = ld_relaxed4(&g_ctl.stat[lane + 32 * k][4]);
            mxb[0] = max(mxb[0], a.x); mxb[1] = max(mxb[1], a.y); mxb[2] = max(mxb[2], a.z); mxb[3] = max(mxb[3], a.w);
            ss[0] += __uint_as_float(b.x); ss[1] += __uint_as_float(b.y); ss[2] += __uint_as_float(b.z); ss[3] += __uint_as_float(b.w);
        }
    }
    bad = false;
    const float kdeg = fminf(3.5f * sqrtf(fmaxf(0.5f * (float)p.T / (float)p.E, 1.0f)), 128.f);
#pragma unroll
    for (int ch = 0; ch < 4; ch++) {
        float mx = __uint_as_float(__reduce_max_sync(0xffffffffu, mxb[ch]));
#pragma unroll
        for (int o = 16; o; o >>= 1) ss[ch] += __shfl_xor_sync(0xffffffffu, ss[ch], o);
        float rms = sqrtf(ss[ch] / (float)p.E);
        float range = fmaxf(4.002f * mx, kdeg * rms);
        if (!(mx <= 1e15f) || !(range <= 128.f * rms) || (mx > 0.f && mx < 1e-15f)) bad = true;
        sc[ch] = range > 0.f ? 32767.f / range : 0.f;
    }
}

constexpr int PER = 40;
__host__ __device__ constexpr uint32_t bar_done(uint32_t s) { return SB + P_BAR + (s % NBUF) * 16; }
__host__ __device__ constexpr uint32_t bar_free(uint32_t m) { return bar_done(m + NBUF - (GR - 1)) + 8; }
struct __align__(16) PTab { uint32_t e[PER][4]; };
constexpr PTab make_ptab() {
    PTab t = {};
    for (int s = 0; s < PER; s++) {
        for (int d = 0; d < GR; d++) {
            int gi = (s + d) % GR, buf = (s + d) % NBUF, X = gi & 1, g = gi >> 1;
            t.e[s][X] |= (uint32_t)(4 * UN * buf - g - 4 * X + 7) << (8 * g);
        }
        t.e[s][2] = bar_done(s);
        t.e[s][3] = (((s + GR - 1) / NBUF) & 1) ^ 1;
    }
    return t;
}
__constant__ PTab c_ptab = make_ptab();
constexpr int BIAS = 7 * NCP;
static_assert(NG == 4 && CPS >= FW, "group selection");

struct PCtx { uint32_t a0, a1; };
struct PElem { uint32_t b4, aw, ol, r2; };

__device__ __forceinline__ void p_bin(const PCtx& c, PElem& e, uint32_t i, uint32_t o) {
    uint32_t ib = __umulhi(i, MAG_I), ob = __umulhi(o, MAG_O), sel = ib & 3;
    asm("{.reg .pred p; setp.ge.u32 p, %1, %2; @p add.u32 %0, %0, 4;}" : "+r"(sel) : "r"(o), "n"(HALF_O));
    e.b4 = __dp4a(prmt(c.a0, c.a1, sel), (uint32_t)NCP, ib * NCP + ob * 4);
    e.aw = i - ib * ROWS_I;
    e.ol = o - ob * ROWS_O;
}
__device__ __forceinline__ void p_rank(PElem& e) {
    asm volatile("atom.shared.add.u32 %0, [%1+%2], 2;" : "=r"(e.r2) : "r"(e.b4), "n"(SB + P_CNT - BIAS) : "memory");
}
__device__ __forceinline__ void p_store(const PElem& e) {
    const uint32_t ab = e.b4 * (KS / 2) + e.r2;
    asm volatile("{.reg .pred p; setp.lt.u32 p, %4, %5; @p st.shared.u32 [%0+%6], %1; @p st.shared.u16 [%2+%7], %3;}"
                 ::"r"(ab * 2), "r"(e.aw), "r"(ab), "h"((uint16_t)e.ol), "r"(e.r2), "n"(KS * 2),
                   "n"(SB + P_A - BIAS * KS), "n"(SB + P_B - BIAS * (KS / 2)) : "memory");
}
__device__ __forceinline__ uint32_t cos2(uint32_t x) {
    x = __vminu2(x, 0x42804280u);
    return pack_bf16(__cosf(bf_hi(x)), __cosf(bf_lo(x)));
}

#define PD_ 2
#define CB_ 8
constexpr int CB = CB_;
struct PIn { uint4 i, o; uint2 a; };

struct PFill {
    PCtx c;
    uint32_t qb, qt, lt, f2, bar, par, xmax;
    uint32_t s0, lane, vb;
    bool open;
    __device__ __forceinline__ void fetch(const Prm& p, PIn& x, uint32_t ch) {
        const int v = ((ch & ~(CB - 1u)) * (NP - 1) + ch) * 32 + vb;
        asm volatile("{.reg .b32 d0, d1; tex.1d.v4.u32.s32 {%0,%1,d0,d1}, [%2, {%3}];}" : "=r"(x.a.x), "=r"(x.a.y) : "l"(p.t_ang), "r"(v));
        asm volatile("tex.1d.v4.u32.s32 {%0,%1,%2,%3}, [%4, {%5}];" : "=r"(x.i.x), "=r"(x.i.y), "=r"(x.i.z), "=r"(x.i.w) : "l"(p.t_in), "r"(v));
        asm volatile("tex.1d.v4.u32.s32 {%0,%1,%2,%3}, [%4, {%5}];" : "=r"(x.o.x), "=r"(x.o.y), "=r"(x.o.z), "=r"(x.o.w) : "l"(p.t_out), "r"(v));
    }
    __device__ __forceinline__ uint32_t ticket(uint32_t zero) {
        uint32_t t;
        asm volatile("atom.shared.add.u32 %0, [%1+%2], %3;" : "=r"(t) : "r"(lane * 4), "n"(SB + P_TKT), "r"((~lt & 1) | zero) : "memory");
        return t;
    }
    __device__ __forceinline__ uint32_t use_ticket(uint32_t t) {
        t = __reduce_or_sync(0xffffffffu, t);
        begin(t / CPS);
        return t + PD_ * FW;
    }
    __device__ __forceinline__ void begin(uint32_t step) {
        const uint4 t = ((const uint4*)c_ptab.e)[(step + s0) % PER];
        c.a0 = t.x; c.a1 = t.y; bar = t.z; par = t.w;
        open = mbar_test(bar + 8, par);
    }
    __device__ __forceinline__ void enter() { if (!open) mbar_wait(bar + 8, par); }
    __device__ __forceinline__ void end() {
        __syncwarp();
        asm volatile("{.reg .pred p; setp.eq.u32 p, %1, 0; @p mbarrier.arrive.shared.b64 _, [%0];}" ::"r"(bar), "r"(lt) : "memory");
    }
    __device__ __forceinline__ void push(bool f, uint32_t x, uint32_t y) {
        const uint32_t mask = __ballot_sync(0xffffffffu, f);
        asm volatile("{.reg .pred p; setp.ne.u32 p, %3, 0; @p st.shared.v2.u32 [%0], {%1,%2};}"
                     ::"r"(min(qt + __popc(mask & lt) * 8, qb + (QN - 1) * 8)), "r"(x), "r"(y), "r"((uint32_t)f) : "memory");
        qt += __popc(mask) * 8;
    }
    __device__ __forceinline__ void push3(bool f, uint32_t i, uint32_t o, uint32_t aw) { push(f, prmt(i, aw, 0x6210), prmt(o, aw, 0x7210)); }
    __device__ __forceinline__ uint32_t chunk(const PIn& x) {
        uint32_t x0, x1;
        const uint32_t tk = use_ticket(ticket(x.o.x >> 31));
        PElem e0, e1, e2, e3;
        p_bin(c, e0, x.i.x, x.o.x); p_bin(c, e1, x.i.y, x.o.y); p_bin(c, e2, x.i.z, x.o.z); p_bin(c, e3, x.i.w, x.o.w);
        asm volatile("" : "+r"(e0.b4), "+r"(e1.b4), "+r"(e2.b4), "+r"(e3.b4));
        enter();
        p_rank(e0); p_rank(e1); p_rank(e2); p_rank(e3);
        asm volatile("mul.rn.bf16x2 %0, %1, %2;" : "=r"(x0) : "r"(x.a.x), "r"(f2));
        asm volatile("mul.rn.bf16x2 %0, %1, %2;" : "=r"(x1) : "r"(x.a.y), "r"(f2));
        x0 &= 0x7fff7fffu; x1 &= 0x7fff7fffu;
        xmax = __vimax3_u16x2(xmax, x0, x1);
        const uint32_t c0 = cos2(x0), c1 = cos2(x1);
        e0.aw = prmt(e0.aw, c0, 0x5410); e1.aw = prmt(e1.aw, c0, 0x7610); e2.aw = prmt(e2.aw, c1, 0x5410); e3.aw = prmt(e3.aw, c1, 0x7610);
        p_store(e0); p_store(e1); p_store(e2); p_store(e3);
        if (qt - qb >= QTRIG * 8) retry(32);
        end();
        const uint32_t r01 = e0.r2 | e1.r2, r23 = e2.r2 | e3.r2;
        const bool f = (r01 | r23) >= KS * 2;
        if (__any_sync(0xffffffffu, f)) {
            const bool f0 = e0.r2 >= KS * 2, f1 = e1.r2 >= KS * 2, f2_ = e2.r2 >= KS * 2, f3 = e3.r2 >= KS * 2, f01 = r01 >= KS * 2;
            push3(f, f01 ? (f0 ? x.i.x : x.i.y) : (f2_ ? x.i.z : x.i.w), f01 ? (f0 ? x.o.x : x.o.y) : (f2_ ? x.o.z : x.o.w),
                  f01 ? (f0 ? e0.aw : e1.aw) : (f2_ ? e2.aw : e3.aw));
            const uint32_t s2 = max(max(min(e0.r2, e1.r2), min(e2.r2, e3.r2)), min(r01, r23));
            if (__any_sync(0xffffffffu, s2 >= KS * 2)) {
                push3(f1 && f0, x.i.y, x.o.y, e1.aw); push3(f2_ && f01, x.i.z, x.o.z, e2.aw); push3(f3 && (f01 || f2_), x.i.w, x.o.w, e3.aw);
            }
        }
        return tk;
    }
    __device__ __forceinline__ void retry(uint32_t take) {
        if (qt - qb > QN * 8) { st_relaxed(&g_ctl.bad, 1); qt = qb + QN * 8; }
        uint2 e, r, r1;
        __syncwarp();
        asm volatile("ld.shared.v2.u32 {%0,%1}, [%2];" : "=r"(e.x), "=r"(e.y) : "r"(qb + lane * 8) : "memory");
        asm volatile("ld.shared.v2.u32 {%0,%1}, [%2];" : "=r"(r.x), "=r"(r.y) : "r"(qb + (lane + take) * 8) : "memory");
        qt -= take * 8;
        const bool more = qt - qb > 256;
        if (more) asm volatile("ld.shared.v2.u32 {%0,%1}, [%2];" : "=r"(r1.x), "=r"(r1.y) : "r"(qb + (lane + take) * 8 + 256) : "memory");
        __syncwarp();
        if (more && qb + lane * 8 + 256 < qt) asm volatile("st.shared.v2.u32 [%0], {%1,%2};" ::"r"(qb + lane * 8 + 256), "r"(r1.x), "r"(r1.y) : "memory");
        if (qb + lane * 8 < qt) asm volatile("st.shared.v2.u32 [%0], {%1,%2};" ::"r"(qb + lane * 8), "r"(r.x), "r"(r.y) : "memory");
        PElem el;
        el.r2 = 0;
        if (take == 32 || lane < take) {
            p_bin(c, el, e.x & 0xffffffu, e.y & 0xffffffu);
            el.aw = prmt(el.aw, prmt(e.x, e.y, 0x0073), 0x5410);
            p_rank(el);
            p_store(el);
        }
        push(el.r2 >= KS * 2, e.x, e.y);
    }
};

__device__ __forceinline__ void p_filler(const Prm& p, int q, int w) {
    PFill F;
    const int lane = threadIdx.x & 31;
    const uint32_t NS = p.NS, cend = p.T >> 7, nv = NS * CPS, nc = cend / (NP * CB) * CB + min(max((int)(cend % (NP * CB)) - q * CB, 0), CB);
    static_assert(QN <= 96, "retry moves two batches");
    F.lt = __shfl_sync(0xffffffffu, (1u << lane) - 1u, lane);
    F.lane = __shfl_sync(0xffffffffu, lane, lane);
    F.vb = __shfl_sync(0xffffffffu, q * (32 * CB) + lane, lane);
    F.f2 = __shfl_sync(0xffffffffu, __bfloat16_as_ushort(p.freq[0]) * 0x10001u, 0);
    F.qb = F.qt = SB + P_Q + w * (QN * 8);
    F.s0 = q % GR; F.xmax = 0;
    uint32_t c0 = w, c1 = w + FW;
    PIn x0, x1;
    F.fetch(p, x0, c0);
#pragma unroll 1
    while (c0 < nc) {
        F.fetch(p, x1, c1);
        c0 = F.chunk(x0);
        if (c1 >= nc) break;
        F.fetch(p, x0, c0);
        c1 = F.chunk(x1);
    }
    int left = (c0 < nv) + (c1 < nv);
#pragma unroll 1
    while (left > 0) { left -= F.use_ticket(F.ticket(0)) >= nv; F.enter(); F.end(); }
    if (q == 0 && w < 8) {
        const int t = cend * 128 + w * 16 + lane;
        const bool f = t < p.T && lane < 16;
        uint32_t i = 0, o = 0, x = 0;
        if (f) { i = p.idx_in[t]; o = p.idx_out[t]; asm("mul.rn.bf16x2 %0, %1, %2;" : "=r"(x) : "r"(__bfloat16_as_ushort(p.angle[t]) * 0x10001u), "r"(F.f2)); }
        F.xmax = __vmaxu2(F.xmax, x & 0x7fff7fffu);
        if (F.qt - F.qb >= 32 * 8) { F.begin(NS); F.enter(); F.retry(32); }
        F.push3(f, i, o, cos2(x & 0x7fff7fffu));
    }
#pragma unroll 1
    for (uint32_t n = NS; n <= NS + GR; n++) {
        F.begin(n); F.enter();
        for (uint32_t nq = min((F.qt - F.qb) >> 3, (uint32_t)QN); nq > 0;) { uint32_t take = min(nq, 32u); F.retry(take); nq -= take; }
        F.end();
        if (CPS > FW && w < CPS - FW) F.end();
    }
    if (F.qt != F.qb || ((F.xmax + 0x3d803d80u) & 0x80008000u)) st_relaxed(&g_ctl.bad, 1);
}

template <int N> __device__ __forceinline__ void p_stamp(const uint32_t (&st)[N], uint32_t off, uint32_t bit, bool set) {
    if (set) {
#pragma unroll
        for (int j = 0; j < N; j++) asm volatile("red.shared.or.b32 [%0], %1;" ::"r"(st[j] + off), "r"(bit) : "memory");
    } else {
#pragma unroll
        for (int j = 0; j < N; j++) asm volatile("red.shared.and.b32 [%0], %1;" ::"r"(st[j] + off), "r"(~bit) : "memory");
    }
}
__device__ __forceinline__ void bulk_store(void* dst, uint32_t src, uint32_t bytes) {
    asm volatile("cp.async.bulk.global.shared::cta.bulk_group [%0], [%1], %2;" ::"l"(dst), "r"(src), "r"(bytes) : "memory");
}
__device__ __forceinline__ void p_flusher(const Prm& p, unsigned char* ring, uint32_t pagebits, int q, int f) {
    const int lane = threadIdx.x & 31;
    const uint32_t NS = p.NS, NT = NS + 2 * GR, s0 = q % GR;
    uint32_t sta[4], stb[2];
#pragma unroll
    for (int j = 0; j < 4; j++) {
        const int pp = min(8 * j + (lane >> 2), 26), bin = min(32 * j + lane, NB - 1);
        sta[j] = SB + P_A + pp * 512 + (lane & 3) * 160 + ((pp % 9) & 3) * 4;
        if (j < 2) stb[j] = SB + P_B + bin * 128 + ((bin % NCP) & 15) * 8;
    }
    const uint32_t pfo = OFF_PF + (lane / 6) * 32 + (lane & 1) * 16 + ((lane % 6) >> 1) * 4, pfc = (lane >> 1) * 6 + (lane & 1);
    const uint32_t wto = lane < NCP ? OFF_REL + lane * 4 : OFF_RDY + (lane % 6) * 4;
    PROF_DECL
#pragma unroll 1
    for (uint32_t n = f; n < NT; n += NF) {
        const uint32_t buf = (n + s0) % NBUF, h = n >> 1, lap = h / RB;
        const uint32_t qb = q_base(q, pagebits) ^ (((n + q) & 1) << 12), bb = qb ^ slot_off(h % RB);
        if (h >= RA && !DEV_FREE) {
            const uint32_t hw = lane < NCP ? h : h + RB - RA;
            wait_all_ge(ring + (qb ^ slot_off(hw % RB) ^ wto), (hw / RB) << (lane < NCP ? 0 : 1));
        }
        PROF(0);
#pragma unroll
        for (int d = 2; d >= 0; d--) {
            const int nl = (int)min(n, NS + GR) - d;
            if (nl >= 0) mbar_wait(bar_done(nl + s0), ((nl + s0) / NBUF) & 1);
        }
        PROF(1);
        uint32_t* cnt = (uint32_t*)(smem + P_CNT) + buf * NB;
        bool any = true;
        if (n >= NS) any = __any_sync(0xffffffffu, lane < NCP && (cnt[lane] | cnt[NCP + lane] | cnt[2 * NCP + lane]));
        if (any) {
            const uint32_t oa = buf * (NB * KS * 4), ob = buf * (NB * KS * 2);
            unsigned char* da = ring + (qb ^ slot_off(h % RA) ^ R_A);
            unsigned char* db = ring + (bb ^ R_B);
            p_stamp(sta, oa, 0x40000000u, (h / RA) & 1);
            p_stamp(stb, ob, 0x8000u, lap & 1);
            __syncwarp();
            if (elect_one()) {
                asm volatile("fence.proxy.async.shared::cta;" ::: "memory");
#pragma unroll
                for (int u = 0; u < UN; u++) {
                    bulk_store(da + u * R_UNIT, SB + P_A + oa + u * (NCP * KS * 4), 8 * KS * 4);
                    bulk_store(da + u * R_UNIT + 0x40000, SB + P_A + oa + (u * NCP + 8) * (KS * 4), (NCP - 8) * KS * 4);
                }
#pragma unroll
                for (int u = 0; u < UN; u++) bulk_store(db + u * R_UNIT, SB + P_B + ob + u * (NCP * KS * 2), NCP * KS * 2);
            }
            __syncwarp();
        }
        uint32_t wm = ((lap + 1) << 22) | ((uint32_t)any << 21);
        if (lane < NCP) {
#pragma unroll
            for (int u = 0; u < 3; u++) wm |= min(cnt[pfc + 2 * u] >> 1, (uint32_t)KS) << (7 * u);
        }
        __syncwarp();
        if (lane < NB / 2) ((uint2*)cnt)[lane] = make_uint2(0, 0);
        PROF(3);
        asm volatile("cp.async.bulk.commit_group;" ::: "memory");
        asm volatile("cp.async.bulk.wait_group 0;" ::: "memory");
        __syncwarp();
        PROF(2);
        const bool safe = h < RB || n >= NS;
        if (!safe && lane < NCP) st_relaxed(ring + (bb ^ pfo), wm);
        if (n > 0) mbar_wait(bar_free(n - 1 + s0), ((n - 1 + s0) / NBUF) & 1);
        if (lane == 0) mbar_arrive(bar_free(buf));
        if (safe) {
            if (any) fence_release();
            if (lane < NCP) st_relaxed(ring + (bb ^ pfo), wm);
        }
        PROF(4);
    }
    PROF_END;
}
__device__ __forceinline__ void p_cleanup(unsigned char* ring, int q) {
    const int k = threadIdx.x / 24;
    if (k < 2 * RB) *(uint4*)(ring + ((q << 20) ^ ((k & 1) << 12) ^ slot_off(k >> 1) ^ OFF_PF) + (threadIdx.x % 24) * 16) = make_uint4(0, 0, 0, 0);
}

__device__ __forceinline__ void m_role(const Prm& p, unsigned char* ring, int X, int id) {
    const int tid = threadIdx.x, lane = tid & 31, w = __shfl_sync(0xffffffffu, tid >> 5, 0);
    const int ib = id >> 1, ty = id & 1;
    float* scs = (float*)(smem + S_MISC);
    if (w == 0) {
        const uint32_t bar = SB + S_AUX;
        if (lane == 0) mbar_init(bar, 1);
        wait_ge(&g_ctl.pieces_done, NPC);
        fence_acquire();
        if (lane == 0) {
            asm volatile("fence.proxy.async.global;" ::: "memory");
            asm volatile("fence.proxy.async.shared::cta;" ::: "memory");
            asm volatile("mbarrier.arrive.expect_tx.shared.b64 _, [%0], %1;" ::"r"(bar), "r"(ROWS_I * 4) : "memory");
            constexpr uint32_t PART = (ROWS_I * 4 / 8 + 127) / 128 * 128;
            for (uint32_t o = 0; o < ROWS_I * 4; o += PART)
                asm volatile("cp.async.bulk.shared::cluster.global.mbarrier::complete_tx::bytes [%0], [%1], %2, [%3];"
                             ::"r"(SB + o), "l"((const char*)(g_md[ty] + ib * ROWS_I) + o), "r"(min(PART, ROWS_I * 4 - o)), "r"(bar) : "memory");
        }
        __syncwarp();
            float sc[4]; bool bad;
        get_scales(p, sc, bad);
            if (bad) { st_relaxed(&g_ctl.bad, 1); sc[0] = sc[1] = sc[2] = sc[3] = 0.f; }
        int it = 0; uint32_t pb;
        while (!((pb = ld_relaxed(&g_ctl.pagebits)) >> 31)) backoff(it);
        if (lane == 0) { scs[0] = sc[0]; scs[1] = sc[1]; scs[2] = sc[2]; scs[3] = sc[3]; ((uint32_t*)scs)[4] = X ? ~pb : pb; ((uint32_t*)scs)[5] = bad; }
        mbar_wait(bar, 0);
    }
    __syncthreads();
    if (((uint32_t*)scs)[5]) {
        for (int k = tid; k < (int)ROWS_I; k += THREADS) ((uint32_t*)smem)[k] = 0;
        __syncthreads();
    }
    const uint32_t NT = p.NS + 2 * GR;
    if (w >= MW) return;
    const uint32_t pagebits = ((uint32_t*)scs)[4];
    const int half = lane >> 4, k4 = (lane & 15) * 4;
    const float s_lo = scs[2 * ty], s_hi = scs[2 * ty + 1];
    const float MAG_LO = 12582912.f, MAG_HI = 12582912.f - 19264.f;
    const int il = ib / NG, gi = (ib % NG) * 2 + X;
    const uint32_t a_off = R_A + il * R_UNIT + lane * 16, v_off = ty * R_V1 + il * R_UNIT + lane * 16;
    const uint32_t f_off = OFF_PF + il * 32 + half * 16, r_off = OFF_REL + (lane % NCP) * 4;
    const uint32_t j = w % (NP / GR);
    PROF_DECL
#pragma unroll 1
    for (uint32_t n = w / (NP / GR); n < NT; n += MW / (NP / GR)) {
        const uint32_t q = ((gi - n) & (GR - 1)) + GR * j, h = n >> 1;
        const uint32_t qb = q_base(q, pagebits), bb = qb ^ slot_off(h % RB);
        const uint32_t tag = (h / RB + 1) << 22;
        uint4 cw; int it = 0;
        while (true) {
            cw = ld_relaxed4(ring + (bb ^ f_off));
            if (__all_sync(0xffffffffu, min(min(cw.x, cw.y), cw.z) >= tag)) break;
            if (DEV_FREE) { cw.x = (cw.x & 1) + (63 | 57 << 7 | 50 << 14 | 1 << 21); cw.y = (cw.y & 1) + (53 | 61 << 7 | 57 << 14); cw.z = (cw.z & 1) + (59 | 52 << 7 | 57 << 14); break; }
            backoff(it);
        }
        PROF(0);
        if (__any_sync(0xffffffffu, cw.x & (1u << 21))) {
            const unsigned char* pa = ring + (qb ^ slot_off(h % RA) ^ a_off);
            unsigned char* pv = ring + (qb ^ slot_off(h % RV) ^ v_off);
            const uint32_t hv = h + RB - RV;
            const unsigned char* prel = ring + (qb ^ slot_off(hv % RB) ^ r_off);
            const uint32_t rel = ld_relaxed(prel);
            const uint32_t vlap = h / RV;
            const float mag_lo0 = MAG_LO + (float)(8192 + (vlap & 3) * 16384), mag_hi0 = MAG_HI + (float)(8192 + ((vlap >> 2) & 3) * 16384);
            const uint32_t stamp = ((h / RA) & (0x40100401u >> lane) & 1) << 30;
            uint4 a[9];
#define M_LOAD(ps) a[ps] = ld_relaxed4(pa + (ps) * 512 + ((ps) < 4 ? 0 : R_HI))
#pragma unroll
            for (int ps = 0; ps < MPF; ps++) M_LOAD(ps);
            if (!__all_sync(0xffffffffu, rel >= hv / RB) && !DEV_FREE) wait_all_ge(prel, hv / RB);
            PROF(3);
#pragma unroll
            for (int ps = 0; ps < 9; ps++) {
                const int rem = (int)(((ps < 3 ? cw.x : ps < 6 ? cw.y : cw.z) >> (7 * (ps % 3))) & 0x7f) - k4;
                if (ps % 3 == 0) {
#define M_STAMP(ps) (((ps) & 3) == 0 ? a[ps].x : ((ps) & 3) == 1 ? a[ps].y : ((ps) & 3) == 2 ? a[ps].z : a[ps].w)
                    while (true) {
                        M_STAMP(ps) ^= stamp; M_STAMP(ps + 1) ^= stamp; M_STAMP(ps + 2) ^= stamp;
                        if (!__any_sync(0xffffffffu, (M_STAMP(ps) | M_STAMP(ps + 1) | M_STAMP(ps + 2)) & 0x40000000u)) break;
                        if (DEV_FREE) { M_STAMP(ps) &= 0xbfffffffu; M_STAMP(ps + 1) &= 0xbfffffffu; M_STAMP(ps + 2) &= 0xbfffffffu; break; }
                        if (++it > SPIN_MAX) __trap();
                        M_LOAD(ps); M_LOAD(ps + 1); M_LOAD(ps + 2);
                    }
                }
                uint32_t aw[4] = {a[ps].x, a[ps].y, a[ps].z, a[ps].w}, mv[4], vw[4];
#pragma unroll
                for (int e = 0; e < 4; e++) { mv[e] = 0; lds_lt(mv[e], __dp2a_lo(aw[e], 4u, (uint32_t)SB), e, rem); }
#pragma unroll
                for (int e = 0; e < 4; e++) {
                    float c = bf_hi(aw[e]);
                    float lo = fmaf(bf_lo(mv[e]), c * s_lo, e ? MAG_LO : mag_lo0), hi = fmaf(bf_hi(mv[e]), c * s_hi, e ? MAG_HI : mag_hi0);
                    vw[e] = (__float_as_uint(hi) << 16) + __float_as_uint(lo);
                }
                asm volatile("st.global.v4.u32 [%0], {%1,%2,%3,%4};" ::"l"(pv + ps * 512 + (ps < 4 ? 0 : R_HI)), "r"(vw[0]), "r"(vw[1]), "r"(vw[2]), "r"(vw[3]) : "memory");
                if (ps + MPF < 9) M_LOAD(ps + MPF);
            }
            if (vlap == 0 || n >= p.NS) fence_release();
        }
        st_lane0(ring + (bb ^ (OFF_RDY + (2 * il + ty) * 4)), cw.x >> 21, lane);
        PROF(1);
    }
    PROF_END;
}

__device__ __noinline__ void c_wrap(uint32_t row, int par, uint32_t old, uint32_t w) {
    const uint32_t nw = old + w, ov = ~(old ^ w) & (old ^ nw);
    int d = 0;
    if (ov & 0x8000u) d += (w & 0x8000u) ? -1 : 1;
    if (ov & 0x80000000u) d += (w & 0x80000000u) ? -16 : 16;
    if (d != 0) {
        uint32_t c;
        asm volatile("atom.shared.add.u32 %0, [%1], %2;" : "=r"(c) : "r"(SB + C_WRAP + row * 4), "r"(d << (8 * par)) : "memory");
        c = (c >> (8 * par)) + d;
        if (((c + 1) & 0xe) == 0 || ((c + 16) & 0xe0) == 0) st_relaxed(&g_ctl.bad, 1);
    }
}

#define CGRP 4
struct CTask { uint4 v[3]; uint2 b[3]; };
struct CWork {
    unsigned char* ring;
    uint32_t v_off, b_off, f_off, r_off, acc;
    uint32_t lap1, sv, sb, vtag, fw, stamp;
    int lane, dev_free;
    template <int ODD> __device__ __forceinline__ bool issue(CTask& t) {
        if (!__all_sync(0xffffffffu, fw >= 2 * lap1)) {
            int it = 0;
            do {
                if (dev_free) { fw = 1; break; }
                backoff(it);
                fw = ld_relaxed(ring + (f_off ^ slot_off(sb) ^ (ODD << 20)));
            } while (!__all_sync(0xffffffffu, fw >= 2 * lap1));
        }
        const bool data = __any_sync(0xffffffffu, fw & 1);
        if (data) {
            const unsigned char* pv = ring + (v_off ^ slot_off(sv) ^ (ODD << 20));
            const unsigned char* pb = ring + (b_off ^ slot_off(sb) ^ (ODD << 20));
#pragma unroll
            for (int ps = 0; ps < 3; ps++) {
                t.v[ps] = ld_relaxed4(pv + ps * R_UNIT);
                t.b[ps] = ld_relaxed2(pb + ps * R_UNIT);
            }
        }
        fw = ld_relaxed(ring + (f_off ^ slot_off(ODD ? (sb + 1 == RB ? 0 : sb + 1) : sb) ^ (!ODD << 20)));
        return data;
    }
    template <int ODD> __device__ __forceinline__ void arrive(CTask& t, bool data) {
        if (data) {
            int it = 0;
            while (true) {
#pragma unroll
                for (int ps = 0; ps < 3; ps++) t.b[ps].x ^= stamp;
                if (!__any_sync(0xffffffffu, (((t.v[0].x ^ vtag) | (t.v[1].x ^ vtag) | (t.v[2].x ^ vtag)) & 0xc000c000u) | ((t.b[0].x | t.b[1].x | t.b[2].x) & 0x8000u))) break;
                if (dev_free) { for (int ps = 0; ps < 3; ps++) { t.v[ps].x = (t.v[ps].x & 0x3fff3fffu) | (vtag & 0xc000c000u); t.b[ps].x &= 0xffff7fffu; } break; }
                if (++it > SPIN_MAX) __trap();
#pragma unroll
                for (int ps = 0; ps < 3; ps++) {
                    t.v[ps] = ld_relaxed4(ring + (v_off ^ slot_off(sv) ^ (ODD << 20)) + ps * R_UNIT);
                    t.b[ps] = ld_relaxed2(ring + (b_off ^ slot_off(sb) ^ (ODD << 20)) + ps * R_UNIT);
                }
            }
#pragma unroll
            for (int ps = 0; ps < 3; ps++) t.v[ps].x -= vtag;
        }
        st_lane0(ring + (r_off ^ slot_off(sb) ^ (ODD << 20)), lap1, lane);
        if (ODD) {
            if (++sv == RV) { sv = 0; vtag += 0x4000u; if (vtag & 0x10000u) vtag += 0x3fff0000u; }
            if (++sb == RB) { sb = 0; lap1++; stamp ^= (((b_off >> 3) ^ (b_off >> 7)) & 15) == 0 ? 0x8000u : 0u; }
        }
    }
    __device__ __forceinline__ void add(const CTask& t, bool data) {
        if (!data) return;
        const uint32_t vw[12] = {t.v[0].x, t.v[0].y, t.v[0].z, t.v[0].w, t.v[1].x, t.v[1].y, t.v[1].z, t.v[1].w, t.v[2].x, t.v[2].y, t.v[2].z, t.v[2].w};
        const uint32_t bw[6] = {t.b[0].x, t.b[0].y, t.b[1].x, t.b[1].y, t.b[2].x, t.b[2].y};
#pragma unroll
        for (int g = 0; g < 12; g += CGRP) {
            uint32_t old[CGRP], ov = 0;
#pragma unroll
            for (int e = g; e < g + CGRP; e++)
                asm volatile("atom.shared.add.u32 %0, [%1], %2;" : "=r"(old[e - g]) : "r"((e & 1) ? __dp2a_hi(bw[e >> 1], 0x08000008u, acc) : __dp2a_lo(bw[e >> 1], 0x08000008u, acc)), "r"(vw[e]) : "memory");
#pragma unroll
            for (int e = g; e < g + CGRP; e++) ov |= ~(old[e - g] ^ vw[e]) & (old[e - g] ^ (old[e - g] + vw[e]));
            if (__any_sync(0xffffffffu, ov & 0x80008000u)) {
#pragma unroll
                for (int e = g; e < g + CGRP; e++) c_wrap((e & 1) ? bw[e >> 1] >> 16 : bw[e >> 1] & 0xffffu, lane >> 4, old[e - g], vw[e]);
            }
        }
    }
};

__device__ __forceinline__ void c_role(const Prm& p, unsigned char* ring, int X, int c) {
    const int tid = threadIdx.x, lane = tid & 31, w = __shfl_sync(0xffffffffu, tid >> 5, 0);
    uint32_t* misc = (uint32_t*)(smem + S_MISC);
    Wts* wt = (Wts*)(smem + S_AUX);
    load_wts(p, wt);
    if (tid == 0) misc[6] = TAB_N;
    __syncthreads();
    if (w == 0) {
        float sc[4]; bool bad;
        wait_ge(&g_ctl.pieces_done, NPC);
        fence_acquire();
        get_scales(p, sc, bad);
        const float s = (lane & 2) ? ((lane & 1) ? sc[3] : sc[2]) : ((lane & 1) ? sc[1] : sc[0]);
        wt->ws[lane] *= s > 0.f ? 1.f / s : 0.f;
        int it = 0; uint32_t pb;
        while (!((pb = ld_relaxed(&g_ctl.pagebits)) >> 31)) backoff(it);
        misc[4] = X ? ~pb : pb;
    } else {
        const int r0 = (X * NCP + c) * ROWS_O, nr = min((int)ROWS_O, p.E - r0);
#pragma unroll 4
        for (int r = tid - 32; r < (int)ROWS_O / 2; r += THREADS - 32) {
            const uint32_t d2 = 2 * r < nr ? __ldg((const uint32_t*)(p.dist + r0) + r) : TAB_LO * 0x10001u;
            uint32_t e[2] = {(d2 & 0xffff) - TAB_LO, (d2 >> 16) - TAB_LO};
#pragma unroll
            for (int k = 0; k < 2; k++)
                if (e[k] >= TAB_N) {
                    const uint32_t d = e[k] + TAB_LO;
                    if ((d & 0x7f80) == 0x7f80) st_relaxed(&g_ctl.bad, 1);
                    e[k] = min(atomicAdd(&misc[6], 1u), 0xffffu);
                    if (e[k] < TAB_N + TAB_X) ((uint32_t*)(smem + C_TAB))[e[k] * 4] = d;
                }
            ((uint2*)(smem + C_WRAP))[r] = make_uint2(e[0] << 16 | 0x8888u, e[1] << 16 | 0x8888u);
        }
    }
    __syncthreads();
    if (w >= NP / 2) {
        const int nt = min(misc[6], (uint32_t)(TAB_N + TAB_X));
        for (int k = tid - NP * 16; k < nt; k += THREADS - NP * 16)
            ((uint4*)(smem + C_TAB))[k] = radial_bf16(wt, k < TAB_N ? TAB_LO + k : ((uint32_t*)(smem + C_TAB))[k * 4]);
        if (tid == THREADS - 1 && !DEV_FREE) {
            const uint32_t h = p.NS >> 1;
            const unsigned char* f = ring + (q_base(X, misc[4]) ^ slot_off(h % RB) ^ (OFF_REL + c * 4));
            for (int it = 0; ld_relaxed(f) < h / RB; it++) { __nanosleep(2000); if (it > SPIN_MAX) __trap(); }
            const int r0 = (X * NCP + c) * ROWS_O, nr = min((int)ROWS_O, p.E - r0);
            if (nr > 0) asm volatile("cp.async.bulk.prefetch.L2.global [%0], %1;" ::"l"(p.m + r0), "r"(nr * 8) : "memory");
        }
    }
    const uint32_t pagebits = misc[4];
    if (w >= NP / 2) return;
    CWork W;
    const int par = lane >> 4;
    W.ring = ring; W.lane = __shfl_sync(0xffffffffu, lane, lane); W.dev_free = DEV_FREE;
    const uint32_t qb = q_base(2 * w + X, pagebits), k = lane & 15;
    W.acc = __shfl_sync(0xffffffffu, SB + par * 4, lane);
    W.v_off = __shfl_sync(0xffffffffu, qb ^ (par * R_V1 + (c < 8 ? 0 : R_HI) + c * 256 + k * 16), lane);
    W.b_off = __shfl_sync(0xffffffffu, qb ^ (R_B + c * 128 + k * 8), lane);
    W.f_off = __shfl_sync(0xffffffffu, qb ^ (OFF_RDY + (lane % 6) * 4), lane);
    W.r_off = qb ^ (OFF_REL + c * 4);
    W.lap1 = 1; W.sv = W.sb = W.fw = W.stamp = 0; W.vtag = 0x20002000u;
    const uint32_t NT = p.NS + 2 * GR;
    CTask A, B;
    PROF_DECL
    bool da = W.issue<0>(A), db;
#pragma unroll 1
    for (uint32_t n = 2;; n += 2) {
        W.arrive<0>(A, da); PROF(1); db = W.issue<1>(B); PROF(0); W.add(A, da);
        W.arrive<1>(B, db);
        if (n >= NT) break;
        PROF(1); da = W.issue<0>(A); PROF(0); W.add(B, db);
    }
    W.add(B, db);
    PROF_END;
}

__device__ __forceinline__ uint32_t bf2_mul(uint32_t a, uint32_t b) { uint32_t r; asm("mul.rn.bf16x2 %0, %1, %2;" : "=r"(r) : "r"(a), "r"(b)); return r; }
__device__ __forceinline__ uint32_t bf2_fma(uint32_t a, uint32_t b, uint32_t c) { uint32_t r; asm("fma.rn.bf16x2 %0, %1, %2, %3;" : "=r"(r) : "r"(a), "r"(b), "r"(c)); return r; }
__device__ __forceinline__ uint32_t c_agg(uint32_t a, uint32_t s, uint32_t wr, bool wrapped) {
    int x0 = (short)a, x1 = ((int)a >> 16) + ((a >> 15) & 1);
    if (wrapped) { const int w0 = (int)(wr & 15) - 8, w1 = (int)((wr >> 4) & 15) - 8; x0 += 65536 * w0; x1 += 65536 * w1 - w0; }
    return pack_bf16((float)x1 * bf_hi(s), (float)x0 * bf_lo(s));
}
__device__ __forceinline__ void c_epilogue(const Prm& p, int X, int c) {
    const int tid = threadIdx.x, lane = tid & 31;
    const Wts* wt = (const Wts*)(smem + S_AUX);
    uint32_t bw[4];
#pragma unroll
    for (int k = 0; k < 4; k++) {
        const int col = (k >> 1) * 2 + ((lane >> 2) & 1), row = (k & 1) * 2;
        bw[k] = (lane >> 3) == (lane & 3) ? pack_bf16(wt->wu[(row + 1) * 4 + col], wt->wu[row * 4 + col]) : 0u;
    }
    const int r0 = (X * NCP + c) * ROWS_O, np = max(min((int)ROWS_O, p.E - r0), 0) / 2;
    const uint4* mp = (const uint4*)(p.m + r0);
    uint4* op = (uint4*)(p.out + r0);
    constexpr int EB = 5;
#pragma unroll 1
    for (int rb = tid; rb - lane < np; rb += EB * THREADS) {
        uint4 mr[EB];
#pragma unroll
        for (int k = 0; k < EB; k++) mr[k] = __ldg(mp + min(rb + k * THREADS, np - 1));
#pragma unroll
        for (int k = 0; k < EB; k++) {
            const int r = min(rb + k * THREADS, np - 1);
            const uint4 a = ((const uint4*)smem)[r];
            const uint2 wr = ((const uint2*)(smem + C_WRAP))[r];
            const uint4 t0 = ((const uint4*)(smem + C_TAB))[min(wr.x >> 16, (uint32_t)(TAB_N + TAB_X - 1))];
            const uint4 t1 = ((const uint4*)(smem + C_TAB))[min(wr.y >> 16, (uint32_t)(TAB_N + TAB_X - 1))];
            const bool wrapped = __any_sync(0xffffffffu, prmt(wr.x, wr.y, 0x5410) != 0x88888888u);
            uint32_t a0, a1, a2, a3;
            if (wrapped) { a0 = c_agg(a.x, t0.x, wr.x, true); a2 = c_agg(a.y, t0.y, wr.x >> 8, true); a1 = c_agg(a.z, t1.x, wr.y, true); a3 = c_agg(a.w, t1.y, wr.y >> 8, true); }
            else { a0 = c_agg(a.x, t0.x, 0, false); a2 = c_agg(a.y, t0.y, 0, false); a1 = c_agg(a.z, t1.x, 0, false); a3 = c_agg(a.w, t1.y, 0, false); }
            float u[8];
#pragma unroll
            for (int h = 0; h < 2; h++)
                asm("mma.sync.aligned.m16n8k16.row.col.f32.bf16.bf16.f32 {%0,%1,%2,%3}, {%4,%5,%6,%7}, {%8,%9}, {%10,%10,%10,%10};"
                    : "=f"(u[4 * h]), "=f"(u[4 * h + 1]), "=f"(u[4 * h + 2]), "=f"(u[4 * h + 3])
                    : "r"(a0), "r"(a1), "r"(a2), "r"(a3), "r"(bw[2 * h]), "r"(bw[2 * h + 1]), "f"(0.f));
            const uint4 o = make_uint4(bf2_fma(pack_bf16(u[1], u[0]), t0.z, mr[k].x), bf2_fma(pack_bf16(u[5], u[4]), t0.w, mr[k].y),
                                       bf2_fma(pack_bf16(u[3], u[2]), t1.z, mr[k].z), bf2_fma(pack_bf16(u[7], u[6]), t1.w, mr[k].w));
            if (rb + k * THREADS < np) op[r] = o;
        }
    }
    if (((const uint32_t*)(smem + S_MISC))[6] > TAB_N + TAB_X) {
        for (int r = 2 * tid; r < 2 * np; r += (r & 1) ? 2 * THREADS - 1 : 1) {
            const uint32_t wr = ((const uint32_t*)(smem + C_WRAP))[r];
            if ((wr >> 16) < TAB_N + TAB_X) continue;
            const uint4 t = radial_bf16(wt, __bfloat16_as_ushort(p.dist[r0 + r]));
            const uint2 a = ((const uint2*)smem)[r];
            const uint32_t a0 = c_agg(a.x, t.x, wr, true), a1 = c_agg(a.y, t.y, wr >> 8, true);
            const float agg[4] = {bf_lo(a0), bf_hi(a0), bf_lo(a1), bf_hi(a1)}, g[4] = {bf_lo(t.z), bf_hi(t.z), bf_lo(t.w), bf_hi(t.w)};
            p.out[r0 + r] = finish_row(wt->wu, agg, g, p.m[r0 + r]);
        }
    }
}

__device__ __forceinline__ void grid_bar(unsigned* ctr) {
    __syncthreads();
    if (threadIdx.x == 0) { fence_gpu(); red_add(ctr, 1); wait_ge(ctr, gridDim.x); fence_gpu(); }
    __syncthreads();
}
__device__ __noinline__ void fallback(const Prm& p) {
    const int gt = blockIdx.x * THREADS + threadIdx.x, gs = gridDim.x * THREADS;
    Wts* wt = (Wts*)smem;
    __syncthreads();
    load_wts(p, wt);
    for (int e = gt; e < p.E; e += gs) g_acc[e] = make_float4(0.f, 0.f, 0.f, 0.f);
    grid_bar(&g_ctl.bar[0]);
    const float f = __bfloat162float(p.freq[0]);
    for (int t = gt; t < p.T; t += gs) {
        uint2 r = __ldg(p.m + p.idx_in[t]);
        float c = rbf16(cosf(rbf16(f * __bfloat162float(p.angle[t]))));
        asm volatile("red.global.add.v4.f32 [%0], {%1,%2,%3,%4};" ::"l"(g_acc + p.idx_out[t]), "f"(bf_lo(r.x) * c),
                     "f"(bf_hi(r.x) * c), "f"(bf_lo(r.y) * c), "f"(bf_hi(r.y) * c) : "memory");
    }
    grid_bar(&g_ctl.bar[1]);
    for (int e = gt; e < p.E; e += gs) {
        float4 a4 = __ldcg(g_acc + e);
        float a[4] = {a4.x, a4.y, a4.z, a4.w}, s[4], g[4];
        radial(wt, __bfloat162float(p.dist[e]), s, g);
        float agg[4];
#pragma unroll
        for (int j = 0; j < 4; j++) agg[j] = s[j] * (a[0] * wt->wd[j] + a[1] * wt->wd[4 + j] + a[2] * wt->wd[8 + j] + a[3] * wt->wd[12 + j]);
        p.out[e] = finish_row(wt->wu, agg, g, p.m[e]);
    }
}

__device__ __forceinline__ void smem_init(bool isp, int from, int to) {
    for (int k = from / 16 + threadIdx.x; k < to / 16; k += THREADS) {
        const bool b = isp && k >= P_B / 16 && k < P_Q / 16;
        const uint32_t z = b ? (k & 7) * 0x20002u : 0u, y = b ? z + 0x10001u : 0u;
        ((uint4*)smem)[k] = make_uint4(z, z, y, y);
    }
}

__global__ void __launch_bounds__(THREADS, 1) gemnet_kernel(const __grid_constant__ Prm p) {
    const int tid = threadIdx.x, lane = tid & 31, w = __shfl_sync(0xffffffffu, tid >> 5, 0);
    uint32_t* misc = (uint32_t*)(smem + S_MISC);
    bool run_fallback = true;
    if (!p.force_bad && __cvta_generic_to_shared(smem) == SB) {
        unsigned char* const ring = p.ring;
        uint32_t smid; asm("mov.u32 %0, %%smid;" : "=r"(smid));
        const int cls = smid < NM ? 0 : (smid < NM + NP - 4 || (smid >= 124 && smid < 128)) ? 2 : 1;
        if (lane == 0) {
            if (w < 2 && (cls != 2 || blockIdx.x == 0)) misc[16 + w] = probe(ring + OFF_PROBE + w * 4096 + ((blockIdx.x >> 7) << 20) + (blockIdx.x & 127) * 32);
            else if (blockIdx.x == 0 && w <= NPAGES) misc[16 + w] = probe(ring + ((size_t)(w - 1) << 21) + OFF_PROBE);
        }
        float wd[16];
        if (cls != 2 || blockIdx.x == 0) __syncthreads();
        if (tid == 0) {
            int pool = cls == 2 ? 4 : cls * 2 + (misc[16] > misc[17]), id = 0;
            for (int k = 0; k < 7; k++) {
                int cap = pool < 2 ? NMP : pool < 4 ? NCP : NP;
                id = atomicAdd(&g_ctl.ticket[pool], 1);
                if (id < cap) break;
                pool = k == 0 ? (pool == 4 ? 0 : pool ^ 1) : k - 1;
            }
            misc[8] = pool; misc[9] = id;
            if (pool != 4) down_load(p, pool < 2 ? pool * NMP + id : NM + (pool - 2) * NCP + id);
        }
        if (blockIdx.x == 0 && tid == 32) {
            uint32_t pb = 0x80000000u;
            for (int k = 1; k < NPAGES; k++) pb |= (uint32_t)((2 * misc[17 + k] > misc[16] + misc[17]) != (misc[16] > misc[17])) << k;
            st_relaxed(&g_ctl.pagebits, pb);
        }
#pragma unroll
        for (int k = 0; k < 16; k++) wd[k] = __bfloat162float(p.w_down[k]);
        if (cls == 2) smem_init(true, 0, S_PC);
        __syncthreads();
        const int pool = misc[8], id = misc[9];
        if (pool >= 2 && (pool < 4 || cls != 2)) smem_init(pool == 4, 0, S_PC);
        if (pool != 4) down_piece(p, pool < 2 ? pool * NMP + id : NM + (pool - 2) * NCP + id, wd);
        if (DEV_FREE && !(DEV_FREE & (pool == 4 ? 1 : pool < 2 ? 2 : 4))) {
        } else if (pool == 4) {
            smem_init(true, S_PC, S_MISC);
            __syncthreads();
            if (tid < 2 * NBUF) {
                const uint32_t a = tid < NBUF ? bar_done(tid) : bar_free(tid), cnt = tid < NBUF ? CPS : 1;
                mbar_init(a, cnt);
                if (tid % NBUF < id % GR) asm volatile("mbarrier.arrive.shared.b64 _, [%0], %1;" ::"r"(a), "r"(cnt) : "memory");
            }
            __syncthreads();
            if (w < FW) p_filler(p, id, w);
            else if (w < FW + NF) {
                int it = 0; uint32_t pb;
                while (!((pb = ld_relaxed(&g_ctl.pagebits)) >> 31)) backoff(it);
                p_flusher(p, ring, __shfl_sync(0xffffffffu, pb, 0), id, w - FW);
            }
        } else if (pool < 2) {
            m_role(p, ring, pool, id);
        } else {
            c_role(p, ring, pool - 2, id);
        }
        __syncthreads();
        if (tid == 0) { fence_gpu(); red_add(&g_ctl.fin, 1); }
        if ((pool == 2 || pool == 3) && !DEV_FREE) c_epilogue(p, pool - 2, id);
        if (tid == 0) { wait_ge(&g_ctl.fin, NCTA); fence_gpu(); misc[10] = ld_relaxed(&g_ctl.bad); }
        __syncthreads();
        if (pool == 4) p_cleanup(ring, id);
        run_fallback = misc[10] && !DEV_FREE;
    }
    if (run_fallback) fallback(p);
    if (tid == 0) {
        fence_gpu();
        if (atomicAdd(&g_ctl.exited, 1) == gridDim.x - 1) {
            uint32_t* c = (uint32_t*)&g_ctl;
            for (int k = 0; k < 32; k++) c[k] = 0;
        }
    }
}

cudaTextureObject_t make_tex(const void* ptr, size_t bytes, int words) {
    cudaResourceDesc rd = {};
    rd.resType = cudaResourceTypeLinear;
    rd.res.linear.devPtr = (void*)ptr;
    rd.res.linear.desc = words == 4 ? cudaCreateChannelDesc<uint4>() : cudaCreateChannelDesc<uint2>();
    rd.res.linear.sizeInBytes = bytes;
    cudaTextureDesc td = {};
    td.readMode = cudaReadModeElementType;
    cudaTextureObject_t t = 0;
    if (cudaCreateTextureObject(&t, &rd, &td, nullptr) != cudaSuccess) { cudaGetLastError(); return 0; }
    return t;
}

}

extern "C" void kernel_launch(void* const* d_in, const int* in_sizes, int n_in, void* d_out, int out_size) {
    static Prm p = {};
    static int grid = 0;
    const int E = in_sizes[3], T = in_sizes[1];
    if (grid == 0 || p.idx_in != d_in[1] || p.idx_out != d_in[2] || p.angle != d_in[4] || p.E != E || p.T != T) {
        int dev = 0, sms = 0;
        cudaGetDevice(&dev);
        cudaDeviceGetAttribute(&sms, cudaDevAttrMultiProcessorCount, dev);
        cudaFuncSetAttribute(gemnet_kernel, cudaFuncAttributeMaxDynamicSharedMemorySize, SMEM_BYTES);
        p.E = E; p.T = T;
        p.NS = ((((T / 128 + NP * CB - 1) / (NP * CB)) * CB + CPS - 1) / CPS + 1) & ~1;
        void* rp = nullptr;
        cudaGetSymbolAddress(&rp, g_ring);
        p.ring = (unsigned char*)(((uintptr_t)rp + ((2u << 20) - 1)) & ~(uintptr_t)((2u << 20) - 1));
        bool fast = sms >= NCTA && E <= (int)FAST_E && (E & 1) == 0 && T >= 128 && T <= (1 << 29);
        if (fast) {
            p.t_in = make_tex(d_in[1], (size_t)(T / 128) * 512, 4);
            p.t_out = make_tex(d_in[2], (size_t)(T / 128) * 512, 4);
            p.t_ang = make_tex(d_in[4], (size_t)(T / 128) * 256, 2);
            fast = p.t_in && p.t_out && p.t_ang;
        }
        p.force_bad = !fast;
        grid = fast ? NCTA : sms;
    }
    p.m = (const uint2*)d_in[0];
    p.idx_in = (const int*)d_in[1];
    p.idx_out = (const int*)d_in[2];
    p.dist = (const __nv_bfloat16*)d_in[3];
    p.angle = (const __nv_bfloat16*)d_in[4];
    p.centers = (const __nv_bfloat16*)d_in[5];
    p.freq = (const __nv_bfloat16*)d_in[6];
    p.w_rbf = (const __nv_bfloat16*)d_in[7];
    p.w_sbf = (const __nv_bfloat16*)d_in[8];
    p.w_down = (const __nv_bfloat16*)d_in[9];
    p.w_up = (const __nv_bfloat16*)d_in[10];
    p.out = (uint2*)d_out;
    gemnet_kernel<<<grid, THREADS, SMEM_BYTES>>>(p);
}
```

```cpp
#include <cuda_runtime.h>
#include <cuda_bf16.h>
#include <stdint.h>

namespace {

constexpr int NI = 12;
constexpr int UN = 3;
constexpr int NG = NI / UN;
constexpr int GR = 2 * NG;
constexpr int NCP = 18;
constexpr int NO = 2 * NCP;
constexpr int KS = 64;
constexpr int NB = UN * NCP;
constexpr int NBUF = 10;
constexpr int NMP = 2 * NI;
constexpr int NP = 48, NM = 2 * NMP, NC = NO, NCTA = NP + NM + NC;
#define CPS_ 25
constexpr int CPS = CPS_;
#define FW_ 24
constexpr int FW = FW_;
constexpr int NF = 4;
#define RA_ 3
#define RV_ 3
#define RB_ 4
constexpr int RA = RA_, RV = RV_, RB = RB_;
#define QN_ 96
#define QTRIG_ 48
constexpr int QN = QN_, QTRIG = QTRIG_;
#define MW_ 18
constexpr int MW = MW_;
#define MPF_ 6
constexpr int MPF = MPF_;
constexpr int THREADS = 896, NW = THREADS / 32;
#define DEV_FREE 0
#define SLEEP_ 50

constexpr int RING_BYTES = NP << 20;
constexpr int NPAGES = RING_BYTES >> 21;
constexpr int MAX_E = 1 << 20;
constexpr int SMEM_BYTES = 232448;

constexpr int SB = 1024;

constexpr int P_CNT = 0;
constexpr int P_BAR = P_CNT + NBUF * NB * 4;
constexpr int P_TKT = P_BAR + 2 * NBUF * 8;
constexpr int P_B = (P_TKT + 128 + 127) / 128 * 128;
constexpr int P_Q = P_B + NBUF * NB * KS * 2;
constexpr int P_A = SMEM_BYTES - 256 - NBUF * NB * KS * 4;
static_assert(P_Q + FW * QN * 8 + 512 <= P_A && P_A % 128 == 0, "P smem");
constexpr int S_MISC = SMEM_BYTES - 256;
constexpr int S_AUX = S_MISC - 512;

constexpr unsigned FAST_E = 640000;
constexpr unsigned magic_of(unsigned long long d) { return (unsigned)(((1ull << 32) + d - 1) / d); }
constexpr bool magic_ok(unsigned long long d) { return (magic_of(d) * d - (1ull << 32)) * FAST_E < (1ull << 32); }
constexpr unsigned pick_rows(unsigned lo) {
    unsigned d = (lo + 3) & ~3u;
    while (!magic_ok(d)) d += 4;
    return d;
}
constexpr unsigned ROWS_I = pick_rows((FAST_E + NI - 1) / NI), ROWS_O = pick_rows((FAST_E + NO - 1) / NO);
constexpr unsigned MAG_I = magic_of(ROWS_I), MAG_O = magic_of(ROWS_O), HALF_O = ROWS_O * NCP;
constexpr int C_WRAP = ROWS_O * 8, C_TAB = ROWS_O * 12, TAB_N = 1025, TAB_LO = 0x3f80 - 1024, TAB_X = (S_AUX - C_TAB) / 16 - TAB_N;
static_assert(ROWS_I * 4 <= S_AUX && TAB_X >= 100 && ROWS_I <= 65536 && ROWS_O <= 32768, "tables");

constexpr int NPC = NM + NC;
constexpr int PC_ROWS = ((FAST_E + NPC - 1) / NPC + 3) & ~3;
constexpr int S_PC = C_WRAP + 128 - C_WRAP % 128;
static_assert(S_PC + PC_ROWS * 8 + 1024 <= S_AUX, "pre-pass");
struct __align__(128) Ctl {
    unsigned ticket[5];
    unsigned pagebits;
    unsigned pieces_done, late_done;
    unsigned bad;
    unsigned fin;
    unsigned bar[3];
    unsigned exited;
    unsigned late_n[NO];
    unsigned pad[64 - 14 - NO];
    float stat[NPC][8];
};

struct Prm {
    const uint2* m; const int* idx_in; const int* idx_out; const __nv_bfloat16* dist; const __nv_bfloat16* angle;
    const __nv_bfloat16* centers; const __nv_bfloat16* freq; const __nv_bfloat16* w_rbf; const __nv_bfloat16* w_sbf;
    const __nv_bfloat16* w_down; const __nv_bfloat16* w_up; uint2* out;
    cudaTextureObject_t t_in, t_out, t_ang;
    int E, T;
    unsigned char* ring;
    int NS;
    int force_bad;
};

__device__ __align__(128) unsigned char g_ring[RING_BYTES + (2 << 20)];
__device__ Ctl g_ctl;
constexpr int LATE_N = 2048;
__device__ uint4 g_late[NO][LATE_N];
__device__ float4 g_acc[MAX_E];
__device__ __align__(128) uint32_t g_md[2][NI * ROWS_I];
#define TS(k)
#define PROF_DECL
#define PROF(k)
#define PROF_END

extern __shared__ __align__(128) unsigned char smem[];

__device__ __forceinline__ float bf_lo(uint32_t w) { return __uint_as_float(w << 16); }
__device__ __forceinline__ float bf_hi(uint32_t w) { return __uint_as_float(w & 0xffff0000u); }
__device__ __forceinline__ float rbf16(float x) { return __bfloat162float(__float2bfloat16_rn(x)); }
__device__ __forceinline__ uint32_t pack_bf16(float hi, float lo) {
    uint32_t r; asm("cvt.rn.bf16x2.f32 %0, %1, %2;" : "=r"(r) : "f"(hi), "f"(lo)); return r;
}
__device__ __forceinline__ uint32_t prmt(uint32_t a, uint32_t b, uint32_t c) {
    uint32_t r; asm("prmt.b32 %0, %1, %2, %3;" : "=r"(r) : "r"(a), "r"(b), "r"(c)); return r;
}
__device__ __forceinline__ uint32_t ld_relaxed(const void* p) {
    uint32_t v; asm volatile("ld.relaxed.gpu.global.u32 %0, [%1];" : "=r"(v) : "l"(p) : "memory"); return v;
}
__device__ __forceinline__ uint2 ld_relaxed2(const void* p) {
    uint2 v; asm volatile("ld.relaxed.gpu.global.v2.u32 {%0,%1}, [%2];" : "=r"(v.x), "=r"(v.y) : "l"(p) : "memory"); return v;
}
__device__ __forceinline__ uint4 ld_relaxed4(const void* p) {
    uint4 v; asm volatile("ld.relaxed.gpu.global.v4.u32 {%0,%1,%2,%3}, [%4];" : "=r"(v.x), "=r"(v.y), "=r"(v.z), "=r"(v.w) : "l"(p) : "memory"); return v;
}
__device__ __forceinline__ void st_relaxed(void* p, uint32_t v) { asm volatile("st.relaxed.gpu.global.u32 [%0], %1;" ::"l"(p), "r"(v) : "memory"); }
__device__ __forceinline__ void st_relaxed16(void* p, uint32_t v) { asm volatile("st.relaxed.gpu.global.u16 [%0], %1;" ::"l"(p), "h"((uint16_t)v) : "memory"); }
__device__ __forceinline__ void red_add(void* p, uint32_t v) { asm volatile("red.relaxed.gpu.global.add.u32 [%0], %1;" ::"l"(p), "r"(v) : "memory"); }
__device__ __forceinline__ void fence_gpu() { asm volatile("fence.acq_rel.gpu;" ::: "memory"); }
__device__ __forceinline__ void fence_acquire() { asm volatile("fence.acquire.gpu;" ::: "memory"); }
__device__ __forceinline__ void fence_release() { asm volatile("fence.release.gpu;" ::: "memory"); }
__device__ __forceinline__ void mbar_init(uint32_t a, uint32_t n) { asm volatile("mbarrier.init.shared.b64 [%0], %1;" ::"r"(a), "r"(n) : "memory"); }
__device__ __forceinline__ void mbar_arrive(uint32_t a) { asm volatile("mbarrier.arrive.shared.b64 _, [%0];" ::"r"(a) : "memory"); }
__device__ __forceinline__ bool mbar_try(uint32_t a, uint32_t ph) {
    uint32_t ok;
    asm volatile("{.reg .pred p; mbarrier.try_wait.parity.shared.b64 p, [%1], %2, %3; selp.u32 %0, 1, 0, p;}" : "=r"(ok) : "r"(a), "r"(ph), "r"(2000) : "memory");
    return ok;
}
__device__ __forceinline__ bool mbar_test(uint32_t a, uint32_t ph) {
    uint32_t ok;
    asm volatile("{.reg .pred p; mbarrier.test_wait.parity.shared.b64 p, [%1], %2; selp.u32 %0, 1, 0, p;}" : "=r"(ok) : "r"(a), "r"(ph) : "memory");
    return ok;
}
constexpr int SPIN_MAX = 1 << 22;
__device__ __forceinline__ void mbar_wait(uint32_t a, uint32_t ph) {
    int it = 0;
    while (!mbar_try(a, ph)) { if (++it > SPIN_MAX) __trap(); }
}
__device__ __forceinline__ void backoff(int& it) { __nanosleep(SLEEP_); if (++it > SPIN_MAX) __trap(); }
__device__ __forceinline__ void wait_ge(const void* p, uint32_t v) {
    int it = 0;
    while (ld_relaxed(p) < v) backoff(it);
}

__device__ __forceinline__ bool elect_one() {
    uint32_t r; asm volatile("{.reg .pred p; elect.sync _|p, 0xffffffff; selp.u32 %0, 1, 0, p;}" : "=r"(r)); return r;
}
__device__ __forceinline__ void st_lane0(void* p, uint32_t v, int lane) {
    asm volatile("{.reg .pred p; setp.eq.s32 p, %2, 0; @p st.relaxed.gpu.global.u32 [%0], %1;}" ::"l"(p), "r"(v), "r"(lane) : "memory");
}
__device__ __forceinline__ void wait_all_ge(const void* p, uint32_t v) {
    int it = 0;
    while (!__all_sync(0xffffffffu, ld_relaxed(p) >= v)) backoff(it);
}
__device__ __forceinline__ void lds_lt(uint32_t& v, uint32_t ad, int a, int b) {
    asm volatile("{.reg .pred p; setp.lt.s32 p, %2, %3; @p ld.shared.u32 %0, [%1];}" : "+r"(v) : "r"(ad), "r"(a), "r"(b));
}

constexpr uint32_t R_V1 = 0x03000, R_A = 0x81000, R_B = 0x82000, R_UNIT = 0x4000, R_HI = 0x40000 - 8 * 256;
__device__ __forceinline__ uint32_t q_base(uint32_t q, uint32_t pagebits_x) { return (q << 20) | (((pagebits_x >> (q >> 1)) & 1u) << 12); }
__device__ __forceinline__ uint32_t slot_off(uint32_t s) { return (s << 16) | (((s + 1) & 2) << 11); }
constexpr uint32_t OFF_PF = R_B + 3 * R_UNIT, OFF_RDY = OFF_PF + 128, OFF_REL = OFF_PF + 256;
constexpr uint32_t OFF_PROBE = 3 * R_UNIT;
static_assert(RA <= 4 && RV <= 4 && RB <= 8 && RA <= RB && RV <= RB, "ring");

__device__ __forceinline__ uint32_t probe(unsigned char* p) {
    volatile uint32_t* sink = (volatile uint32_t*)(smem + S_MISC + 240);
    asm volatile("st.global.v4.u32 [%0], {%1,%1,%1,%1};" ::"l"(p), "r"(0) : "memory");
    asm volatile("st.global.v4.u32 [%0], {%1,%1,%1,%1};" ::"l"(p + 16), "r"(0) : "memory");
    uint32_t best = 0xffffffffu;
#pragma unroll 1
    for (int r = 0; r < 3; r++) {
        uint32_t t0, t1, v;
        asm volatile("mov.u32 %0, %%clock;" : "=r"(t0)::"memory");
        asm volatile("atom.relaxed.gpu.global.add.u32 %0, [%1], 1;" : "=r"(v) : "l"(p) : "memory");
        *sink = v;
        asm volatile("mov.u32 %0, %%clock;" : "=r"(t1)::"memory");
        best = min(best, t1 - t0);
    }
    return best;
}

struct Wts { float c[8], wr[32], ws[32], wd[16], wu[16]; };
__device__ __forceinline__ void load_wts(const Prm& p, Wts* w) {
    int t = threadIdx.x;
    if (t < 8) w->c[t] = __bfloat162float(p.centers[t]);
    if (t < 32) { w->wr[t] = __bfloat162float(p.w_rbf[t]); w->ws[t] = __bfloat162float(p.w_sbf[t]); }
    if (t < 16) { w->wd[t] = __bfloat162float(p.w_down[t]); w->wu[t] = __bfloat162float(p.w_up[t]); }
}
__device__ __forceinline__ void radial(const Wts* w, float d, float s[4], float g[4]) {
#pragma unroll
    for (int j = 0; j < 4; j++) s[j] = g[j] = 0.f;
#pragma unroll
    for (int r = 0; r < 8; r++) {
        float x = rbf16(d - w->c[r]);
        float b = rbf16(__expf(rbf16(-10.0f * rbf16(x * x))));
#pragma unroll
        for (int j = 0; j < 4; j++) { s[j] += b * w->ws[r * 4 + j]; g[j] += b * w->wr[r * 4 + j]; }
    }
}
__device__ __noinline__ uint4 radial_bf16(const Wts* w, uint32_t dbits) {
    float s[4], g[4];
    radial(w, __uint_as_float(dbits << 16), s, g);
    return make_uint4(pack_bf16(s[1], s[0]), pack_bf16(s[3], s[2]), pack_bf16(g[1], g[0]), pack_bf16(g[3], g[2]));
}
__device__ __forceinline__ uint2 finish_row(const float* wu, const float agg[4], const float g[4], uint2 r) {
    float o[4];
    const float mm[4] = {bf_lo(r.x), bf_hi(r.x), bf_lo(r.y), bf_hi(r.y)};
#pragma unroll
    for (int j = 0; j < 4; j++) o[j] = mm[j] + (agg[0] * wu[j] + agg[1] * wu[4 + j] + agg[2] * wu[8 + j] + agg[3] * wu[12 + j]) * g[j];
    return make_uint2(pack_bf16(o[1], o[0]), pack_bf16(o[3], o[2]));
}
__device__ __forceinline__ uint2 down_row(const float* wd, uint32_t x, uint32_t y) {
    const float a[4] = {bf_lo(x), bf_hi(x), bf_lo(y), bf_hi(y)};
    float d[4];
#pragma unroll
    for (int j = 0; j < 4; j++) d[j] = a[0] * wd[j] + a[1] * wd[4 + j] + a[2] * wd[8 + j] + a[3] * wd[12 + j];
    return make_uint2(pack_bf16(d[1], d[0]), pack_bf16(d[3], d[2]));
}

__device__ __forceinline__ void down_load(const Prm& p, int pc) {
    const int r0 = pc * PC_ROWS / 2, nr = max(min((pc + 1) * PC_ROWS, p.E) / 2 - r0, 0);
    const uint32_t bar = SB + S_MISC + 248;
    mbar_init(bar, 1);
    asm volatile("fence.proxy.async.shared::cta;" ::: "memory");
    asm volatile("mbarrier.arrive.expect_tx.shared.b64 _, [%0], %1;" ::"r"(bar), "r"(nr * 16) : "memory");
    for (int o = 0; o < nr; o += 640)
        asm volatile("cp.async.bulk.shared::cluster.global.mbarrier::complete_tx::bytes [%0], [%1], %2, [%3];"
                     ::"r"(SB + S_PC + o * 16), "l"((const uint4*)p.m + r0 + o), "r"(min(640, nr - o) * 16), "r"(bar) : "memory");
}
__device__ __forceinline__ void down_piece(const Prm& p, int pc, const float* wd) {
    const int tid = threadIdx.x, lane = tid & 31, w = tid >> 5;
    const int r0 = pc * PC_ROWS / 2, nr = max(min((pc + 1) * PC_ROWS, p.E) / 2 - r0, 0);
    mbar_wait(SB + S_MISC + 248, 0);
    uint32_t mx0 = 0, mx1 = 0; float ss[4] = {0.f, 0.f, 0.f, 0.f};
    for (int r = tid; r < nr; r += THREADS) {
        const uint4 v = ((const uint4*)(smem + S_PC))[r];
        const uint2 a = down_row(wd, v.x, v.y), b = down_row(wd, v.z, v.w);
        ((uint2*)g_md[0])[r0 + r] = make_uint2(a.x, b.x); ((uint2*)g_md[1])[r0 + r] = make_uint2(a.y, b.y);
        mx0 = __vimax3_u16x2(mx0, a.x & 0x7fff7fffu, b.x & 0x7fff7fffu); mx1 = __vimax3_u16x2(mx1, a.y & 0x7fff7fffu, b.y & 0x7fff7fffu);
        ss[0] += bf_lo(a.x) * bf_lo(a.x) + bf_lo(b.x) * bf_lo(b.x); ss[1] += bf_hi(a.x) * bf_hi(a.x) + bf_hi(b.x) * bf_hi(b.x);
        ss[2] += bf_lo(a.y) * bf_lo(a.y) + bf_lo(b.y) * bf_lo(b.y); ss[3] += bf_hi(a.y) * bf_hi(a.y) + bf_hi(b.y) * bf_hi(b.y);
    }
    uint32_t st[4] = {mx0 << 16, mx0 & 0xffff0000u, mx1 << 16, mx1 & 0xffff0000u};
    uint4* red = (uint4*)(smem + S_PC + PC_ROWS * 8);
    for (int pass = 0; pass < 2; pass++) {
#pragma unroll
        for (int ch = 0; ch < 4; ch++) {
            st[ch] = __reduce_max_sync(0xffffffffu, st[ch]);
#pragma unroll
            for (int o = 16; o; o >>= 1) ss[ch] += __shfl_xor_sync(0xffffffffu, ss[ch], o);
        }
        uint4* dst = pass ? (uint4*)g_ctl.stat[pc] : red + 2 * w;
        if (lane == 0) { dst[0] = make_uint4(st[0], st[1], st[2], st[3]); dst[1] = make_uint4(__float_as_uint(ss[0]), __float_as_uint(ss[1]), __float_as_uint(ss[2]), __float_as_uint(ss[3])); }
        if (pass) break;
        __syncthreads();
        const uint4 a = lane < NW ? red[2 * lane] : make_uint4(0, 0, 0, 0), b = lane < NW ? red[2 * lane + 1] : make_uint4(0, 0, 0, 0);
        __syncthreads();
        if (w != NW - 1) return;
        st[0] = a.x; st[1] = a.y; st[2] = a.z; st[3] = a.w;
        ss[0] = __uint_as_float(b.x); ss[1] = __uint_as_float(b.y); ss[2] = __uint_as_float(b.z); ss[3] = __uint_as_float(b.w);
    }
    if (lane == 0) { fence_release(); red_add(&g_ctl.pieces_done, 1); }
    __syncwarp();
}

__device__ __forceinline__ void get_scales(const Prm& p, float sc[4], bool& bad) {
    const int lane = threadIdx.x & 31;
    uint32_t mxb[4] = {0, 0, 0, 0};
    float ss[4] = {0.f, 0.f, 0.f, 0.f};
#pragma unroll
    for (int k = 0; k < (NPC + 31) / 32; k++) {
        if (lane + 32 * k < NPC) {
            const uint4 a = ld_relaxed4(&g_ctl.stat[lane + 32 * k][0]), b = ld_relaxed4(&g_ctl.stat[lane + 32 * k][4]);
            mxb[0] = max(mxb[0], a.x); mxb[1] = max(mxb[1], a.y); mxb[2] = max(mxb[2], a.z); mxb[3] = max(mxb[3], a.w);
            ss[0] += __uint_as_float(b.x); ss[1] += __uint_as_float(b.y); ss[2] += __uint_as_float(b.z); ss[3] += __uint_as_float(b.w);
        }
    }
    bad = false;
    const float kdeg = fminf(3.5f * sqrtf(fmaxf(0.5f * (float)p.T / (float)p.E, 1.0f)), 128.f);
#pragma unroll
    for (int ch = 0; ch < 4; ch++) {
        float mx = __uint_as_float(__reduce_max_sync(0xffffffffu, mxb[ch]));
#pragma unroll
        for (int o = 16; o; o >>= 1) ss[ch] += __shfl_xor_sync(0xffffffffu, ss[ch], o);
        float rms = sqrtf(ss[ch] / (float)p.E);
        float range = fmaxf(4.002f * mx, kdeg * rms);
        if (!(mx <= 1e15f) || !(range <= 128.f * rms) || (mx > 0.f && mx < 1e-15f)) bad = true;
        sc[ch] = range > 0.f ? 32767.f / range : 0.f;
    }
}

constexpr float MAG_LO = 12582912.f, MAG_HI = 12582912.f - 19264.f;
__device__ __forceinline__ uint32_t term(uint32_t m, float f_lo, float f_hi, float mag_lo, float mag_hi) {
    return (__float_as_uint(fmaf(bf_hi(m), f_hi, mag_hi)) << 16) + __float_as_uint(fmaf(bf_lo(m), f_lo, mag_lo));
}

constexpr int PER = 40;
__host__ __device__ constexpr uint32_t bar_done(uint32_t s) { return SB + P_BAR + (s % NBUF) * 16; }
__host__ __device__ constexpr uint32_t bar_free(uint32_t m) { return bar_done(m + NBUF - (GR - 1)) + 8; }
struct __align__(16) PTab { uint32_t e[PER][4]; };
constexpr PTab make_ptab() {
    PTab t = {};
    for (int s = 0; s < PER; s++) {
        for (int d = 0; d < GR; d++) {
            int gi = (s + d) % GR, buf = (s + d) % NBUF, X = gi & 1, g = gi >> 1;
            t.e[s][X] |= (uint32_t)(4 * UN * buf - g - 4 * X + 7) << (8 * g);
        }
        t.e[s][2] = bar_done(s);
        t.e[s][3] = (((s + GR - 1) / NBUF) & 1) ^ 1;
    }
    return t;
}
__constant__ PTab c_ptab = make_ptab();
constexpr int BIAS = 7 * NCP;
static_assert(NG == 4 && CPS >= FW, "group selection");

struct PCtx { uint32_t a0, a1; };
struct PElem { uint32_t b4, aw, ol, r2; };

__device__ __forceinline__ void p_bin(const PCtx& c, PElem& e, uint32_t i, uint32_t o) {
    uint32_t ib = __umulhi(i, MAG_I), ob = __umulhi(o, MAG_O), sel = ib & 3;
    asm("{.reg .pred p; setp.ge.u32 p, %1, %2; @p add.u32 %0, %0, 4;}" : "+r"(sel) : "r"(o), "n"(HALF_O));
    e.b4 = __dp4a(prmt(c.a0, c.a1, sel), (uint32_t)NCP, ib * NCP + ob * 4);
    e.aw = i - ib * ROWS_I;
    e.ol = o - ob * ROWS_O;
}
__device__ __forceinline__ void p_rank(PElem& e) {
    asm volatile("atom.shared.add.u32 %0, [%1+%2], 2;" : "=r"(e.r2) : "r"(e.b4), "n"(SB + P_CNT - BIAS) : "memory");
}
__device__ __forceinline__ void p_store(const PElem& e) {
    const uint32_t ab = e.b4 * (KS / 2) + e.r2;
    asm volatile("{.reg .pred p; setp.lt.u32 p, %4, %5; @p st.shared.u32 [%0+%6], %1; @p st.shared.u16 [%2+%7], %3;}"
                 ::"r"(ab * 2), "r"(e.aw), "r"(ab), "h"((uint16_t)e.ol), "r"(e.r2), "n"(KS * 2),
                   "n"(SB + P_A - BIAS * KS), "n"(SB + P_B - BIAS * (KS / 2)) : "memory");
}
__device__ __forceinline__ uint32_t cos2(uint32_t x) {
    x = __vminu2(x, 0x42804280u);
    return pack_bf16(__cosf(bf_hi(x)), __cosf(bf_lo(x)));
}

#define PD_ 2
#define CB_ 8
constexpr int CB = CB_;
struct PIn { uint4 i, o; uint2 a; };

struct PFill {
    PCtx c;
    uint32_t qb, qt, lt, f2, bar, par, xmax;
    uint32_t s0, lane, vb;
    bool open;
    __device__ __forceinline__ void fetch(const Prm& p, PIn& x, uint32_t ch) {
        const int v = ((ch & ~(CB - 1u)) * (NP - 1) + ch) * 32 + vb;
        asm volatile("{.reg .b32 d0, d1; tex.1d.v4.u32.s32 {%0,%1,d0,d1}, [%2, {%3}];}" : "=r"(x.a.x), "=r"(x.a.y) : "l"(p.t_ang), "r"(v));
        asm volatile("tex.1d.v4.u32.s32 {%0,%1,%2,%3}, [%4, {%5}];" : "=r"(x.i.x), "=r"(x.i.y), "=r"(x.i.z), "=r"(x.i.w) : "l"(p.t_in), "r"(v));
        asm volatile("tex.1d.v4.u32.s32 {%0,%1,%2,%3}, [%4, {%5}];" : "=r"(x.o.x), "=r"(x.o.y), "=r"(x.o.z), "=r"(x.o.w) : "l"(p.t_out), "r"(v));
    }
    __device__ __forceinline__ uint32_t ticket(uint32_t zero) {
        uint32_t t;
        asm volatile("atom.shared.add.u32 %0, [%1+%2], %3;" : "=r"(t) : "r"(lane * 4), "n"(SB + P_TKT), "r"((~lt & 1) | zero) : "memory");
        return t;
    }
    __device__ __forceinline__ uint32_t use_ticket(uint32_t t) {
        t = __reduce_or_sync(0xffffffffu, t);
        begin(t / CPS);
        return t + PD_ * FW;
    }
    __device__ __forceinline__ void begin(uint32_t step) {
        const uint4 t = ((const uint4*)c_ptab.e)[(step + s0) % PER];
        c.a0 = t.x; c.a1 = t.y; bar = t.z; par = t.w;
        open = mbar_test(bar + 8, par);
    }
    __device__ __forceinline__ void enter() { if (!open) mbar_wait(bar + 8, par); }
    __device__ __forceinline__ void end() {
        __syncwarp();
        asm volatile("{.reg .pred p; setp.eq.u32 p, %1, 0; @p mbarrier.arrive.shared.b64 _, [%0];}" ::"r"(bar), "r"(lt) : "memory");
    }
    __device__ __forceinline__ void push(bool f, uint32_t x, uint32_t y) {
        const uint32_t mask = __ballot_sync(0xffffffffu, f);
        asm volatile("{.reg .pred p; setp.ne.u32 p, %3, 0; @p st.shared.v2.u32 [%0], {%1,%2};}"
                     ::"r"(min(qt + __popc(mask & lt) * 8, qb + (QN - 1) * 8)), "r"(x), "r"(y), "r"((uint32_t)f) : "memory");
        qt += __popc(mask) * 8;
    }
    __device__ __forceinline__ void push3(bool f, uint32_t i, uint32_t o, uint32_t aw) { push(f, prmt(i, aw, 0x6210), prmt(o, aw, 0x7210)); }
    __device__ __forceinline__ uint32_t chunk(const PIn& x) {
        uint32_t x0, x1;
        const uint32_t tk = use_ticket(ticket(x.o.x >> 31));
        PElem e0, e1, e2, e3;
        p_bin(c, e0, x.i.x, x.o.x); p_bin(c, e1, x.i.y, x.o.y); p_bin(c, e2, x.i.z, x.o.z); p_bin(c, e3, x.i.w, x.o.w);
        asm volatile("" : "+r"(e0.b4), "+r"(e1.b4), "+r"(e2.b4), "+r"(e3.b4));
        enter();
        p_rank(e0); p_rank(e1); p_rank(e2); p_rank(e3);
        asm volatile("mul.rn.bf16x2 %0, %1, %2;" : "=r"(x0) : "r"(x.a.x), "r"(f2));
        asm volatile("mul.rn.bf16x2 %0, %1, %2;" : "=r"(x1) : "r"(x.a.y), "r"(f2));
        x0 &= 0x7fff7fffu; x1 &= 0x7fff7fffu;
        xmax = __vimax3_u16x2(xmax, x0, x1);
        const uint32_t c0 = cos2(x0), c1 = cos2(x1);
        e0.aw = prmt(e0.aw, c0, 0x5410); e1.aw = prmt(e1.aw, c0, 0x7610); e2.aw = prmt(e2.aw, c1, 0x5410); e3.aw = prmt(e3.aw, c1, 0x7610);
        p_store(e0); p_store(e1); p_store(e2); p_store(e3);
        if (qt - qb >= QTRIG * 8) retry(32);
        end();
        const uint32_t r01 = e0.r2 | e1.r2, r23 = e2.r2 | e3.r2;
        const bool f = (r01 | r23) >= KS * 2;
        if (__any_sync(0xffffffffu, f)) {
            const bool f0 = e0.r2 >= KS * 2, f1 = e1.r2 >= KS * 2, f2_ = e2.r2 >= KS * 2, f3 = e3.r2 >= KS * 2, f01 = r01 >= KS * 2;
            push3(f, f01 ? (f0 ? x.i.x : x.i.y) : (f2_ ? x.i.z : x.i.w), f01 ? (f0 ? x.o.x : x.o.y) : (f2_ ? x.o.z : x.o.w),
                  f01 ? (f0 ? e0.aw : e1.aw) : (f2_ ? e2.aw : e3.aw));
            const uint32_t s2 = max(max(min(e0.r2, e1.r2), min(e2.r2, e3.r2)), min(r01, r23));
            if (__any_sync(0xffffffffu, s2 >= KS * 2)) {
                push3(f1 && f0, x.i.y, x.o.y, e1.aw); push3(f2_ && f01, x.i.z, x.o.z, e2.aw); push3(f3 && (f01 || f2_), x.i.w, x.o.w, e3.aw);
            }
        }
        return tk;
    }
    __device__ __forceinline__ void retry(uint32_t take) {
        if (qt - qb > QN * 8) { st_relaxed(&g_ctl.bad, 1); qt = qb + QN * 8; }
        uint2 e, r, r1;
        __syncwarp();
        asm volatile("ld.shared.v2.u32 {%0,%1}, [%2];" : "=r"(e.x), "=r"(e.y) : "r"(qb + lane * 8) : "memory");
        asm volatile("ld.shared.v2.u32 {%0,%1}, [%2];" : "=r"(r.x), "=r"(r.y) : "r"(qb + (lane + take) * 8) : "memory");
        qt -= take * 8;
        const bool more = qt - qb > 256;
        if (more) asm volatile("ld.shared.v2.u32 {%0,%1}, [%2];" : "=r"(r1.x), "=r"(r1.y) : "r"(qb + (lane + take) * 8 + 256) : "memory");
        __syncwarp();
        if (more && qb + lane * 8 + 256 < qt) asm volatile("st.shared.v2.u32 [%0], {%1,%2};" ::"r"(qb + lane * 8 + 256), "r"(r1.x), "r"(r1.y) : "memory");
        if (qb + lane * 8 < qt) asm volatile("st.shared.v2.u32 [%0], {%1,%2};" ::"r"(qb + lane * 8), "r"(r.x), "r"(r.y) : "memory");
        PElem el;
        el.r2 = 0;
        if (take == 32 || lane < take) {
            p_bin(c, el, e.x & 0xffffffu, e.y & 0xffffffu);
            el.aw = prmt(el.aw, prmt(e.x, e.y, 0x0073), 0x5410);
            p_rank(el);
            p_store(el);
        }
        push(el.r2 >= KS * 2, e.x, e.y);
    }
};

__device__ __forceinline__ void p_filler(const Prm& p, int q, int w) {
    PFill F;
    const int lane = threadIdx.x & 31;
    const uint32_t NS = p.NS, cend = p.T >> 7, nv = NS * CPS, nc = cend / (NP * CB) * CB + min(max((int)(cend % (NP * CB)) - q * CB, 0), CB);
    static_assert(QN <= 96, "retry moves two batches");
    F.lt = __shfl_sync(0xffffffffu, (1u << lane) - 1u, lane);
    F.lane = __shfl_sync(0xffffffffu, lane, lane);
    F.vb = __shfl_sync(0xffffffffu, q * (32 * CB) + lane, lane);
    F.f2 = __shfl_sync(0xffffffffu, __bfloat16_as_ushort(p.freq[0]) * 0x10001u, 0);
    F.qb = F.qt = SB + P_Q + w * (QN * 8);
    F.s0 = q % GR; F.xmax = 0;
    uint32_t c0 = w, c1 = w + FW;
    PIn x0, x1;
    F.fetch(p, x0, c0);
#pragma unroll 1
    while (c0 < nc) {
        F.fetch(p, x1, c1);
        c0 = F.chunk(x0);
        if (c1 >= nc) break;
        F.fetch(p, x0, c0);
        c1 = F.chunk(x1);
    }
    int left = (c0 < nv) + (c1 < nv);
#pragma unroll 1
    while (left > 0) { left -= F.use_ticket(F.ticket(0)) >= nv; F.enter(); F.end(); }
    if (q == 0 && w < 8) {
        const int t = cend * 128 + w * 16 + lane;
        const bool f = t < p.T && lane < 16;
        uint32_t i = 0, o = 0, x = 0;
        if (f) { i = p.idx_in[t]; o = p.idx_out[t]; asm("mul.rn.bf16x2 %0, %1, %2;" : "=r"(x) : "r"(__bfloat16_as_ushort(p.angle[t]) * 0x10001u), "r"(F.f2)); }
        F.xmax = __vmaxu2(F.xmax, x & 0x7fff7fffu);
        if (F.qt - F.qb >= 32 * 8) { F.begin(NS); F.enter(); F.retry(32); }
        F.push3(f, i, o, cos2(x & 0x7fff7fffu));
    }
    F.begin(NS); F.enter();
    for (uint32_t nq = min((F.qt - F.qb) >> 3, (uint32_t)QN); nq > 0;) { uint32_t take = min(nq, 32u); F.retry(take); nq -= take; }
    F.end();
    if (CPS > FW && w < CPS - FW) F.end();
    if ((F.xmax + 0x3d803d80u) & 0x80008000u) st_relaxed(&g_ctl.bad, 1);
    if (F.qt != F.qb) {
        float sc[4]; bool bad;
        wait_ge(&g_ctl.pieces_done, NPC);
        fence_acquire();
        get_scales(p, sc, bad);
        __syncwarp();
        for (uint32_t a = F.qb + lane * 8; a < F.qt && !bad; a += 256) {
            uint2 e;
            asm volatile("ld.shared.v2.u32 {%0,%1}, [%2];" : "=r"(e.x), "=r"(e.y) : "r"(a) : "memory");
            const uint32_t i = e.x & 0xffffffu, o = e.y & 0xffffffu, ob = __umulhi(o, MAG_O);
            const float c = __uint_as_float(prmt(e.x, e.y, 0x7300) & 0xffff0000u);
            const uint32_t k = atomicAdd(&g_ctl.late_n[ob], 1);
            if (k < LATE_N) g_late[ob][k] = make_uint4(o - ob * ROWS_O, term(ld_relaxed(&g_md[0][i]), c * sc[0], c * sc[1], MAG_LO, MAG_HI),
                                                       term(ld_relaxed(&g_md[1][i]), c * sc[2], c * sc[3], MAG_LO, MAG_HI), 0);
            else st_relaxed(&g_ctl.bad, 1);
        }
    }
    asm volatile("bar.sync 2, %0;" ::"n"(FW * 32) : "memory");
    if (threadIdx.x == 0) { fence_release(); red_add(&g_ctl.late_done, 1); }
}

template <int N> __device__ __forceinline__ void p_stamp(const uint32_t (&st)[N], uint32_t off, uint32_t bit, bool set) {
    if (set) {
#pragma unroll
        for (int j = 0; j < N; j++) asm volatile("red.shared.or.b32 [%0], %1;" ::"r"(st[j] + off), "r"(bit) : "memory");
    } else {
#pragma unroll
        for (int j = 0; j < N; j++) asm volatile("red.shared.and.b32 [%0], %1;" ::"r"(st[j] + off), "r"(~bit) : "memory");
    }
}
__device__ __forceinline__ void bulk_store(void* dst, uint32_t src, uint32_t bytes) {
    asm volatile("cp.async.bulk.global.shared::cta.bulk_group [%0], [%1], %2;" ::"l"(dst), "r"(src), "r"(bytes) : "memory");
}
__device__ __forceinline__ void p_flusher(const Prm& p, unsigned char* ring, uint32_t pagebits, int q, int f) {
    const int lane = threadIdx.x & 31;
    const uint32_t NS = p.NS, NT = NS + GR, s0 = q % GR;
    uint32_t sta[4], stb[2];
#pragma unroll
    for (int j = 0; j < 4; j++) {
        const int pp = min(8 * j + (lane >> 2), 26), bin = min(32 * j + lane, NB - 1);
        sta[j] = SB + P_A + pp * 512 + (lane & 3) * 160 + ((pp % 9) & 3) * 4;
        if (j < 2) stb[j] = SB + P_B + bin * 128 + ((bin % NCP) & 15) * 8;
    }
    const uint32_t pfo = OFF_PF + (lane / 6) * 32 + (lane & 1) * 16 + ((lane % 6) >> 1) * 4, pfc = (lane >> 1) * 6 + (lane & 1);
    const uint32_t wto = lane < NCP ? OFF_REL + lane * 4 : OFF_RDY + (lane % 6) * 4;
    PROF_DECL
#pragma unroll 1
    for (uint32_t n = f; n < NT; n += NF) {
        const uint32_t buf = (n + s0) % NBUF, h = n >> 1, lap = h / RB;
        const uint32_t qb = q_base(q, pagebits) ^ (((n + q) & 1) << 12), bb = qb ^ slot_off(h % RB);
        if (h >= RA && !DEV_FREE) {
            const uint32_t hw = lane < NCP ? h : h + RB - RA;
            wait_all_ge(ring + (qb ^ slot_off(hw % RB) ^ wto), (hw / RB) << (lane < NCP ? 0 : 1));
        }
        PROF(0);
#pragma unroll
        for (int d = 2; d >= 0; d--) {
            const int nl = (int)min(n, NS) - d;
            if (nl >= 0) mbar_wait(bar_done(nl + s0), ((nl + s0) / NBUF) & 1);
        }
        PROF(1);
        uint32_t* cnt = (uint32_t*)(smem + P_CNT) + buf * NB;
        bool any = true;
        if (n >= NS) any = __any_sync(0xffffffffu, lane < NCP && (cnt[lane] | cnt[NCP + lane] | cnt[2 * NCP + lane]));
        if (any) {
            const uint32_t oa = buf * (NB * KS * 4), ob = buf * (NB * KS * 2);
            unsigned char* da = ring + (qb ^ slot_off(h % RA) ^ R_A);
            unsigned char* db = ring + (bb ^ R_B);
            p_stamp(sta, oa, 0x40000000u, (h / RA) & 1);
            p_stamp(stb, ob, 0x8000u, lap & 1);
            __syncwarp();
            if (elect_one()) {
                asm volatile("fence.proxy.async.shared::cta;" ::: "memory");
#pragma unroll
                for (int u = 0; u < UN; u++) {
                    bulk_store(da + u * R_UNIT, SB + P_A + oa + u * (NCP * KS * 4), 8 * KS * 4);
                    bulk_store(da + u * R_UNIT + 0x40000, SB + P_A + oa + (u * NCP + 8) * (KS * 4), (NCP - 8) * KS * 4);
                }
#pragma unroll
                for (int u = 0; u < UN; u++) bulk_store(db + u * R_UNIT, SB + P_B + ob + u * (NCP * KS * 2), NCP * KS * 2);
            }
            __syncwarp();
        }
        uint32_t wm = ((lap + 1) << 22) | ((uint32_t)any << 21);
        if (lane < NCP) {
#pragma unroll
            for (int u = 0; u < 3; u++) wm |= min(cnt[pfc + 2 * u] >> 1, (uint32_t)KS) << (7 * u);
        }
        __syncwarp();
        if (lane < NB / 2) ((uint2*)cnt)[lane] = make_uint2(0, 0);
        PROF(3);
        asm volatile("cp.async.bulk.commit_group;" ::: "memory");
        asm volatile("cp.async.bulk.wait_group 0;" ::: "memory");
        __syncwarp();
        PROF(2);
        const bool safe = h < RB || n >= NS;
        if (!safe && lane < NCP) st_relaxed(ring + (bb ^ pfo), wm);
        if (n > 0) mbar_wait(bar_free(n - 1 + s0), ((n - 1 + s0) / NBUF) & 1);
        if (lane == 0) mbar_arrive(bar_free(buf));
        if (safe) {
            if (any) fence_release();
            if (lane < NCP) st_relaxed(ring + (bb ^ pfo), wm);
        }
        PROF(4);
    }
    PROF_END;
}
__device__ __forceinline__ void p_cleanup(unsigned char* ring, int q) {
    const int k = threadIdx.x / 24;
    if (k < 2 * RB) *(uint4*)(ring + ((q << 20) ^ ((k & 1) << 12) ^ slot_off(k >> 1) ^ OFF_PF) + (threadIdx.x % 24) * 16) = make_uint4(0, 0, 0, 0);
}

__device__ __forceinline__ void m_role(const Prm& p, unsigned char* ring, int X, int id) {
    const int tid = threadIdx.x, lane = tid & 31, w = __shfl_sync(0xffffffffu, tid >> 5, 0);
    const int ib = id >> 1, ty = id & 1;
    float* scs = (float*)(smem + S_MISC);
    if (w == 0) {
        const uint32_t bar = SB + S_AUX;
        if (lane == 0) mbar_init(bar, 1);
        wait_ge(&g_ctl.pieces_done, NPC);
        fence_acquire();
        if (lane == 0) {
            asm volatile("fence.proxy.async.global;" ::: "memory");
            asm volatile("fence.proxy.async.shared::cta;" ::: "memory");
            asm volatile("mbarrier.arrive.expect_tx.shared.b64 _, [%0], %1;" ::"r"(bar), "r"(ROWS_I * 4) : "memory");
            constexpr uint32_t PART = (ROWS_I * 4 / 8 + 127) / 128 * 128;
            for (uint32_t o = 0; o < ROWS_I * 4; o += PART)
                asm volatile("cp.async.bulk.shared::cluster.global.mbarrier::complete_tx::bytes [%0], [%1], %2, [%3];"
                             ::"r"(SB + o), "l"((const char*)(g_md[ty] + ib * ROWS_I) + o), "r"(min(PART, ROWS_I * 4 - o)), "r"(bar) : "memory");
        }
        __syncwarp();
            float sc[4]; bool bad;
        get_scales(p, sc, bad);
            if (bad) { st_relaxed(&g_ctl.bad, 1); sc[0] = sc[1] = sc[2] = sc[3] = 0.f; }
        int it = 0; uint32_t pb;
        while (!((pb = ld_relaxed(&g_ctl.pagebits)) >> 31)) backoff(it);
        if (lane == 0) { scs[0] = sc[0]; scs[1] = sc[1]; scs[2] = sc[2]; scs[3] = sc[3]; ((uint32_t*)scs)[4] = X ? ~pb : pb; ((uint32_t*)scs)[5] = bad; }
        mbar_wait(bar, 0);
    }
    __syncthreads();
    if (((uint32_t*)scs)[5]) {
        for (int k = tid; k < (int)ROWS_I; k += THREADS) ((uint32_t*)smem)[k] = 0;
        __syncthreads();
    }
    const uint32_t NT = p.NS + GR;
    if (w >= MW) return;
    const uint32_t pagebits = ((uint32_t*)scs)[4];
    const int half = lane >> 4, k4 = (lane & 15) * 4;
    const float s_lo = scs[2 * ty], s_hi = scs[2 * ty + 1];
    const int il = ib / NG, gi = (ib % NG) * 2 + X;
    const uint32_t a_off = R_A + il * R_UNIT + lane * 16, v_off = ty * R_V1 + il * R_UNIT + lane * 16;
    const uint32_t f_off = OFF_PF + il * 32 + half * 16, r_off = OFF_REL + (lane % NCP) * 4;
    const uint32_t j = w % (NP / GR);
    PROF_DECL
#pragma unroll 1
    for (uint32_t n = w / (NP / GR); n < NT; n += MW / (NP / GR)) {
        const uint32_t q = ((gi - n) & (GR - 1)) + GR * j, h = n >> 1;
        const uint32_t qb = q_base(q, pagebits), bb = qb ^ slot_off(h % RB);
        const uint32_t tag = (h / RB + 1) << 22;
        uint4 cw; int it = 0;
        while (true) {
            cw = ld_relaxed4(ring + (bb ^ f_off));
            if (__all_sync(0xffffffffu, min(min(cw.x, cw.y), cw.z) >= tag)) break;
            if (DEV_FREE) { cw.x = (cw.x & 1) + (63 | 57 << 7 | 50 << 14 | 1 << 21); cw.y = (cw.y & 1) + (53 | 61 << 7 | 57 << 14); cw.z = (cw.z & 1) + (59 | 52 << 7 | 57 << 14); break; }
            backoff(it);
        }
        PROF(0);
        if (__any_sync(0xffffffffu, cw.x & (1u << 21))) {
            const unsigned char* pa = ring + (qb ^ slot_off(h % RA) ^ a_off);
            unsigned char* pv = ring + (qb ^ slot_off(h % RV) ^ v_off);
            const uint32_t hv = h + RB - RV;
            const unsigned char* prel = ring + (qb ^ slot_off(hv % RB) ^ r_off);
            const uint32_t rel = ld_relaxed(prel);
            const uint32_t vlap = h / RV;
            const float mag_lo0 = MAG_LO + (float)(8192 + (vlap & 3) * 16384), mag_hi0 = MAG_HI + (float)(8192 + ((vlap >> 2) & 3) * 16384);
            const uint32_t stamp = ((h / RA) & (0x40100401u >> lane) & 1) << 30;
            uint4 a[9];
#define M_LOAD(ps) a[ps] = ld_relaxed4(pa + (ps) * 512 + ((ps) < 4 ? 0 : R_HI))
#pragma unroll
            for (int ps = 0; ps < MPF; ps++) M_LOAD(ps);
            if (!__all_sync(0xffffffffu, rel >= hv / RB) && !DEV_FREE) wait_all_ge(prel, hv / RB);
            PROF(3);
#pragma unroll
            for (int ps = 0; ps < 9; ps++) {
                const int rem = (int)(((ps < 3 ? cw.x : ps < 6 ? cw.y : cw.z) >> (7 * (ps % 3))) & 0x7f) - k4;
                if (ps % 3 == 0) {
#define M_STAMP(ps) (((ps) & 3) == 0 ? a[ps].x : ((ps) & 3) == 1 ? a[ps].y : ((ps) & 3) == 2 ? a[ps].z : a[ps].w)
                    while (true) {
                        M_STAMP(ps) ^= stamp; M_STAMP(ps + 1) ^= stamp; M_STAMP(ps + 2) ^= stamp;
                        if (!__any_sync(0xffffffffu, (M_STAMP(ps) | M_STAMP(ps + 1) | M_STAMP(ps + 2)) & 0x40000000u)) break;
                        if (DEV_FREE) { M_STAMP(ps) &= 0xbfffffffu; M_STAMP(ps + 1) &= 0xbfffffffu; M_STAMP(ps + 2) &= 0xbfffffffu; break; }
                        if (++it > SPIN_MAX) __trap();
                        M_LOAD(ps); M_LOAD(ps + 1); M_LOAD(ps + 2);
                    }
                }
                uint32_t aw[4] = {a[ps].x, a[ps].y, a[ps].z, a[ps].w}, mv[4], vw[4];
#pragma unroll
                for (int e = 0; e < 4; e++) { mv[e] = 0; lds_lt(mv[e], __dp2a_lo(aw[e], 4u, (uint32_t)SB), e, rem); }
#pragma unroll
                for (int e = 0; e < 4; e++) {
                    const float c = bf_hi(aw[e]);
                    vw[e] = term(mv[e], c * s_lo, c * s_hi, e ? MAG_LO : mag_lo0, e ? MAG_HI : mag_hi0);
                }
                asm volatile("st.global.v4.u32 [%0], {%1,%2,%3,%4};" ::"l"(pv + ps * 512 + (ps < 4 ? 0 : R_HI)), "r"(vw[0]), "r"(vw[1]), "r"(vw[2]), "r"(vw[3]) : "memory");
                if (ps + MPF < 9) M_LOAD(ps + MPF);
            }
            if (vlap == 0 || n >= p.NS) fence_release();
        }
        st_lane0(ring + (bb ^ (OFF_RDY + (2 * il + ty) * 4)), cw.x >> 21, lane);
        PROF(1);
    }
    PROF_END;
}

__device__ __noinline__ void c_wrap(uint32_t row, int par, uint32_t old, uint32_t w) {
    const uint32_t nw = old + w, ov = ~(old ^ w) & (old ^ nw);
    int d = 0;
    if (ov & 0x8000u) d += (w & 0x8000u) ? -1 : 1;
    if (ov & 0x80000000u) d += (w & 0x80000000u) ? -16 : 16;
    if (d != 0) {
        uint32_t c;
        asm volatile("atom.shared.add.u32 %0, [%1], %2;" : "=r"(c) : "r"(SB + C_WRAP + row * 4), "r"(d << (8 * par)) : "memory");
        c = (c >> (8 * par)) + d;
        if (((c + 1) & 0xe) == 0 || ((c + 16) & 0xe0) == 0) st_relaxed(&g_ctl.bad, 1);
    }
}

#define CGRP 4
struct CTask { uint4 v[3]; uint2 b[3]; };
struct CWork {
    unsigned char* ring;
    uint32_t v_off, b_off, f_off, r_off, acc;
    uint32_t lap1, sv, sb, vtag, fw, stamp;
    int lane, dev_free;
    template <int ODD> __device__ __forceinline__ bool issue(CTask& t) {
        if (!__all_sync(0xffffffffu, fw >= 2 * lap1)) {
            int it = 0;
            do {
                if (dev_free) { fw = 1; break; }
                backoff(it);
                fw = ld_relaxed(ring + (f_off ^ slot_off(sb) ^ (ODD << 20)));
            } while (!__all_sync(0xffffffffu, fw >= 2 * lap1));
        }
        const bool data = __any_sync(0xffffffffu, fw & 1);
        if (data) {
            const unsigned char* pv = ring + (v_off ^ slot_off(sv) ^ (ODD << 20));
            const unsigned char* pb = ring + (b_off ^ slot_off(sb) ^ (ODD << 20));
#pragma unroll
            for (int ps = 0; ps < 3; ps++) {
                t.v[ps] = ld_relaxed4(pv + ps * R_UNIT);
                t.b[ps] = ld_relaxed2(pb + ps * R_UNIT);
            }
        }
        fw = ld_relaxed(ring + (f_off ^ slot_off(ODD ? (sb + 1 == RB ? 0 : sb + 1) : sb) ^ (!ODD << 20)));
        return data;
    }
    template <int ODD> __device__ __forceinline__ void arrive(CTask& t, bool data) {
        if (data) {
            int it = 0;
            while (true) {
#pragma unroll
                for (int ps = 0; ps < 3; ps++) t.b[ps].x ^= stamp;
                if (!__any_sync(0xffffffffu, (((t.v[0].x ^ vtag) | (t.v[1].x ^ vtag) | (t.v[2].x ^ vtag)) & 0xc000c000u) | ((t.b[0].x | t.b[1].x | t.b[2].x) & 0x8000u))) break;
                if (dev_free) { for (int ps = 0; ps < 3; ps++) { t.v[ps].x = (t.v[ps].x & 0x3fff3fffu) | (vtag & 0xc000c000u); t.b[ps].x &= 0xffff7fffu; } break; }
                if (++it > SPIN_MAX) __trap();
#pragma unroll
                for (int ps = 0; ps < 3; ps++) {
                    t.v[ps] = ld_relaxed4(ring + (v_off ^ slot_off(sv) ^ (ODD << 20)) + ps * R_UNIT);
                    t.b[ps] = ld_relaxed2(ring + (b_off ^ slot_off(sb) ^ (ODD << 20)) + ps * R_UNIT);
                }
            }
#pragma unroll
            for (int ps = 0; ps < 3; ps++) t.v[ps].x -= vtag;
        }
        st_lane0(ring + (r_off ^ slot_off(sb) ^ (ODD << 20)), lap1, lane);
        if (ODD) {
            if (++sv == RV) { sv = 0; vtag += 0x4000u; if (vtag & 0x10000u) vtag += 0x3fff0000u; }
            if (++sb == RB) { sb = 0; lap1++; stamp ^= (((b_off >> 3) ^ (b_off >> 7)) & 15) == 0 ? 0x8000u : 0u; }
        }
    }
    __device__ __forceinline__ void add(const CTask& t, bool data) {
        if (!data) return;
        const uint32_t vw[12] = {t.v[0].x, t.v[0].y, t.v[0].z, t.v[0].w, t.v[1].x, t.v[1].y, t.v[1].z, t.v[1].w, t.v[2].x, t.v[2].y, t.v[2].z, t.v[2].w};
        const uint32_t bw[6] = {t.b[0].x, t.b[0].y, t.b[1].x, t.b[1].y, t.b[2].x, t.b[2].y};
#pragma unroll
        for (int g = 0; g < 12; g += CGRP) {
            uint32_t old[CGRP], ov = 0;
#pragma unroll
            for (int e = g; e < g + CGRP; e++)
                asm volatile("atom.shared.add.u32 %0, [%1], %2;" : "=r"(old[e - g]) : "r"((e & 1) ? __dp2a_hi(bw[e >> 1], 0x08000008u, acc) : __dp2a_lo(bw[e >> 1], 0x08000008u, acc)), "r"(vw[e]) : "memory");
#pragma unroll
            for (int e = g; e < g + CGRP; e++) ov |= ~(old[e - g] ^ vw[e]) & (old[e - g] ^ (old[e - g] + vw[e]));
            if (__any_sync(0xffffffffu, ov & 0x80008000u)) {
#pragma unroll
                for (int e = g; e < g + CGRP; e++) c_wrap((e & 1) ? bw[e >> 1] >> 16 : bw[e >> 1] & 0xffffu, lane >> 4, old[e - g], vw[e]);
            }
        }
    }
};

__device__ __forceinline__ void c_role(const Prm& p, unsigned char* ring, int X, int c) {
    const int tid = threadIdx.x, lane = tid & 31, w = __shfl_sync(0xffffffffu, tid >> 5, 0);
    uint32_t* misc = (uint32_t*)(smem + S_MISC);
    Wts* wt = (Wts*)(smem + S_AUX);
    load_wts(p, wt);
    if (tid == 0) misc[6] = TAB_N;
    __syncthreads();
    if (w == 0) {
        float sc[4]; bool bad;
        wait_ge(&g_ctl.pieces_done, NPC);
        fence_acquire();
        get_scales(p, sc, bad);
        const float s = (lane & 2) ? ((lane & 1) ? sc[3] : sc[2]) : ((lane & 1) ? sc[1] : sc[0]);
        wt->ws[lane] *= s > 0.f ? 1.f / s : 0.f;
        int it = 0; uint32_t pb;
        while (!((pb = ld_relaxed(&g_ctl.pagebits)) >> 31)) backoff(it);
        misc[4] = X ? ~pb : pb;
    } else {
        const int r0 = (X * NCP + c) * ROWS_O, nr = min((int)ROWS_O, p.E - r0);
#pragma unroll 4
        for (int r = tid - 32; r < (int)ROWS_O / 2; r += THREADS - 32) {
            const uint32_t d2 = 2 * r < nr ? __ldg((const uint32_t*)(p.dist + r0) + r) : TAB_LO * 0x10001u;
            uint32_t e[2] = {(d2 & 0xffff) - TAB_LO, (d2 >> 16) - TAB_LO};
#pragma unroll
            for (int k = 0; k < 2; k++)
                if (e[k] >= TAB_N) {
                    const uint32_t d = e[k] + TAB_LO;
                    if ((d & 0x7f80) == 0x7f80) st_relaxed(&g_ctl.bad, 1);
                    e[k] = min(atomicAdd(&misc[6], 1u), 0xffffu);
                    if (e[k] < TAB_N + TAB_X) ((uint32_t*)(smem + C_TAB))[e[k] * 4] = d;
                }
            ((uint2*)(smem + C_WRAP))[r] = make_uint2(e[0] << 16 | 0x8888u, e[1] << 16 | 0x8888u);
        }
    }
    __syncthreads();
    if (w >= NP / 2) {
        const int nt = min(misc[6], (uint32_t)(TAB_N + TAB_X));
        for (int k = tid - NP * 16; k < nt; k += THREADS - NP * 16)
            ((uint4*)(smem + C_TAB))[k] = radial_bf16(wt, k < TAB_N ? TAB_LO + k : ((uint32_t*)(smem + C_TAB))[k * 4]);
        if (DEV_FREE) return;
        for (int it = 0; ld_relaxed(&g_ctl.late_done) == 0; it++) { __nanosleep(1000); if (it > SPIN_MAX) __trap(); }
        const int ob = X * NCP + c, nr = min((int)ROWS_O, p.E - ob * (int)ROWS_O);
        if (tid == THREADS - 1 && nr > 0) asm volatile("cp.async.bulk.prefetch.L2.global [%0], %1;" ::"l"(p.m + ob * ROWS_O), "r"(nr * 8) : "memory");
        for (int it = 0; ld_relaxed(&g_ctl.late_done) < NP; it++) { __nanosleep(300); if (it > SPIN_MAX) __trap(); }
        fence_acquire();
        for (uint32_t k = tid - NP * 16, n = min(ld_relaxed(&g_ctl.late_n[ob]), (uint32_t)LATE_N); k < n; k += THREADS - NP * 16) {
            const uint4 e = ld_relaxed4(&g_late[ob][k]);
            c_wrap(e.x, 0, atomicAdd((uint32_t*)smem + 2 * e.x, e.y), e.y);
            c_wrap(e.x, 1, atomicAdd((uint32_t*)smem + 2 * e.x + 1, e.z), e.z);
        }
    }
    const uint32_t pagebits = misc[4];
    if (w >= NP / 2) return;
    CWork W;
    const int par = lane >> 4;
    W.ring = ring; W.lane = __shfl_sync(0xffffffffu, lane, lane); W.dev_free = DEV_FREE;
    const uint32_t qb = q_base(2 * w + X, pagebits), k = lane & 15;
    W.acc = __shfl_sync(0xffffffffu, SB + par * 4, lane);
    W.v_off = __shfl_sync(0xffffffffu, qb ^ (par * R_V1 + (c < 8 ? 0 : R_HI) + c * 256 + k * 16), lane);
    W.b_off = __shfl_sync(0xffffffffu, qb ^ (R_B + c * 128 + k * 8), lane);
    W.f_off = __shfl_sync(0xffffffffu, qb ^ (OFF_RDY + (lane % 6) * 4), lane);
    W.r_off = qb ^ (OFF_REL + c * 4);
    W.lap1 = 1; W.sv = W.sb = W.fw = W.stamp = 0; W.vtag = 0x20002000u;
    const uint32_t NT = p.NS + GR;
    CTask A, B;
    PROF_DECL
    bool da = W.issue<0>(A), db;
#pragma unroll 1
    for (uint32_t n = 2;; n += 2) {
        W.arrive<0>(A, da); PROF(1); db = W.issue<1>(B); PROF(0); W.add(A, da);
        W.arrive<1>(B, db);
        if (n >= NT) break;
        PROF(1); da = W.issue<0>(A); PROF(0); W.add(B, db);
    }
    W.add(B, db);
    PROF_END;
}

__device__ __forceinline__ uint32_t bf2_mul(uint32_t a, uint32_t b) { uint32_t r; asm("mul.rn.bf16x2 %0, %1, %2;" : "=r"(r) : "r"(a), "r"(b)); return r; }
__device__ __forceinline__ uint32_t bf2_fma(uint32_t a, uint32_t b, uint32_t c) { uint32_t r; asm("fma.rn.bf16x2 %0, %1, %2, %3;" : "=r"(r) : "r"(a), "r"(b), "r"(c)); return r; }
__device__ __forceinline__ uint32_t c_agg(uint32_t a, uint32_t s, uint32_t wr, bool wrapped) {
    int x0 = (short)a, x1 = ((int)a >> 16) + ((a >> 15) & 1);
    if (wrapped) { const int w0 = (int)(wr & 15) - 8, w1 = (int)((wr >> 4) & 15) - 8; x0 += 65536 * w0; x1 += 65536 * w1 - w0; }
    return pack_bf16((float)x1 * bf_hi(s), (float)x0 * bf_lo(s));
}
__device__ __forceinline__ void c_epilogue(const Prm& p, int X, int c) {
    const int tid = threadIdx.x, lane = tid & 31;
    const Wts* wt = (const Wts*)(smem + S_AUX);
    uint32_t bw[4];
#pragma unroll
    for (int k = 0; k < 4; k++) {
        const int col = (k >> 1) * 2 + ((lane >> 2) & 1), row = (k & 1) * 2;
        bw[k] = (lane >> 3) == (lane & 3) ? pack_bf16(wt->wu[(row + 1) * 4 + col], wt->wu[row * 4 + col]) : 0u;
    }
    const int r0 = (X * NCP + c) * ROWS_O, np = max(min((int)ROWS_O, p.E - r0), 0) / 2;
    const uint4* mp = (const uint4*)(p.m + r0);
    uint4* op = (uint4*)(p.out + r0);
    constexpr int EB = 5;
#pragma unroll 1
    for (int rb = tid; rb - lane < np; rb += EB * THREADS) {
        uint4 mr[EB];
#pragma unroll
        for (int k = 0; k < EB; k++) mr[k] = __ldg(mp + min(rb + k * THREADS, np - 1));
#pragma unroll
        for (int k = 0; k < EB; k++) {
            const int r = min(rb + k * THREADS, np - 1);
            const uint4 a = ((const uint4*)smem)[r];
            const uint2 wr = ((const uint2*)(smem + C_WRAP))[r];
            const uint4 t0 = ((const uint4*)(smem + C_TAB))[min(wr.x >> 16, (uint32_t)(TAB_N + TAB_X - 1))];
            const uint4 t1 = ((const uint4*)(smem + C_TAB))[min(wr.y >> 16, (uint32_t)(TAB_N + TAB_X - 1))];
            const bool wrapped = __any_sync(0xffffffffu, prmt(wr.x, wr.y, 0x5410) != 0x88888888u);
            uint32_t a0, a1, a2, a3;
            if (wrapped) { a0 = c_agg(a.x, t0.x, wr.x, true); a2 = c_agg(a.y, t0.y, wr.x >> 8, true); a1 = c_agg(a.z, t1.x, wr.y, true); a3 = c_agg(a.w, t1.y, wr.y >> 8, true); }
            else { a0 = c_agg(a.x, t0.x, 0, false); a2 = c_agg(a.y, t0.y, 0, false); a1 = c_agg(a.z, t1.x, 0, false); a3 = c_agg(a.w, t1.y, 0, false); }
            float u[8];
#pragma unroll
            for (int h = 0; h < 2; h++)
                asm("mma.sync.aligned.m16n8k16.row.col.f32.bf16.bf16.f32 {%0,%1,%2,%3}, {%4,%5,%6,%7}, {%8,%9}, {%10,%10,%10,%10};"
                    : "=f"(u[4 * h]), "=f"(u[4 * h + 1]), "=f"(u[4 * h + 2]), "=f"(u[4 * h + 3])
                    : "r"(a0), "r"(a1), "r"(a2), "r"(a3), "r"(bw[2 * h]), "r"(bw[2 * h + 1]), "f"(0.f));
            const uint4 o = make_uint4(bf2_fma(pack_bf16(u[1], u[0]), t0.z, mr[k].x), bf2_fma(pack_bf16(u[5], u[4]), t0.w, mr[k].y),
                                       bf2_fma(pack_bf16(u[3], u[2]), t1.z, mr[k].z), bf2_fma(pack_bf16(u[7], u[6]), t1.w, mr[k].w));
            if (rb + k * THREADS < np) op[r] = o;
        }
    }
    if (((const uint32_t*)(smem + S_MISC))[6] > TAB_N + TAB_X) {
        for (int r = 2 * tid; r < 2 * np; r += (r & 1) ? 2 * THREADS - 1 : 1) {
            const uint32_t wr = ((const uint32_t*)(smem + C_WRAP))[r];
            if ((wr >> 16) < TAB_N + TAB_X) continue;
            const uint4 t = radial_bf16(wt, __bfloat16_as_ushort(p.dist[r0 + r]));
            const uint2 a = ((const uint2*)smem)[r];
            const uint32_t a0 = c_agg(a.x, t.x, wr, true), a1 = c_agg(a.y, t.y, wr >> 8, true);
            const float agg[4] = {bf_lo(a0), bf_hi(a0), bf_lo(a1), bf_hi(a1)}, g[4] = {bf_lo(t.z), bf_hi(t.z), bf_lo(t.w), bf_hi(t.w)};
            p.out[r0 + r] = finish_row(wt->wu, agg, g, p.m[r0 + r]);
        }
    }
}

__device__ __forceinline__ void grid_bar(unsigned* ctr) {
    __syncthreads();
    if (threadIdx.x == 0) { fence_gpu(); red_add(ctr, 1); wait_ge(ctr, gridDim.x); fence_gpu(); }
    __syncthreads();
}
__device__ __noinline__ void fallback(const Prm& p) {
    const int gt = blockIdx.x * THREADS + threadIdx.x, gs = gridDim.x * THREADS;
    Wts* wt = (Wts*)smem;
    __syncthreads();
    load_wts(p, wt);
    for (int e = gt; e < p.E; e += gs) g_acc[e] = make_float4(0.f, 0.f, 0.f, 0.f);
    grid_bar(&g_ctl.bar[0]);
    const float f = __bfloat162float(p.freq[0]);
    for (int t = gt; t < p.T; t += gs) {
        uint2 r = __ldg(p.m + p.idx_in[t]);
        float c = rbf16(cosf(rbf16(f * __bfloat162float(p.angle[t]))));
        asm volatile("red.global.add.v4.f32 [%0], {%1,%2,%3,%4};" ::"l"(g_acc + p.idx_out[t]), "f"(bf_lo(r.x) * c),
                     "f"(bf_hi(r.x) * c), "f"(bf_lo(r.y) * c), "f"(bf_hi(r.y) * c) : "memory");
    }
    grid_bar(&g_ctl.bar[1]);
    for (int e = gt; e < p.E; e += gs) {
        float4 a4 = __ldcg(g_acc + e);
        float a[4] = {a4.x, a4.y, a4.z, a4.w}, s[4], g[4];
        radial(wt, __bfloat162float(p.dist[e]), s, g);
        float agg[4];
#pragma unroll
        for (int j = 0; j < 4; j++) agg[j] = s[j] * (a[0] * wt->wd[j] + a[1] * wt->wd[4 + j] + a[2] * wt->wd[8 + j] + a[3] * wt->wd[12 + j]);
        p.out[e] = finish_row(wt->wu, agg, g, p.m[e]);
    }
}

__device__ __forceinline__ void smem_init(bool isp, int from, int to) {
    for (int k = from / 16 + threadIdx.x; k < to / 16; k += THREADS) {
        const bool b = isp && k >= P_B / 16 && k < P_Q / 16;
        const uint32_t z = b ? (k & 7) * 0x20002u : 0u, y = b ? z + 0x10001u : 0u;
        ((uint4*)smem)[k] = make_uint4(z, z, y, y);
    }
}

__global__ void __launch_bounds__(THREADS, 1) gemnet_kernel(const __grid_constant__ Prm p) {
    const int tid = threadIdx.x, lane = tid & 31, w = __shfl_sync(0xffffffffu, tid >> 5, 0);
    uint32_t* misc = (uint32_t*)(smem + S_MISC);
    bool run_fallback = true;
    if (!p.force_bad && __cvta_generic_to_shared(smem) == SB) {
        unsigned char* const ring = p.ring;
        uint32_t smid; asm("mov.u32 %0, %%smid;" : "=r"(smid));
        const int cls = smid < NM ? 0 : (smid < NM + NP - 4 || (smid >= 124 && smid < 128)) ? 2 : 1;
        if (lane == 0) {
            if (w < 2 && (cls != 2 || blockIdx.x == 0)) misc[16 + w] = probe(ring + OFF_PROBE + w * 4096 + ((blockIdx.x >> 7) << 20) + (blockIdx.x & 127) * 32);
            else if (blockIdx.x == 0 && w <= NPAGES) misc[16 + w] = probe(ring + ((size_t)(w - 1) << 21) + OFF_PROBE);
        }
        float wd[16];
        if (cls != 2 || blockIdx.x == 0) __syncthreads();
        if (tid == 0) {
            int pool = cls == 2 ? 4 : cls * 2 + (misc[16] > misc[17]), id = 0;
            for (int k = 0; k < 7; k++) {
                int cap = pool < 2 ? NMP : pool < 4 ? NCP : NP;
                id = atomicAdd(&g_ctl.ticket[pool], 1);
                if (id < cap) break;
                pool = k == 0 ? (pool == 4 ? 0 : pool ^ 1) : k - 1;
            }
            misc[8] = pool; misc[9] = id;
            if (pool != 4) down_load(p, pool < 2 ? pool * NMP + id : NM + (pool - 2) * NCP + id);
        }
        if (blockIdx.x == 0 && tid == 32) {
            uint32_t pb = 0x80000000u;
            for (int k = 1; k < NPAGES; k++) pb |= (uint32_t)((2 * misc[17 + k] > misc[16] + misc[17]) != (misc[16] > misc[17])) << k;
            st_relaxed(&g_ctl.pagebits, pb);
        }
#pragma unroll
        for (int k = 0; k < 16; k++) wd[k] = __bfloat162float(p.w_down[k]);
        if (cls == 2) smem_init(true, 0, S_PC);
        __syncthreads();
        const int pool = misc[8], id = misc[9];
        if (pool >= 2 && (pool < 4 || cls != 2)) smem_init(pool == 4, 0, S_PC);
        if (pool != 4) down_piece(p, pool < 2 ? pool * NMP + id : NM + (pool - 2) * NCP + id, wd);
        if (DEV_FREE && !(DEV_FREE & (pool == 4 ? 1 : pool < 2 ? 2 : 4))) {
        } else if (pool == 4) {
            smem_init(true, S_PC, S_MISC);
            __syncthreads();
            if (tid < 2 * NBUF) {
                const uint32_t a = tid < NBUF ? bar_done(tid) : bar_free(tid), cnt = tid < NBUF ? CPS : 1;
                mbar_init(a, cnt);
                if (tid % NBUF < id % GR) asm volatile("mbarrier.arrive.shared.b64 _, [%0], %1;" ::"r"(a), "r"(cnt) : "memory");
            }
            __syncthreads();
            if (w < FW) p_filler(p, id, w);
            else if (w < FW + NF) {
                int it = 0; uint32_t pb;
                while (!((pb = ld_relaxed(&g_ctl.pagebits)) >> 31)) backoff(it);
                p_flusher(p, ring, __shfl_sync(0xffffffffu, pb, 0), id, w - FW);
            }
        } else if (pool < 2) {
            m_role(p, ring, pool, id);
        } else {
            c_role(p, ring, pool - 2, id);
        }
        __syncthreads();
        if (tid == 0) { fence_gpu(); red_add(&g_ctl.fin, 1); }
        if ((pool == 2 || pool == 3) && !DEV_FREE) c_epilogue(p, pool - 2, id);
        if (tid == 0) { wait_ge(&g_ctl.fin, NCTA); fence_gpu(); misc[10] = ld_relaxed(&g_ctl.bad); }
        __syncthreads();
        if (pool == 4) p_cleanup(ring, id);
        run_fallback = misc[10] && !DEV_FREE;
    }
    if (run_fallback) fallback(p);
    if (tid == 0) {
        fence_gpu();
        if (atomicAdd(&g_ctl.exited, 1) == gridDim.x - 1) {
            uint32_t* c = (uint32_t*)&g_ctl;
            for (int k = 0; k < 64; k++) c[k] = 0;
        }
    }
}

cudaTextureObject_t make_tex(const void* ptr, size_t bytes, int words) {
    cudaResourceDesc rd = {};
    rd.resType = cudaResourceTypeLinear;
    rd.res.linear.devPtr = (void*)ptr;
    rd.res.linear.desc = words == 4 ? cudaCreateChannelDesc<uint4>() : cudaCreateChannelDesc<uint2>();
    rd.res.linear.sizeInBytes = bytes;
    cudaTextureDesc td = {};
    td.readMode = cudaReadModeElementType;
    cudaTextureObject_t t = 0;
    if (cudaCreateTextureObject(&t, &rd, &td, nullptr) != cudaSuccess) { cudaGetLastError(); return 0; }
    return t;
}

}

extern "C" void kernel_launch(void* const* d_in, const int* in_sizes, int n_in, void* d_out, int out_size) {
    static Prm p = {};
    static int grid = 0;
    const int E = in_sizes[3], T = in_sizes[1];
    if (grid == 0 || p.idx_in != d_in[1] || p.idx_out != d_in[2] || p.angle != d_in[4] || p.E != E || p.T != T) {
        int dev = 0, sms = 0;
        cudaGetDevice(&dev);
        cudaDeviceGetAttribute(&sms, cudaDevAttrMultiProcessorCount, dev);
        cudaFuncSetAttribute(gemnet_kernel, cudaFuncAttributeMaxDynamicSharedMemorySize, SMEM_BYTES);
        p.E = E; p.T = T;
        p.NS = ((((T / 128 + NP * CB - 1) / (NP * CB)) * CB + CPS - 1) / CPS + 1) & ~1;
        void* rp = nullptr;
        cudaGetSymbolAddress(&rp, g_ring);
        p.ring = (unsigned char*)(((uintptr_t)rp + ((2u << 20) - 1)) & ~(uintptr_t)((2u << 20) - 1));
        bool fast = sms >= NCTA && E <= (int)FAST_E && (E & 1) == 0 && T >= 128 && T <= (1 << 29);
        if (fast) {
            p.t_in = make_tex(d_in[1], (size_t)(T / 128) * 512, 4);
            p.t_out = make_tex(d_in[2], (size_t)(T / 128) * 512, 4);
            p.t_ang = make_tex(d_in[4], (size_t)(T / 128) * 256, 2);
            fast = p.t_in && p.t_out && p.t_ang;
        }
        p.force_bad = !fast;
        grid = fast ? NCTA : sms;
    }
    p.m = (const uint2*)d_in[0];
    p.idx_in = (const int*)d_in[1];
    p.idx_out = (const int*)d_in[2];
    p.dist = (const __nv_bfloat16*)d_in[3];
    p.angle = (const __nv_bfloat16*)d_in[4];
    p.centers = (const __nv_bfloat16*)d_in[5];
    p.freq = (const __nv_bfloat16*)d_in[6];
    p.w_rbf = (const __nv_bfloat16*)d_in[7];
    p.w_sbf = (const __nv_bfloat16*)d_in[8];
    p.w_down = (const __nv_bfloat16*)d_in[9];
    p.w_up = (const __nv_bfloat16*)d_in[10];
    p.out = (uint2*)d_out;
    gemnet_kernel<<<grid, THREADS, SMEM_BYTES>>>(p);
}
```

```cpp
#include <cuda_runtime.h>
#include <cuda_bf16.h>
#include <stdint.h>

namespace {

constexpr int NI = 12;
constexpr int UN = 3;
constexpr int NG = NI / UN;
constexpr int GR = 2 * NG;
constexpr int NCP = 18;
constexpr int NO = 2 * NCP;
constexpr int KS = 64;
constexpr int NB = UN * NCP;
constexpr int NBUF = 10;
constexpr int NMP = 2 * NI;
constexpr int NP = 48, NM = 2 * NMP, NC = NO, NCTA = NP + NM + NC;
#define CPS_ 25
constexpr int CPS = CPS_;
#define FW_ 24
constexpr int FW = FW_;
constexpr int NF = 4;
#define RA_ 3
#define RV_ 3
#define RB_ 4
constexpr int RA = RA_, RV = RV_, RB = RB_;
#define QN_ 96
#define QTRIG_ 48
constexpr int QN = QN_, QTRIG = QTRIG_;
#define MW_ 18
constexpr int MW = MW_;
#define MPF_ 6
constexpr int MPF = MPF_;
constexpr int THREADS = 896, NW = THREADS / 32;
#define DEV_FREE 0
#define SLEEP_ 50

constexpr int RING_BYTES = NP << 20;
constexpr int NPAGES = RING_BYTES >> 21;
constexpr int MAX_E = 1 << 20;
constexpr int SMEM_BYTES = 232448;

constexpr int SB = 1024;

constexpr int P_CNT = 0;
constexpr int P_BAR = P_CNT + NBUF * NB * 4;
constexpr int P_TKT = P_BAR + 2 * NBUF * 8;
constexpr int P_LATE = P_TKT + 128;
constexpr int P_B = (P_LATE + 256 + 127) / 128 * 128;
constexpr int P_Q = P_B + NBUF * NB * KS * 2;
constexpr int P_A = SMEM_BYTES - 256 - NBUF * NB * KS * 4;
static_assert(P_Q + FW * QN * 8 + 512 <= P_A && P_A % 128 == 0, "P smem");
constexpr int S_MISC = SMEM_BYTES - 256;
constexpr int S_AUX = S_MISC - 512;

constexpr unsigned FAST_E = 640000;
constexpr unsigned magic_of(unsigned long long d) { return (unsigned)(((1ull << 32) + d - 1) / d); }
constexpr bool magic_ok(unsigned long long d) { return (magic_of(d) * d - (1ull << 32)) * FAST_E < (1ull << 32); }
constexpr unsigned pick_rows(unsigned lo) {
    unsigned d = (lo + 3) & ~3u;
    while (!magic_ok(d)) d += 4;
    return d;
}
constexpr unsigned ROWS_I = pick_rows((FAST_E + NI - 1) / NI), ROWS_O = pick_rows((FAST_E + NO - 1) / NO);
constexpr unsigned MAG_I = magic_of(ROWS_I), MAG_O = magic_of(ROWS_O), HALF_O = ROWS_O * NCP;
constexpr int C_WRAP = ROWS_O * 8, C_TAB = ROWS_O * 12, TAB_N = 1025, TAB_LO = 0x3f80 - 1024, TAB_X = (S_AUX - C_TAB) / 16 - TAB_N;
static_assert(ROWS_I * 4 <= S_AUX && TAB_X >= 100 && ROWS_I <= 65536 && ROWS_O <= 32768, "tables");

constexpr int NPC = NM + NC;
constexpr int PC_ROWS = ((FAST_E + NPC - 1) / NPC + 3) & ~3;
constexpr int S_PC = C_WRAP + 128 - C_WRAP % 128;
static_assert(S_PC + PC_ROWS * 8 + 1024 <= S_AUX, "pre-pass");
struct __align__(128) Ctl {
    unsigned ticket[5];
    unsigned pagebits;
    unsigned pieces_done, late_done;
    unsigned bad;
    unsigned fin;
    unsigned bar[3];
    unsigned exited;
    unsigned pad[18];
    float stat[NPC][8];
};

struct Prm {
    const uint2* m; const int* idx_in; const int* idx_out; const __nv_bfloat16* dist; const __nv_bfloat16* angle;
    const __nv_bfloat16* centers; const __nv_bfloat16* freq; const __nv_bfloat16* w_rbf; const __nv_bfloat16* w_sbf;
    const __nv_bfloat16* w_down; const __nv_bfloat16* w_up; uint2* out;
    cudaTextureObject_t t_in, t_out, t_ang;
    int E, T;
    unsigned char* ring;
    int NS, NT;
    int force_bad;
};

__device__ __align__(128) unsigned char g_ring[RING_BYTES + (2 << 20)];
__device__ Ctl g_ctl;
constexpr int LATE_N = 64;
__device__ uint4 g_late_n[NP][16];
__device__ uint4 g_late[NO][NP][LATE_N][2];
__device__ float4 g_acc[MAX_E];
__device__ __align__(128) uint32_t g_md[2][NI * ROWS_I];
#define TS(k)
#define PROF_DECL
#define PROF(k)
#define PROF_END

extern __shared__ __align__(128) unsigned char smem[];

__device__ __forceinline__ float bf_lo(uint32_t w) { return __uint_as_float(w << 16); }
__device__ __forceinline__ float bf_hi(uint32_t w) { return __uint_as_float(w & 0xffff0000u); }
__device__ __forceinline__ float rbf16(float x) { return __bfloat162float(__float2bfloat16_rn(x)); }
__device__ __forceinline__ uint32_t pack_bf16(float hi, float lo) {
    uint32_t r; asm("cvt.rn.bf16x2.f32 %0, %1, %2;" : "=r"(r) : "f"(hi), "f"(lo)); return r;
}
__device__ __forceinline__ uint32_t prmt(uint32_t a, uint32_t b, uint32_t c) {
    uint32_t r; asm("prmt.b32 %0, %1, %2, %3;" : "=r"(r) : "r"(a), "r"(b), "r"(c)); return r;
}
__device__ __forceinline__ uint32_t ld_relaxed(const void* p) {
    uint32_t v; asm volatile("ld.relaxed.gpu.global.u32 %0, [%1];" : "=r"(v) : "l"(p) : "memory"); return v;
}
__device__ __forceinline__ uint2 ld_relaxed2(const void* p) {
    uint2 v; asm volatile("ld.relaxed.gpu.global.v2.u32 {%0,%1}, [%2];" : "=r"(v.x), "=r"(v.y) : "l"(p) : "memory"); return v;
}
__device__ __forceinline__ uint4 ld_relaxed4(const void* p) {
    uint4 v; asm volatile("ld.relaxed.gpu.global.v4.u32 {%0,%1,%2,%3}, [%4];" : "=r"(v.x), "=r"(v.y), "=r"(v.z), "=r"(v.w) : "l"(p) : "memory"); return v;
}
__device__ __forceinline__ void st_relaxed(void* p, uint32_t v) { asm volatile("st.relaxed.gpu.global.u32 [%0], %1;" ::"l"(p), "r"(v) : "memory"); }
__device__ __forceinline__ void st_relaxed16(void* p, uint32_t v) { asm volatile("st.relaxed.gpu.global.u16 [%0], %1;" ::"l"(p), "h"((uint16_t)v) : "memory"); }
__device__ __forceinline__ void red_add(void* p, uint32_t v) { asm volatile("red.relaxed.gpu.global.add.u32 [%0], %1;" ::"l"(p), "r"(v) : "memory"); }
__device__ __forceinline__ void fence_gpu() { asm volatile("fence.acq_rel.gpu;" ::: "memory"); }
__device__ __forceinline__ void fence_acquire() { asm volatile("fence.acquire.gpu;" ::: "memory"); }
__device__ __forceinline__ void fence_release() { asm volatile("fence.release.gpu;" ::: "memory"); }
__device__ __forceinline__ void mbar_init(uint32_t a, uint32_t n) { asm volatile("mbarrier.init.shared.b64 [%0], %1;" ::"r"(a), "r"(n) : "memory"); }
__device__ __forceinline__ void mbar_arrive(uint32_t a) { asm volatile("mbarrier.arrive.shared.b64 _, [%0];" ::"r"(a) : "memory"); }
__device__ __forceinline__ bool mbar_try(uint32_t a, uint32_t ph) {
    uint32_t ok;
    asm volatile("{.reg .pred p; mbarrier.try_wait.parity.shared.b64 p, [%1], %2, %3; selp.u32 %0, 1, 0, p;}" : "=r"(ok) : "r"(a), "r"(ph), "r"(2000) : "memory");
    return ok;
}
__device__ __forceinline__ bool mbar_test(uint32_t a, uint32_t ph) {
    uint32_t ok;
    asm volatile("{.reg .pred p; mbarrier.test_wait.parity.shared.b64 p, [%1], %2; selp.u32 %0, 1, 0, p;}" : "=r"(ok) : "r"(a), "r"(ph) : "memory");
    return ok;
}
constexpr int SPIN_MAX = 1 << 22;
__device__ __forceinline__ void mbar_wait(uint32_t a, uint32_t ph) {
    int it = 0;
    while (!mbar_try(a, ph)) { if (++it > SPIN_MAX) __trap(); }
}
__device__ __forceinline__ void backoff(int& it) { __nanosleep(SLEEP_); if (++it > SPIN_MAX) __trap(); }
__device__ __forceinline__ void wait_ge(const void* p, uint32_t v) {
    int it = 0;
    while (ld_relaxed(p) < v) backoff(it);
}

__device__ __forceinline__ bool elect_one() {
    uint32_t r; asm volatile("{.reg .pred p; elect.sync _|p, 0xffffffff; selp.u32 %0, 1, 0, p;}" : "=r"(r)); return r;
}
__device__ __forceinline__ void st_lane0(void* p, uint32_t v, int lane) {
    asm volatile("{.reg .pred p; setp.eq.s32 p, %2, 0; @p st.relaxed.gpu.global.u32 [%0], %1;}" ::"l"(p), "r"(v), "r"(lane) : "memory");
}
__device__ __forceinline__ void wait_all_ge(const void* p, uint32_t v) {
    int it = 0;
    while (!__all_sync(0xffffffffu, ld_relaxed(p) >= v)) backoff(it);
}
__device__ __forceinline__ void lds_lt(uint32_t& v, uint32_t ad, int a, int b) {
    asm volatile("{.reg .pred p; setp.lt.s32 p, %2, %3; @p ld.shared.u32 %0, [%1];}" : "+r"(v) : "r"(ad), "r"(a), "r"(b));
}

constexpr uint32_t R_V1 = 0x03000, R_A = 0x81000, R_B = 0x82000, R_UNIT = 0x4000, R_HI = 0x40000 - 8 * 256;
__device__ __forceinline__ uint32_t q_base(uint32_t q, uint32_t pagebits_x) { return (q << 20) | (((pagebits_x >> (q >> 1)) & 1u) << 12); }
__device__ __forceinline__ uint32_t slot_off(uint32_t s) { return (s << 16) | (((s + 1) & 2) << 11); }
constexpr uint32_t OFF_PF = R_B + 3 * R_UNIT, OFF_RDY = OFF_PF + 128, OFF_REL = OFF_PF + 256;
constexpr uint32_t OFF_PROBE = 3 * R_UNIT;
static_assert(RA <= 4 && RV <= 4 && RB <= 8 && RA <= RB && RV <= RB, "ring");

__device__ __forceinline__ uint32_t probe(unsigned char* p) {
    volatile uint32_t* sink = (volatile uint32_t*)(smem + S_MISC + 240);
    asm volatile("st.global.v4.u32 [%0], {%1,%1,%1,%1};" ::"l"(p), "r"(0) : "memory");
    asm volatile("st.global.v4.u32 [%0], {%1,%1,%1,%1};" ::"l"(p + 16), "r"(0) : "memory");
    uint32_t best = 0xffffffffu;
#pragma unroll 1
    for (int r = 0; r < 3; r++) {
        uint32_t t0, t1, v;
        asm volatile("mov.u32 %0, %%clock;" : "=r"(t0)::"memory");
        asm volatile("atom.relaxed.gpu.global.add.u32 %0, [%1], 1;" : "=r"(v) : "l"(p) : "memory");
        *sink = v;
        asm volatile("mov.u32 %0, %%clock;" : "=r"(t1)::"memory");
        best = min(best, t1 - t0);
    }
    return best;
}

struct Wts { float c[8], wr[32], ws[32], wd[16], wu[16]; };
__device__ __forceinline__ void load_wts(const Prm& p, Wts* w) {
    int t = threadIdx.x;
    if (t < 8) w->c[t] = __bfloat162float(p.centers[t]);
    if (t < 32) { w->wr[t] = __bfloat162float(p.w_rbf[t]); w->ws[t] = __bfloat162float(p.w_sbf[t]); }
    if (t < 16) { w->wd[t] = __bfloat162float(p.w_down[t]); w->wu[t] = __bfloat162float(p.w_up[t]); }
}
__device__ __forceinline__ void radial(const Wts* w, float d, float s[4], float g[4]) {
#pragma unroll
    for (int j = 0; j < 4; j++) s[j] = g[j] = 0.f;
#pragma unroll
    for (int r = 0; r < 8; r++) {
        float x = rbf16(d - w->c[r]);
        float b = rbf16(__expf(rbf16(-10.0f * rbf16(x * x))));
#pragma unroll
        for (int j = 0; j < 4; j++) { s[j] += b * w->ws[r * 4 + j]; g[j] += b * w->wr[r * 4 + j]; }
    }
}
__device__ __noinline__ uint4 radial_bf16(const Wts* w, uint32_t dbits) {
    float s[4], g[4];
    radial(w, __uint_as_float(dbits << 16), s, g);
    return make_uint4(pack_bf16(s[1], s[0]), pack_bf16(s[3], s[2]), pack_bf16(g[1], g[0]), pack_bf16(g[3], g[2]));
}
__device__ __forceinline__ uint2 finish_row(const float* wu, const float agg[4], const float g[4], uint2 r) {
    float o[4];
    const float mm[4] = {bf_lo(r.x), bf_hi(r.x), bf_lo(r.y), bf_hi(r.y)};
#pragma unroll
    for (int j = 0; j < 4; j++) o[j] = mm[j] + (agg[0] * wu[j] + agg[1] * wu[4 + j] + agg[2] * wu[8 + j] + agg[3] * wu[12 + j]) * g[j];
    return make_uint2(pack_bf16(o[1], o[0]), pack_bf16(o[3], o[2]));
}
__device__ __forceinline__ uint2 down_row(const float* wd, uint32_t x, uint32_t y) {
    const float a[4] = {bf_lo(x), bf_hi(x), bf_lo(y), bf_hi(y)};
    float d[4];
#pragma unroll
    for (int j = 0; j < 4; j++) d[j] = a[0] * wd[j] + a[1] * wd[4 + j] + a[2] * wd[8 + j] + a[3] * wd[12 + j];
    return make_uint2(pack_bf16(d[1], d[0]), pack_bf16(d[3], d[2]));
}

__device__ __forceinline__ void down_load(const Prm& p, int pc) {
    const int r0 = pc * PC_ROWS / 2, nr = max(min((pc + 1) * PC_ROWS, p.E) / 2 - r0, 0);
    const uint32_t bar = SB + S_MISC + 248;
    mbar_init(bar, 1);
    asm volatile("fence.proxy.async.shared::cta;" ::: "memory");
    asm volatile("mbarrier.arrive.expect_tx.shared.b64 _, [%0], %1;" ::"r"(bar), "r"(nr * 16) : "memory");
    for (int o = 0; o < nr; o += 640)
        asm volatile("cp.async.bulk.shared::cluster.global.mbarrier::complete_tx::bytes [%0], [%1], %2, [%3];"
                     ::"r"(SB + S_PC + o * 16), "l"((const uint4*)p.m + r0 + o), "r"(min(640, nr - o) * 16), "r"(bar) : "memory");
}
__device__ __forceinline__ void down_piece(const Prm& p, int pc, const float* wd) {
    const int tid = threadIdx.x, lane = tid & 31, w = tid >> 5;
    const int r0 = pc * PC_ROWS / 2, nr = max(min((pc + 1) * PC_ROWS, p.E) / 2 - r0, 0);
    mbar_wait(SB + S_MISC + 248, 0);
    uint32_t mx0 = 0, mx1 = 0; float ss[4] = {0.f, 0.f, 0.f, 0.f};
    for (int r = tid; r < nr; r += THREADS) {
        const uint4 v = ((const uint4*)(smem + S_PC))[r];
        const uint2 a = down_row(wd, v.x, v.y), b = down_row(wd, v.z, v.w);
        ((uint2*)g_md[0])[r0 + r] = make_uint2(a.x, b.x); ((uint2*)g_md[1])[r0 + r] = make_uint2(a.y, b.y);
        mx0 = __vimax3_u16x2(mx0, a.x & 0x7fff7fffu, b.x & 0x7fff7fffu); mx1 = __vimax3_u16x2(mx1, a.y & 0x7fff7fffu, b.y & 0x7fff7fffu);
        ss[0] += bf_lo(a.x) * bf_lo(a.x) + bf_lo(b.x) * bf_lo(b.x); ss[1] += bf_hi(a.x) * bf_hi(a.x) + bf_hi(b.x) * bf_hi(b.x);
        ss[2] += bf_lo(a.y) * bf_lo(a.y) + bf_lo(b.y) * bf_lo(b.y); ss[3] += bf_hi(a.y) * bf_hi(a.y) + bf_hi(b.y) * bf_hi(b.y);
    }
    uint32_t st[4] = {mx0 << 16, mx0 & 0xffff0000u, mx1 << 16, mx1 & 0xffff0000u};
    uint4* red = (uint4*)(smem + S_PC + PC_ROWS * 8);
    for (int pass = 0; pass < 2; pass++) {
#pragma unroll
        for (int ch = 0; ch < 4; ch++) {
            st[ch] = __reduce_max_sync(0xffffffffu, st[ch]);
#pragma unroll
            for (int o = 16; o; o >>= 1) ss[ch] += __shfl_xor_sync(0xffffffffu, ss[ch], o);
        }
        uint4* dst = pass ? (uint4*)g_ctl.stat[pc] : red + 2 * w;
        if (lane == 0) { dst[0] = make_uint4(st[0], st[1], st[2], st[3]); dst[1] = make_uint4(__float_as_uint(ss[0]), __float_as_uint(ss[1]), __float_as_uint(ss[2]), __float_as_uint(ss[3])); }
        if (pass) break;
        __syncthreads();
        const uint4 a = lane < NW ? red[2 * lane] : make_uint4(0, 0, 0, 0), b = lane < NW ? red[2 * lane + 1] : make_uint4(0, 0, 0, 0);
        __syncthreads();
        if (w != NW - 1) return;
        st[0] = a.x; st[1] = a.y; st[2] = a.z; st[3] = a.w;
        ss[0] = __uint_as_float(b.x); ss[1] = __uint_as_float(b.y); ss[2] = __uint_as_float(b.z); ss[3] = __uint_as_float(b.w);
    }
    if (lane == 0) { fence_release(); red_add(&g_ctl.pieces_done, 1); }
    __syncwarp();
}

__device__ __forceinline__ void get_scales(const Prm& p, float sc[4], bool& bad) {
    const int lane = threadIdx.x & 31;
    uint32_t mxb[4] = {0, 0, 0, 0};
    float ss[4] = {0.f, 0.f, 0.f, 0.f};
#pragma unroll
    for (int k = 0; k < (NPC + 31) / 32; k++) {
        if (lane + 32 * k < NPC) {
            const uint4 a = ld_relaxed4(&g_ctl.stat[lane + 32 * k][0]), b = ld_relaxed4(&g_ctl.stat[lane + 32 * k][4]);
            mxb[0] = max(mxb[0], a.x); mxb[1] = max(mxb[1], a.y); mxb[2] = max(mxb[2], a.z); mxb[3] = max(mxb[3], a.w);
            ss[0] += __uint_as_float(b.x); ss[1] += __uint_as_float(b.y); ss[2] += __uint_as_float(b.z); ss[3] += __uint_as_float(b.w);
        }
    }
    bad = false;
    const float kdeg = fminf(3.5f * sqrtf(fmaxf(0.5f * (float)p.T / (float)p.E, 1.0f)), 128.f);
#pragma unroll
    for (int ch = 0; ch < 4; ch++) {
        float mx = __uint_as_float(__reduce_max_sync(0xffffffffu, mxb[ch]));
#pragma unroll
        for (int o = 16; o; o >>= 1) ss[ch] += __shfl_xor_sync(0xffffffffu, ss[ch], o);
        float rms = sqrtf(ss[ch] / (float)p.E);
        float range = fmaxf(4.002f * mx, kdeg * rms);
        if (!(mx <= 1e15f) || !(range <= 128.f * rms) || (mx > 0.f && mx < 1e-15f)) bad = true;
        sc[ch] = range > 0.f ? 32767.f / range : 0.f;
    }
}

constexpr float MAG_LO = 12582912.f, MAG_HI = 12582912.f - 19264.f;
__device__ __forceinline__ uint32_t term(uint32_t m, float f_lo, float f_hi, float mag_lo, float mag_hi) {
    return (__float_as_uint(fmaf(bf_hi(m), f_hi, mag_hi)) << 16) + __float_as_uint(fmaf(bf_lo(m), f_lo, mag_lo));
}

constexpr int PER = 40;
__host__ __device__ constexpr uint32_t bar_done(uint32_t s) { return SB + P_BAR + (s % NBUF) * 16; }
__host__ __device__ constexpr uint32_t bar_free(uint32_t m) { return bar_done(m + NBUF - (GR - 1)) + 8; }
struct __align__(16) PTab { uint32_t e[PER][4]; };
constexpr PTab make_ptab() {
    PTab t = {};
    for (int s = 0; s < PER; s++) {
        for (int d = 0; d < GR; d++) {
            int gi = (s + d) % GR, buf = (s + d) % NBUF, X = gi & 1, g = gi >> 1;
            t.e[s][X] |= (uint32_t)(4 * UN * buf - g - 4 * X + 7) << (8 * g);
        }
        t.e[s][2] = bar_done(s);
        t.e[s][3] = (((s + GR - 1) / NBUF) & 1) ^ 1;
    }
    return t;
}
__constant__ PTab c_ptab = make_ptab();
constexpr int BIAS = 7 * NCP;
static_assert(NG == 4 && CPS >= FW, "group selection");

struct PCtx { uint32_t a0, a1; };
struct PElem { uint32_t b4, aw, ol, r2; };

__device__ __forceinline__ void p_bin(const PCtx& c, PElem& e, uint32_t i, uint32_t o) {
    uint32_t ib = __umulhi(i, MAG_I), ob = __umulhi(o, MAG_O), sel = ib & 3;
    asm("{.reg .pred p; setp.ge.u32 p, %1, %2; @p add.u32 %0, %0, 4;}" : "+r"(sel) : "r"(o), "n"(HALF_O));
    e.b4 = __dp4a(prmt(c.a0, c.a1, sel), (uint32_t)NCP, ib * NCP + ob * 4);
    e.aw = i - ib * ROWS_I;
    e.ol = o - ob * ROWS_O;
}
__device__ __forceinline__ void p_rank(PElem& e) {
    asm volatile("atom.shared.add.u32 %0, [%1+%2], 2;" : "=r"(e.r2) : "r"(e.b4), "n"(SB + P_CNT - BIAS) : "memory");
}
__device__ __forceinline__ void p_store(const PElem& e) {
    const uint32_t ab = e.b4 * (KS / 2) + e.r2;
    asm volatile("{.reg .pred p; setp.lt.u32 p, %4, %5; @p st.shared.u32 [%0+%6], %1; @p st.shared.u16 [%2+%7], %3;}"
                 ::"r"(ab * 2), "r"(e.aw), "r"(ab), "h"((uint16_t)e.ol), "r"(e.r2), "n"(KS * 2),
                   "n"(SB + P_A - BIAS * KS), "n"(SB + P_B - BIAS * (KS / 2)) : "memory");
}
__device__ __forceinline__ uint32_t cos2(uint32_t x) {
    x = __vminu2(x, 0x42804280u);
    return pack_bf16(__cosf(bf_hi(x)), __cosf(bf_lo(x)));
}

#define PD_ 2
#define CB_ 8
constexpr int CB = CB_;
struct PIn { uint4 i, o; uint2 a; };

struct PFill {
    PCtx c;
    uint32_t qb, qt, lt, f2, bar, par, xmax;
    uint32_t s0, lane, vb;
    bool open;
    __device__ __forceinline__ void fetch(const Prm& p, PIn& x, uint32_t ch) {
        const int v = ((ch & ~(CB - 1u)) * (NP - 1) + ch) * 32 + vb;
        asm volatile("{.reg .b32 d0, d1; tex.1d.v4.u32.s32 {%0,%1,d0,d1}, [%2, {%3}];}" : "=r"(x.a.x), "=r"(x.a.y) : "l"(p.t_ang), "r"(v));
        asm volatile("tex.1d.v4.u32.s32 {%0,%1,%2,%3}, [%4, {%5}];" : "=r"(x.i.x), "=r"(x.i.y), "=r"(x.i.z), "=r"(x.i.w) : "l"(p.t_in), "r"(v));
        asm volatile("tex.1d.v4.u32.s32 {%0,%1,%2,%3}, [%4, {%5}];" : "=r"(x.o.x), "=r"(x.o.y), "=r"(x.o.z), "=r"(x.o.w) : "l"(p.t_out), "r"(v));
    }
    __device__ __forceinline__ uint32_t ticket(uint32_t zero) {
        uint32_t t;
        asm volatile("atom.shared.add.u32 %0, [%1+%2], %3;" : "=r"(t) : "r"(lane * 4), "n"(SB + P_TKT), "r"((~lt & 1) | zero) : "memory");
        return t;
    }
    __device__ __forceinline__ uint32_t use_ticket(uint32_t t) {
        t = __reduce_or_sync(0xffffffffu, t);
        begin(t / CPS);
        return t + PD_ * FW;
    }
    __device__ __forceinline__ void begin(uint32_t step) {
        const uint4 t = ((const uint4*)c_ptab.e)[(step + s0) % PER];
        c.a0 = t.x; c.a1 = t.y; bar = t.z; par = t.w;
        open = mbar_test(bar + 8, par);
    }
    __device__ __forceinline__ void enter() { if (!open) mbar_wait(bar + 8, par); }
    __device__ __forceinline__ void end() {
        __syncwarp();
        asm volatile("{.reg .pred p; setp.eq.u32 p, %1, 0; @p mbarrier.arrive.shared.b64 _, [%0];}" ::"r"(bar), "r"(lt) : "memory");
    }
    __device__ __forceinline__ void push(bool f, uint32_t x, uint32_t y) {
        const uint32_t mask = __ballot_sync(0xffffffffu, f);
        asm volatile("{.reg .pred p; setp.ne.u32 p, %3, 0; @p st.shared.v2.u32 [%0], {%1,%2};}"
                     ::"r"(min(qt + __popc(mask & lt) * 8, qb + (QN - 1) * 8)), "r"(x), "r"(y), "r"((uint32_t)f) : "memory");
        qt += __popc(mask) * 8;
    }
    __device__ __forceinline__ void push3(bool f, uint32_t i, uint32_t o, uint32_t aw) { push(f, prmt(i, aw, 0x6210), prmt(o, aw, 0x7210)); }
    __device__ __forceinline__ uint32_t chunk(const PIn& x) {
        uint32_t x0, x1;
        const uint32_t tk = use_ticket(ticket(x.o.x >> 31));
        PElem e0, e1, e2, e3;
        p_bin(c, e0, x.i.x, x.o.x); p_bin(c, e1, x.i.y, x.o.y); p_bin(c, e2, x.i.z, x.o.z); p_bin(c, e3, x.i.w, x.o.w);
        asm volatile("" : "+r"(e0.b4), "+r"(e1.b4), "+r"(e2.b4), "+r"(e3.b4));
        enter();
        p_rank(e0); p_rank(e1); p_rank(e2); p_rank(e3);
        asm volatile("mul.rn.bf16x2 %0, %1, %2;" : "=r"(x0) : "r"(x.a.x), "r"(f2));
        asm volatile("mul.rn.bf16x2 %0, %1, %2;" : "=r"(x1) : "r"(x.a.y), "r"(f2));
        x0 &= 0x7fff7fffu; x1 &= 0x7fff7fffu;
        xmax = __vimax3_u16x2(xmax, x0, x1);
        const uint32_t c0 = cos2(x0), c1 = cos2(x1);
        e0.aw = prmt(e0.aw, c0, 0x5410); e1.aw = prmt(e1.aw, c0, 0x7610); e2.aw = prmt(e2.aw, c1, 0x5410); e3.aw = prmt(e3.aw, c1, 0x7610);
        p_store(e0); p_store(e1); p_store(e2); p_store(e3);
        if (qt - qb >= QTRIG * 8) retry(32);
        end();
        const uint32_t r01 = e0.r2 | e1.r2, r23 = e2.r2 | e3.r2;
        const bool f = (r01 | r23) >= KS * 2;
        if (__any_sync(0xffffffffu, f)) {
            const bool f0 = e0.r2 >= KS * 2, f1 = e1.r2 >= KS * 2, f2_ = e2.r2 >= KS * 2, f3 = e3.r2 >= KS * 2, f01 = r01 >= KS * 2;
            push3(f, f01 ? (f0 ? x.i.x : x.i.y) : (f2_ ? x.i.z : x.i.w), f01 ? (f0 ? x.o.x : x.o.y) : (f2_ ? x.o.z : x.o.w),
                  f01 ? (f0 ? e0.aw : e1.aw) : (f2_ ? e2.aw : e3.aw));
            const uint32_t s2 = max(max(min(e0.r2, e1.r2), min(e2.r2, e3.r2)), min(r01, r23));
            if (__any_sync(0xffffffffu, s2 >= KS * 2)) {
                push3(f1 && f0, x.i.y, x.o.y, e1.aw); push3(f2_ && f01, x.i.z, x.o.z, e2.aw); push3(f3 && (f01 || f2_), x.i.w, x.o.w, e3.aw);
            }
        }
        return tk;
    }
    __device__ __forceinline__ void retry(uint32_t take) {
        if (qt - qb > QN * 8) { st_relaxed(&g_ctl.bad, 1); qt = qb + QN * 8; }
        uint2 e, r, r1;
        __syncwarp();
        asm volatile("ld.shared.v2.u32 {%0,%1}, [%2];" : "=r"(e.x), "=r"(e.y) : "r"(qb + lane * 8) : "memory");
        asm volatile("ld.shared.v2.u32 {%0,%1}, [%2];" : "=r"(r.x), "=r"(r.y) : "r"(qb + (lane + take) * 8) : "memory");
        qt -= take * 8;
        const bool more = qt - qb > 256;
        if (more) asm volatile("ld.shared.v2.u32 {%0,%1}, [%2];" : "=r"(r1.x), "=r"(r1.y) : "r"(qb + (lane + take) * 8 + 256) : "memory");
        __syncwarp();
        if (more && qb + lane * 8 + 256 < qt) asm volatile("st.shared.v2.u32 [%0], {%1,%2};" ::"r"(qb + lane * 8 + 256), "r"(r1.x), "r"(r1.y) : "memory");
        if (qb + lane * 8 < qt) asm volatile("st.shared.v2.u32 [%0], {%1,%2};" ::"r"(qb + lane * 8), "r"(r.x), "r"(r.y) : "memory");
        PElem el;
        el.r2 = 0;
        if (take == 32 || lane < take) {
            p_bin(c, el, e.x & 0xffffffu, e.y & 0xffffffu);
            el.aw = prmt(el.aw, prmt(e.x, e.y, 0x0073), 0x5410);
            p_rank(el);
            p_store(el);
        }
        push(el.r2 >= KS * 2, e.x, e.y);
    }
};

__device__ __forceinline__ void p_filler(const Prm& p, int q, int w) {
    PFill F;
    const int lane = threadIdx.x & 31;
    const uint32_t NS = p.NS, cend = p.T >> 7, nv = NS * CPS, nc = cend / (NP * CB) * CB + min(max((int)(cend % (NP * CB)) - q * CB, 0), CB);
    static_assert(QN <= 96, "retry moves two batches");
    F.lt = __shfl_sync(0xffffffffu, (1u << lane) - 1u, lane);
    F.lane = __shfl_sync(0xffffffffu, lane, lane);
    F.vb = __shfl_sync(0xffffffffu, q * (32 * CB) + lane, lane);
    F.f2 = __shfl_sync(0xffffffffu, __bfloat16_as_ushort(p.freq[0]) * 0x10001u, 0);
    F.qb = F.qt = SB + P_Q + w * (QN * 8);
    F.s0 = q % GR; F.xmax = 0;
    uint32_t c0 = w, c1 = w + FW;
    PIn x0, x1;
    F.fetch(p, x0, c0);
#pragma unroll 1
    while (c0 < nc) {
        F.fetch(p, x1, c1);
        c0 = F.chunk(x0);
        if (c1 >= nc) break;
        F.fetch(p, x0, c0);
        c1 = F.chunk(x1);
    }
    int left = (c0 < nv) + (c1 < nv);
#pragma unroll 1
    while (left > 0) { left -= F.use_ticket(F.ticket(0)) >= nv; F.enter(); F.end(); }
    if (q == 0 && w < 8) {
        const int t = cend * 128 + w * 16 + lane;
        const bool f = t < p.T && lane < 16;
        uint32_t i = 0, o = 0, x = 0;
        if (f) { i = p.idx_in[t]; o = p.idx_out[t]; asm("mul.rn.bf16x2 %0, %1, %2;" : "=r"(x) : "r"(__bfloat16_as_ushort(p.angle[t]) * 0x10001u), "r"(F.f2)); }
        F.xmax = __vmaxu2(F.xmax, x & 0x7fff7fffu);
        if (F.qt - F.qb >= 32 * 8) { F.begin(NS); F.enter(); F.retry(32); }
        F.push3(f, i, o, cos2(x & 0x7fff7fffu));
    }
    TS(8);
    F.begin(NS); F.enter();
    for (uint32_t nq = min((F.qt - F.qb) >> 3, (uint32_t)QN); nq > 0;) { uint32_t take = min(nq, 32u); F.retry(take); nq -= take; }
    F.end();
    if (CPS > FW && w < CPS - FW) F.end();
    if ((F.xmax + 0x3d803d80u) & 0x80008000u) st_relaxed(&g_ctl.bad, 1);
    TS(9);
    uint32_t* late = (uint32_t*)(smem + P_LATE);
    const float* sc = (const float*)(smem + S_MISC);
    mbar_wait(SB + S_MISC + 248, 0);
    __syncwarp();
    for (uint32_t a = F.qb + lane * 8; a < F.qt; a += 256) {
        uint2 e;
        asm volatile("ld.shared.v2.u32 {%0,%1}, [%2];" : "=r"(e.x), "=r"(e.y) : "r"(a) : "memory");
        const uint32_t i = e.x & 0xffffffu, o = e.y & 0xffffffu, ob = __umulhi(o, MAG_O);
        const float c = __uint_as_float(prmt(e.x, e.y, 0x7300) & 0xffff0000u);
        const uint32_t m0 = ld_relaxed(&g_md[0][i]), m1 = ld_relaxed(&g_md[1][i]);
        const uint32_t k = atomicAdd(&late[ob], 1);
        if (k < LATE_N) g_late[ob][q][k][0] = g_late[ob][q][k][1] = make_uint4(o - ob * ROWS_O, term(m0, c * sc[0], c * sc[1], MAG_LO, MAG_HI), term(m1, c * sc[2], c * sc[3], MAG_LO, MAG_HI), 0);
        else st_relaxed(&g_ctl.bad, 1);
    }
    asm volatile("bar.sync 2, %0;" ::"n"(FW * 32) : "memory");
    if (w == 0) {
        if (lane < 16) g_late_n[q][lane] = ((const uint4*)late)[lane];
        __syncwarp();
        if (lane == 0) { fence_release(); red_add(&g_ctl.late_done, 1); }
    }
}

template <int N> __device__ __forceinline__ void p_stamp(const uint32_t (&st)[N], uint32_t off, uint32_t bit, bool set) {
    if (set) {
#pragma unroll
        for (int j = 0; j < N; j++) asm volatile("red.shared.or.b32 [%0], %1;" ::"r"(st[j] + off), "r"(bit) : "memory");
    } else {
#pragma unroll
        for (int j = 0; j < N; j++) asm volatile("red.shared.and.b32 [%0], %1;" ::"r"(st[j] + off), "r"(~bit) : "memory");
    }
}
__device__ __forceinline__ void bulk_store(void* dst, uint32_t src, uint32_t bytes) {
    asm volatile("cp.async.bulk.global.shared::cta.bulk_group [%0], [%1], %2;" ::"l"(dst), "r"(src), "r"(bytes) : "memory");
}
__device__ __forceinline__ void p_flusher(const Prm& p, unsigned char* ring, uint32_t pagebits, int q, int f) {
    const int lane = threadIdx.x & 31;
    const uint32_t NS = p.NS, NT = p.NT, s0 = q % GR;
    uint32_t sta[4], stb[2];
#pragma unroll
    for (int j = 0; j < 4; j++) {
        const int pp = min(8 * j + (lane >> 2), 26), bin = min(32 * j + lane, NB - 1);
        sta[j] = SB + P_A + pp * 512 + (lane & 3) * 160 + ((pp % 9) & 3) * 4;
        if (j < 2) stb[j] = SB + P_B + bin * 128 + ((bin % NCP) & 15) * 8;
    }
    const uint32_t pfo = OFF_PF + (lane / 6) * 32 + (lane & 1) * 16 + ((lane % 6) >> 1) * 4, pfc = (lane >> 1) * 6 + (lane & 1);
    const uint32_t wto = lane < NCP ? OFF_REL + lane * 4 : OFF_RDY + (lane % 6) * 4;
    PROF_DECL
#pragma unroll 1
    for (uint32_t n = f; n < NT; n += NF) {
        const uint32_t buf = (n + s0) % NBUF, h = n >> 1, lap = h / RB;
        const uint32_t qb = q_base(q, pagebits) ^ (((n + q) & 1) << 12), bb = qb ^ slot_off(h % RB);
        if (n == 2 * NF - 1) {
            float sc[4]; bool bad;
            wait_ge(&g_ctl.pieces_done, NPC);
            fence_acquire();
            get_scales(p, sc, bad);
            if (lane == 0) { *(float4*)(smem + S_MISC) = make_float4(sc[0], sc[1], sc[2], sc[3]); mbar_arrive(SB + S_MISC + 248); }
            __syncwarp();
        }
        if (h >= RA && !DEV_FREE) {
            const uint32_t hw = lane < NCP ? h : h + RB - RA;
            wait_all_ge(ring + (qb ^ slot_off(hw % RB) ^ wto), hw / RB);
        }
        PROF(0);
#pragma unroll
        for (int d = 2; d >= 0; d--) {
            const int nl = (int)min(n, NS) - d;
            if (nl >= 0) mbar_wait(bar_done(nl + s0), ((nl + s0) / NBUF) & 1);
        }
        PROF(1);
        uint32_t* cnt = (uint32_t*)(smem + P_CNT) + buf * NB;
        {
            const uint32_t oa = buf * (NB * KS * 4), ob = buf * (NB * KS * 2);
            unsigned char* da = ring + (qb ^ slot_off(h % RA) ^ R_A);
            unsigned char* db = ring + (bb ^ R_B);
            p_stamp(sta, oa, 0x40000000u, (h / RA) & 1);
            p_stamp(stb, ob, 0x8000u, lap & 1);
            __syncwarp();
            if (elect_one()) {
                asm volatile("fence.proxy.async.shared::cta;" ::: "memory");
#pragma unroll
                for (int u = 0; u < UN; u++) {
                    bulk_store(da + u * R_UNIT, SB + P_A + oa + u * (NCP * KS * 4), 8 * KS * 4);
                    bulk_store(da + u * R_UNIT + 0x40000, SB + P_A + oa + (u * NCP + 8) * (KS * 4), (NCP - 8) * KS * 4);
                }
#pragma unroll
                for (int u = 0; u < UN; u++) bulk_store(db + u * R_UNIT, SB + P_B + ob + u * (NCP * KS * 2), NCP * KS * 2);
            }
            __syncwarp();
        }
        uint32_t wm = (lap + 1) << 21;
        if (lane < NCP) {
#pragma unroll
            for (int u = 0; u < 3; u++) wm |= min(cnt[pfc + 2 * u] >> 1, (uint32_t)KS) << (7 * u);
        }
        __syncwarp();
        const uint32_t c0 = n + NBUF < NT ? 0 : KS * 2;
        if (lane < NB / 2) ((uint2*)cnt)[lane] = make_uint2(c0, c0);
        PROF(3);
        asm volatile("cp.async.bulk.commit_group;" ::: "memory");
        asm volatile("cp.async.bulk.wait_group 0;" ::: "memory");
        __syncwarp();
        PROF(2);
        const bool safe = h < RB;
        if (!safe && lane < NCP) st_relaxed(ring + (bb ^ pfo), wm);
        if (n > 0) mbar_wait(bar_free(n - 1 + s0), ((n - 1 + s0) / NBUF) & 1);
        if (lane == 0) mbar_arrive(bar_free(buf));
        if (safe) {
            fence_release();
            if (lane < NCP) st_relaxed(ring + (bb ^ pfo), wm);
        }
        PROF(4);
    }
    PROF_END;
}
__device__ __forceinline__ void p_cleanup(unsigned char* ring, int q) {
    const int k = threadIdx.x / 24;
    if (k < 2 * RB) *(uint4*)(ring + ((q << 20) ^ ((k & 1) << 12) ^ slot_off(k >> 1) ^ OFF_PF) + (threadIdx.x % 24) * 16) = make_uint4(0, 0, 0, 0);
}

__device__ __forceinline__ void m_role(const Prm& p, unsigned char* ring, int X, int id) {
    const int tid = threadIdx.x, lane = tid & 31, w = __shfl_sync(0xffffffffu, tid >> 5, 0);
    const int ib = id >> 1, ty = id & 1;
    float* scs = (float*)(smem + S_MISC);
    if (w == 0) {
        const uint32_t bar = SB + S_AUX;
        if (lane == 0) mbar_init(bar, 1);
        wait_ge(&g_ctl.pieces_done, NPC);
        fence_acquire();
        if (lane == 0) {
            asm volatile("fence.proxy.async.global;" ::: "memory");
            asm volatile("fence.proxy.async.shared::cta;" ::: "memory");
            asm volatile("mbarrier.arrive.expect_tx.shared.b64 _, [%0], %1;" ::"r"(bar), "r"(ROWS_I * 4) : "memory");
            constexpr uint32_t PART = (ROWS_I * 4 / 8 + 127) / 128 * 128;
            for (uint32_t o = 0; o < ROWS_I * 4; o += PART)
                asm volatile("cp.async.bulk.shared::cluster.global.mbarrier::complete_tx::bytes [%0], [%1], %2, [%3];"
                             ::"r"(SB + o), "l"((const char*)(g_md[ty] + ib * ROWS_I) + o), "r"(min(PART, ROWS_I * 4 - o)), "r"(bar) : "memory");
        }
        __syncwarp();
            float sc[4]; bool bad;
        get_scales(p, sc, bad);
            if (bad) { st_relaxed(&g_ctl.bad, 1); sc[0] = sc[1] = sc[2] = sc[3] = 0.f; }
        int it = 0; uint32_t pb;
        while (!((pb = ld_relaxed(&g_ctl.pagebits)) >> 31)) backoff(it);
        if (lane == 0) { scs[0] = sc[0]; scs[1] = sc[1]; scs[2] = sc[2]; scs[3] = sc[3]; ((uint32_t*)scs)[4] = X ? ~pb : pb; ((uint32_t*)scs)[5] = bad; }
        mbar_wait(bar, 0);
    }
    __syncthreads();
    if (((uint32_t*)scs)[5]) {
        for (int k = tid; k < (int)ROWS_I; k += THREADS) ((uint32_t*)smem)[k] = 0;
        __syncthreads();
    }
    const uint32_t NT = p.NT;
    if (w >= MW) return;
    const uint32_t pagebits = ((uint32_t*)scs)[4];
    const int half = lane >> 4, k4 = (lane & 15) * 4;
    const float s_lo = scs[2 * ty], s_hi = scs[2 * ty + 1];
    const int il = ib / NG, gi = (ib % NG) * 2 + X;
    const uint32_t a_off = R_A + il * R_UNIT + lane * 16, v_off = ty * R_V1 + il * R_UNIT + lane * 16;
    const uint32_t f_off = OFF_PF + il * 32 + half * 16, r_off = OFF_REL + (lane % NCP) * 4;
    const uint32_t j = w % (NP / GR);
    PROF_DECL
#pragma unroll 1
    for (uint32_t n = w / (NP / GR); n < NT; n += MW / (NP / GR)) {
        const uint32_t q = ((gi - n) & (GR - 1)) + GR * j, h = n >> 1;
        const uint32_t qb = q_base(q, pagebits), bb = qb ^ slot_off(h % RB);
        const uint32_t tag = (h / RB + 1) << 21;
        uint4 cw; int it = 0;
        while (true) {
            cw = ld_relaxed4(ring + (bb ^ f_off));
            if (__all_sync(0xffffffffu, min(min(cw.x, cw.y), cw.z) >= tag)) break;
            if (DEV_FREE) { cw.x = (cw.x & 1) + (63 | 57 << 7 | 50 << 14); cw.y = (cw.y & 1) + (53 | 61 << 7 | 57 << 14); cw.z = (cw.z & 1) + (59 | 52 << 7 | 57 << 14); break; }
            backoff(it);
        }
        PROF(0);
        {
            const unsigned char* pa = ring + (qb ^ slot_off(h % RA) ^ a_off);
            unsigned char* pv = ring + (qb ^ slot_off(h % RV) ^ v_off);
            const uint32_t hv = h + RB - RV;
            const unsigned char* prel = ring + (qb ^ slot_off(hv % RB) ^ r_off);
            const uint32_t rel = ld_relaxed(prel);
            const uint32_t vlap = h / RV;
            const float mag_lo0 = MAG_LO + (float)(8192 + (vlap & 3) * 16384), mag_hi0 = MAG_HI + (float)(8192 + ((vlap >> 2) & 3) * 16384);
            const uint32_t stamp = ((h / RA) & (0x40100401u >> lane) & 1) << 30;
            uint4 a[9];
#define M_LOAD(ps) a[ps] = ld_relaxed4(pa + (ps) * 512 + ((ps) < 4 ? 0 : R_HI))
#pragma unroll
            for (int ps = 0; ps < MPF; ps++) M_LOAD(ps);
            if (!__all_sync(0xffffffffu, rel >= hv / RB) && !DEV_FREE) wait_all_ge(prel, hv / RB);
            PROF(3);
#pragma unroll
            for (int ps = 0; ps < 9; ps++) {
                const int rem = (int)(((ps < 3 ? cw.x : ps < 6 ? cw.y : cw.z) >> (7 * (ps % 3))) & 0x7f) - k4;
                if (ps % 3 == 0) {
#define M_STAMP(ps) (((ps) & 3) == 0 ? a[ps].x : ((ps) & 3) == 1 ? a[ps].y : ((ps) & 3) == 2 ? a[ps].z : a[ps].w)
                    while (true) {
                        M_STAMP(ps) ^= stamp; M_STAMP(ps + 1) ^= stamp; M_STAMP(ps + 2) ^= stamp;
                        if (!__any_sync(0xffffffffu, (M_STAMP(ps) | M_STAMP(ps + 1) | M_STAMP(ps + 2)) & 0x40000000u)) break;
                        if (DEV_FREE) { M_STAMP(ps) &= 0xbfffffffu; M_STAMP(ps + 1) &= 0xbfffffffu; M_STAMP(ps + 2) &= 0xbfffffffu; break; }
                        if (++it > SPIN_MAX) __trap();
                        M_LOAD(ps); M_LOAD(ps + 1); M_LOAD(ps + 2);
                    }
                }
                uint32_t aw[4] = {a[ps].x, a[ps].y, a[ps].z, a[ps].w}, mv[4], vw[4];
#pragma unroll
                for (int e = 0; e < 4; e++) { mv[e] = 0; lds_lt(mv[e], __dp2a_lo(aw[e], 4u, (uint32_t)SB), e, rem); }
#pragma unroll
                for (int e = 0; e < 4; e++) {
                    const float c = bf_hi(aw[e]);
                    vw[e] = term(mv[e], c * s_lo, c * s_hi, e ? MAG_LO : mag_lo0, e ? MAG_HI : mag_hi0);
                }
                asm volatile("st.global.v4.u32 [%0], {%1,%2,%3,%4};" ::"l"(pv + ps * 512 + (ps < 4 ? 0 : R_HI)), "r"(vw[0]), "r"(vw[1]), "r"(vw[2]), "r"(vw[3]) : "memory");
                if (ps + MPF < 9) M_LOAD(ps + MPF);
            }
            if (vlap == 0) fence_release();
        }
        st_lane0(ring + (bb ^ (OFF_RDY + (2 * il + ty) * 4)), cw.x >> 21, lane);
        PROF(1);
    }
    PROF_END;
}

__device__ __noinline__ void c_wrap(uint32_t row, int par, uint32_t old, uint32_t w) {
    const uint32_t nw = old + w, ov = ~(old ^ w) & (old ^ nw);
    int d = 0;
    if (ov & 0x8000u) d += (w & 0x8000u) ? -1 : 1;
    if (ov & 0x80000000u) d += (w & 0x80000000u) ? -16 : 16;
    if (d != 0) {
        uint32_t c;
        asm volatile("atom.shared.add.u32 %0, [%1], %2;" : "=r"(c) : "r"(SB + C_WRAP + row * 4), "r"(d << (8 * par)) : "memory");
        c = (c >> (8 * par)) + d;
        if (((c + 1) & 0xe) == 0 || ((c + 16) & 0xe0) == 0) st_relaxed(&g_ctl.bad, 1);
    }
}

#define CGRP 4
struct CTask { uint4 v[3]; uint2 b[3]; };
struct CWork {
    unsigned char* ring;
    uint32_t v_off, b_off, f_off, r_off, acc;
    uint32_t lap1, sv, sb, vtag, fw, stamp;
    int lane, dev_free;
    template <int ODD> __device__ __forceinline__ void issue(CTask& t) {
        if (!__all_sync(0xffffffffu, fw >= lap1)) {
            int it = 0;
            do {
                if (dev_free) break;
                backoff(it);
                fw = ld_relaxed(ring + (f_off ^ slot_off(sb) ^ (ODD << 20)));
            } while (!__all_sync(0xffffffffu, fw >= lap1));
        }
        {
            const unsigned char* pv = ring + (v_off ^ slot_off(sv) ^ (ODD << 20));
            const unsigned char* pb = ring + (b_off ^ slot_off(sb) ^ (ODD << 20));
#pragma unroll
            for (int ps = 0; ps < 3; ps++) {
                t.v[ps] = ld_relaxed4(pv + ps * R_UNIT);
                t.b[ps] = ld_relaxed2(pb + ps * R_UNIT);
            }
        }
        fw = ld_relaxed(ring + (f_off ^ slot_off(ODD ? (sb + 1 == RB ? 0 : sb + 1) : sb) ^ (!ODD << 20)));
    }
    template <int ODD> __device__ __forceinline__ void arrive(CTask& t) {
        {
            int it = 0;
            while (true) {
#pragma unroll
                for (int ps = 0; ps < 3; ps++) t.b[ps].x ^= stamp;
                if (!__any_sync(0xffffffffu, (((t.v[0].x ^ vtag) | (t.v[1].x ^ vtag) | (t.v[2].x ^ vtag)) & 0xc000c000u) | ((t.b[0].x | t.b[1].x | t.b[2].x) & 0x8000u))) break;
                if (dev_free) { for (int ps = 0; ps < 3; ps++) { t.v[ps].x = (t.v[ps].x & 0x3fff3fffu) | (vtag & 0xc000c000u); t.b[ps].x &= 0xffff7fffu; } break; }
                if (++it > SPIN_MAX) __trap();
#pragma unroll
                for (int ps = 0; ps < 3; ps++) {
                    t.v[ps] = ld_relaxed4(ring + (v_off ^ slot_off(sv) ^ (ODD << 20)) + ps * R_UNIT);
                    t.b[ps] = ld_relaxed2(ring + (b_off ^ slot_off(sb) ^ (ODD << 20)) + ps * R_UNIT);
                }
            }
#pragma unroll
            for (int ps = 0; ps < 3; ps++) t.v[ps].x -= vtag;
        }
        st_lane0(ring + (r_off ^ slot_off(sb) ^ (ODD << 20)), lap1, lane);
        if (ODD) {
            if (++sv == RV) { sv = 0; vtag += 0x4000u; if (vtag & 0x10000u) vtag += 0x3fff0000u; }
            if (++sb == RB) { sb = 0; lap1++; stamp ^= (((b_off >> 3) ^ (b_off >> 7)) & 15) == 0 ? 0x8000u : 0u; }
        }
    }
    __device__ __forceinline__ void add(const CTask& t) {
        const uint32_t vw[12] = {t.v[0].x, t.v[0].y, t.v[0].z, t.v[0].w, t.v[1].x, t.v[1].y, t.v[1].z, t.v[1].w, t.v[2].x, t.v[2].y, t.v[2].z, t.v[2].w};
        const uint32_t bw[6] = {t.b[0].x, t.b[0].y, t.b[1].x, t.b[1].y, t.b[2].x, t.b[2].y};
#pragma unroll
        for (int g = 0; g < 12; g += CGRP) {
            uint32_t old[CGRP], ov = 0;
#pragma unroll
            for (int e = g; e < g + CGRP; e++)
                asm volatile("atom.shared.add.u32 %0, [%1], %2;" : "=r"(old[e - g]) : "r"((e & 1) ? __dp2a_hi(bw[e >> 1], 0x08000008u, acc) : __dp2a_lo(bw[e >> 1], 0x08000008u, acc)), "r"(vw[e]) : "memory");
#pragma unroll
            for (int e = g; e < g + CGRP; e++) ov |= ~(old[e - g] ^ vw[e]) & (old[e - g] ^ (old[e - g] + vw[e]));
            if (__any_sync(0xffffffffu, ov & 0x80008000u)) {
#pragma unroll
                for (int e = g; e < g + CGRP; e++) c_wrap((e & 1) ? bw[e >> 1] >> 16 : bw[e >> 1] & 0xffffu, lane >> 4, old[e - g], vw[e]);
            }
        }
    }
};

__device__ __forceinline__ void c_role(const Prm& p, unsigned char* ring, int X, int c) {
    const int tid = threadIdx.x, lane = tid & 31, w = __shfl_sync(0xffffffffu, tid >> 5, 0);
    uint32_t* misc = (uint32_t*)(smem + S_MISC);
    Wts* wt = (Wts*)(smem + S_AUX);
    load_wts(p, wt);
    if (tid == 0) misc[6] = TAB_N;
    __syncthreads();
    if (w == 0) {
        float sc[4]; bool bad;
        wait_ge(&g_ctl.pieces_done, NPC);
        fence_acquire();
        get_scales(p, sc, bad);
        const float s = (lane & 2) ? ((lane & 1) ? sc[3] : sc[2]) : ((lane & 1) ? sc[1] : sc[0]);
        wt->ws[lane] *= s > 0.f ? 1.f / s : 0.f;
        int it = 0; uint32_t pb;
        while (!((pb = ld_relaxed(&g_ctl.pagebits)) >> 31)) backoff(it);
        misc[4] = X ? ~pb : pb;
    } else {
        const int r0 = (X * NCP + c) * ROWS_O, nr = min((int)ROWS_O, p.E - r0);
#pragma unroll 4
        for (int r = tid - 32; r < (int)ROWS_O / 2; r += THREADS - 32) {
            const uint32_t d2 = 2 * r < nr ? __ldg((const uint32_t*)(p.dist + r0) + r) : TAB_LO * 0x10001u;
            uint32_t e[2] = {(d2 & 0xffff) - TAB_LO, (d2 >> 16) - TAB_LO};
#pragma unroll
            for (int k = 0; k < 2; k++)
                if (e[k] >= TAB_N) {
                    const uint32_t d = e[k] + TAB_LO;
                    if ((d & 0x7f80) == 0x7f80) st_relaxed(&g_ctl.bad, 1);
                    e[k] = min(atomicAdd(&misc[6], 1u), 0xffffu);
                    if (e[k] < TAB_N + TAB_X) ((uint32_t*)(smem + C_TAB))[e[k] * 4] = d;
                }
            ((uint2*)(smem + C_WRAP))[r] = make_uint2(e[0] << 16 | 0x8888u, e[1] << 16 | 0x8888u);
        }
    }
    __syncthreads();
    if (w >= NP / 2) {
        const int nt = min(misc[6], (uint32_t)(TAB_N + TAB_X));
        for (int k = tid - NP * 16; k < nt; k += THREADS - NP * 16)
            ((uint4*)(smem + C_TAB))[k] = radial_bf16(wt, k < TAB_N ? TAB_LO + k : ((uint32_t*)(smem + C_TAB))[k * 4]);
        if (DEV_FREE) return;
        for (int it = 0; ld_relaxed(&g_ctl.late_done) == 0; it++) { __nanosleep(1000); if (it > SPIN_MAX) __trap(); }
        const int ob = X * NCP + c, nr = min((int)ROWS_O, p.E - ob * (int)ROWS_O);
        if (tid == THREADS - 1 && nr > 0) asm volatile("cp.async.bulk.prefetch.L2.global [%0], %1;" ::"l"(p.m + ob * ROWS_O), "r"(nr * 8) : "memory");
        for (int it = 0; ld_relaxed(&g_ctl.late_done) < NP; it++) { __nanosleep(100); if (it > SPIN_MAX) __trap(); }
        TS(9);
        fence_acquire();
        constexpr int LQ = NP / (2 * (NW - NP / 2));
        const int q0 = (tid - NP * 16) >> 4;
        uint32_t n[LQ], nmax = 0;
#pragma unroll
        for (int j = 0; j < LQ; j++) n[j] = ld_relaxed((const uint32_t*)g_late_n[q0 * LQ + j] + ob);
#pragma unroll
        for (int j = 0; j < LQ; j++) { n[j] = min(n[j], (uint32_t)LATE_N); nmax = max(nmax, n[j]); }
        nmax = __reduce_max_sync(0xffffffffu, nmax);
        for (uint32_t k = lane & 15; k < ((nmax + 15) & ~15u); k += 16) {
            uint4 e[LQ];
            uint32_t o0[LQ], o1[LQ], ov = 0;
#pragma unroll
            for (int j = 0; j < LQ; j++) { e[j] = make_uint4(lane, 0, 0, 0); if (k < n[j]) e[j] = ld_relaxed4(g_late[ob][q0 * LQ + j][k]); }
#pragma unroll
            for (int j = 0; j < LQ; j++) { o0[j] = atomicAdd((uint32_t*)smem + 2 * e[j].x, e[j].y); o1[j] = atomicAdd((uint32_t*)smem + 2 * e[j].x + 1, e[j].z); }
#pragma unroll
            for (int j = 0; j < LQ; j++) ov |= (~(o0[j] ^ e[j].y) & (o0[j] ^ (o0[j] + e[j].y))) | (~(o1[j] ^ e[j].z) & (o1[j] ^ (o1[j] + e[j].z)));
            if (ov & 0x80008000u) {
#pragma unroll
                for (int j = 0; j < LQ; j++) { c_wrap(e[j].x, 0, o0[j], e[j].y); c_wrap(e[j].x, 1, o1[j], e[j].z); }
            }
        }
        __syncwarp();
        TS(10);
    }
    const uint32_t pagebits = misc[4];
    if (w >= NP / 2) return;
    CWork W;
    const int par = lane >> 4;
    W.ring = ring; W.lane = __shfl_sync(0xffffffffu, lane, lane); W.dev_free = DEV_FREE;
    const uint32_t qb = q_base(2 * w + X, pagebits), k = lane & 15;
    W.acc = __shfl_sync(0xffffffffu, SB + par * 4, lane);
    W.v_off = __shfl_sync(0xffffffffu, qb ^ (par * R_V1 + (c < 8 ? 0 : R_HI) + c * 256 + k * 16), lane);
    W.b_off = __shfl_sync(0xffffffffu, qb ^ (R_B + c * 128 + k * 8), lane);
    W.f_off = __shfl_sync(0xffffffffu, qb ^ (OFF_RDY + (lane % 6) * 4), lane);
    W.r_off = qb ^ (OFF_REL + c * 4);
    W.lap1 = 1; W.sv = W.sb = W.fw = W.stamp = 0; W.vtag = 0x20002000u;
    const uint32_t NT = p.NT;
    CTask A, B;
    PROF_DECL
    W.issue<0>(A);
#pragma unroll 1
    for (uint32_t n = 2;; n += 2) {
        W.arrive<0>(A); PROF(1); W.issue<1>(B); PROF(0); W.add(A);
        W.arrive<1>(B);
        if (n >= NT) break;
        PROF(1); W.issue<0>(A); PROF(0); W.add(B);
    }
    W.add(B);
    TS(8);
    PROF_END;
}

__device__ __forceinline__ uint32_t bf2_mul(uint32_t a, uint32_t b) { uint32_t r; asm("mul.rn.bf16x2 %0, %1, %2;" : "=r"(r) : "r"(a), "r"(b)); return r; }
__device__ __forceinline__ uint32_t bf2_fma(uint32_t a, uint32_t b, uint32_t c) { uint32_t r; asm("fma.rn.bf16x2 %0, %1, %2, %3;" : "=r"(r) : "r"(a), "r"(b), "r"(c)); return r; }
__device__ __forceinline__ uint32_t c_agg(uint32_t a, uint32_t s, uint32_t wr, bool wrapped) {
    int x0 = (short)a, x1 = ((int)a >> 16) + ((a >> 15) & 1);
    if (wrapped) { const int w0 = (int)(wr & 15) - 8, w1 = (int)((wr >> 4) & 15) - 8; x0 += 65536 * w0; x1 += 65536 * w1 - w0; }
    return pack_bf16((float)x1 * bf_hi(s), (float)x0 * bf_lo(s));
}
__device__ __forceinline__ void c_epilogue(const Prm& p, int X, int c) {
    const int tid = threadIdx.x, lane = tid & 31;
    const Wts* wt = (const Wts*)(smem + S_AUX);
    uint32_t bw[4];
#pragma unroll
    for (int k = 0; k < 4; k++) {
        const int col = (k >> 1) * 2 + ((lane >> 2) & 1), row = (k & 1) * 2;
        bw[k] = (lane >> 3) == (lane & 3) ? pack_bf16(wt->wu[(row + 1) * 4 + col], wt->wu[row * 4 + col]) : 0u;
    }
    const int r0 = (X * NCP + c) * ROWS_O, np = max(min((int)ROWS_O, p.E - r0), 0) / 2;
    const uint4* mp = (const uint4*)(p.m + r0);
    uint4* op = (uint4*)(p.out + r0);
    constexpr int EB = 5;
#pragma unroll 1
    for (int rb = tid; rb - lane < np; rb += EB * THREADS) {
        uint4 mr[EB];
#pragma unroll
        for (int k = 0; k < EB; k++) mr[k] = __ldg(mp + min(rb + k * THREADS, np - 1));
#pragma unroll
        for (int k = 0; k < EB; k++) {
            const int r = min(rb + k * THREADS, np - 1);
            const uint4 a = ((const uint4*)smem)[r];
            const uint2 wr = ((const uint2*)(smem + C_WRAP))[r];
            const uint4 t0 = ((const uint4*)(smem + C_TAB))[min(wr.x >> 16, (uint32_t)(TAB_N + TAB_X - 1))];
            const uint4 t1 = ((const uint4*)(smem + C_TAB))[min(wr.y >> 16, (uint32_t)(TAB_N + TAB_X - 1))];
            const bool wrapped = __any_sync(0xffffffffu, prmt(wr.x, wr.y, 0x5410) != 0x88888888u);
            uint32_t a0, a1, a2, a3;
            if (wrapped) { a0 = c_agg(a.x, t0.x, wr.x, true); a2 = c_agg(a.y, t0.y, wr.x >> 8, true); a1 = c_agg(a.z, t1.x, wr.y, true); a3 = c_agg(a.w, t1.y, wr.y >> 8, true); }
            else { a0 = c_agg(a.x, t0.x, 0, false); a2 = c_agg(a.y, t0.y, 0, false); a1 = c_agg(a.z, t1.x, 0, false); a3 = c_agg(a.w, t1.y, 0, false); }
            float u[8];
#pragma unroll
            for (int h = 0; h < 2; h++)
                asm("mma.sync.aligned.m16n8k16.row.col.f32.bf16.bf16.f32 {%0,%1,%2,%3}, {%4,%5,%6,%7}, {%8,%9}, {%10,%10,%10,%10};"
                    : "=f"(u[4 * h]), "=f"(u[4 * h + 1]), "=f"(u[4 * h + 2]), "=f"(u[4 * h + 3])
                    : "r"(a0), "r"(a1), "r"(a2), "r"(a3), "r"(bw[2 * h]), "r"(bw[2 * h + 1]), "f"(0.f));
            const uint4 o = make_uint4(bf2_fma(pack_bf16(u[1], u[0]), t0.z, mr[k].x), bf2_fma(pack_bf16(u[5], u[4]), t0.w, mr[k].y),
                                       bf2_fma(pack_bf16(u[3], u[2]), t1.z, mr[k].z), bf2_fma(pack_bf16(u[7], u[6]), t1.w, mr[k].w));
            if (rb + k * THREADS < np) op[r] = o;
        }
    }
    if (((const uint32_t*)(smem + S_MISC))[6] > TAB_N + TAB_X) {
        for (int r = 2 * tid; r < 2 * np; r += (r & 1) ? 2 * THREADS - 1 : 1) {
            const uint32_t wr = ((const uint32_t*)(smem + C_WRAP))[r];
            if ((wr >> 16) < TAB_N + TAB_X) continue;
            const uint4 t = radial_bf16(wt, __bfloat16_as_ushort(p.dist[r0 + r]));
            const uint2 a = ((const uint2*)smem)[r];
            const uint32_t a0 = c_agg(a.x, t.x, wr, true), a1 = c_agg(a.y, t.y, wr >> 8, true);
            const float agg[4] = {bf_lo(a0), bf_hi(a0), bf_lo(a1), bf_hi(a1)}, g[4] = {bf_lo(t.z), bf_hi(t.z), bf_lo(t.w), bf_hi(t.w)};
            p.out[r0 + r] = finish_row(wt->wu, agg, g, p.m[r0 + r]);
        }
    }
}

__device__ __forceinline__ void grid_bar(unsigned* ctr) {
    __syncthreads();
    if (threadIdx.x == 0) { fence_gpu(); red_add(ctr, 1); wait_ge(ctr, gridDim.x); fence_gpu(); }
    __syncthreads();
}
__device__ __noinline__ void fallback(const Prm& p) {
    const int gt = blockIdx.x * THREADS + threadIdx.x, gs = gridDim.x * THREADS;
    Wts* wt = (Wts*)smem;
    __syncthreads();
    load_wts(p, wt);
    for (int e = gt; e < p.E; e += gs) g_acc[e] = make_float4(0.f, 0.f, 0.f, 0.f);
    grid_bar(&g_ctl.bar[0]);
    const float f = __bfloat162float(p.freq[0]);
    for (int t = gt; t < p.T; t += gs) {
        uint2 r = __ldg(p.m + p.idx_in[t]);
        float c = rbf16(cosf(rbf16(f * __bfloat162float(p.angle[t]))));
        asm volatile("red.global.add.v4.f32 [%0], {%1,%2,%3,%4};" ::"l"(g_acc + p.idx_out[t]), "f"(bf_lo(r.x) * c),
                     "f"(bf_hi(r.x) * c), "f"(bf_lo(r.y) * c), "f"(bf_hi(r.y) * c) : "memory");
    }
    grid_bar(&g_ctl.bar[1]);
    for (int e = gt; e < p.E; e += gs) {
        float4 a4 = __ldcg(g_acc + e);
        float a[4] = {a4.x, a4.y, a4.z, a4.w}, s[4], g[4];
        radial(wt, __bfloat162float(p.dist[e]), s, g);
        float agg[4];
#pragma unroll
        for (int j = 0; j < 4; j++) agg[j] = s[j] * (a[0] * wt->wd[j] + a[1] * wt->wd[4 + j] + a[2] * wt->wd[8 + j] + a[3] * wt->wd[12 + j]);
        p.out[e] = finish_row(wt->wu, agg, g, p.m[e]);
    }
}

__device__ __forceinline__ void smem_init(bool isp, int from, int to) {
    for (int k = from / 16 + threadIdx.x; k < to / 16; k += THREADS) {
        const bool b = isp && k >= P_B / 16 && k < P_Q / 16;
        const uint32_t z = b ? (k & 7) * 0x20002u : 0u, y = b ? z + 0x10001u : 0u;
        ((uint4*)smem)[k] = make_uint4(z, z, y, y);
    }
}

__global__ void __launch_bounds__(THREADS, 1) gemnet_kernel(const __grid_constant__ Prm p) {
    const int tid = threadIdx.x, lane = tid & 31, w = __shfl_sync(0xffffffffu, tid >> 5, 0);
    uint32_t* misc = (uint32_t*)(smem + S_MISC);
    bool run_fallback = true;
    if (!p.force_bad && __cvta_generic_to_shared(smem) == SB) {
        unsigned char* const ring = p.ring;
        uint32_t smid; asm("mov.u32 %0, %%smid;" : "=r"(smid));
        const int cls = smid < NM ? 0 : (smid < NM + NP - 4 || (smid >= 124 && smid < 128)) ? 2 : 1;
        if (lane == 0) {
            if (w < 2 && (cls != 2 || blockIdx.x == 0)) misc[16 + w] = probe(ring + OFF_PROBE + w * 4096 + ((blockIdx.x >> 7) << 20) + (blockIdx.x & 127) * 32);
            else if (blockIdx.x == 0 && w <= NPAGES) misc[16 + w] = probe(ring + ((size_t)(w - 1) << 21) + OFF_PROBE);
        }
        float wd[16];
        if (cls != 2 || blockIdx.x == 0) __syncthreads();
        if (tid == 0) {
            int pool = cls == 2 ? 4 : cls * 2 + (misc[16] > misc[17]), id = 0;
            for (int k = 0; k < 7; k++) {
                int cap = pool < 2 ? NMP : pool < 4 ? NCP : NP;
                id = atomicAdd(&g_ctl.ticket[pool], 1);
                if (id < cap) break;
                pool = k == 0 ? (pool == 4 ? 0 : pool ^ 1) : k - 1;
            }
            misc[8] = pool; misc[9] = id;
            if (pool != 4) down_load(p, pool < 2 ? pool * NMP + id : NM + (pool - 2) * NCP + id);
        }
        if (blockIdx.x == 0 && tid == 32) {
            uint32_t pb = 0x80000000u;
            for (int k = 1; k < NPAGES; k++) pb |= (uint32_t)((2 * misc[17 + k] > misc[16] + misc[17]) != (misc[16] > misc[17])) << k;
            st_relaxed(&g_ctl.pagebits, pb);
        }
#pragma unroll
        for (int k = 0; k < 16; k++) wd[k] = __bfloat162float(p.w_down[k]);
        if (cls == 2) smem_init(true, 0, S_PC);
        __syncthreads();
        const int pool = misc[8], id = misc[9];
        if (pool >= 2 && (pool < 4 || cls != 2)) smem_init(pool == 4, 0, S_PC);
        if (pool != 4) down_piece(p, pool < 2 ? pool * NMP + id : NM + (pool - 2) * NCP + id, wd);
        if (DEV_FREE && !(DEV_FREE & (pool == 4 ? 1 : pool < 2 ? 2 : 4))) {
        } else if (pool == 4) {
            smem_init(true, S_PC, S_MISC);
            __syncthreads();
            if (tid < 2 * NBUF) {
                const uint32_t a = tid < NBUF ? bar_done(tid) : bar_free(tid), cnt = tid < NBUF ? CPS : 1;
                mbar_init(a, cnt);
                if (tid % NBUF < id % GR) asm volatile("mbarrier.arrive.shared.b64 _, [%0], %1;" ::"r"(a), "r"(cnt) : "memory");
            }
            if (tid == 32) mbar_init(SB + S_MISC + 248, 1);
            __syncthreads();
            if (w < FW) p_filler(p, id, w);
            else if (w < FW + NF) {
                int it = 0; uint32_t pb;
                while (!((pb = ld_relaxed(&g_ctl.pagebits)) >> 31)) backoff(it);
                p_flusher(p, ring, __shfl_sync(0xffffffffu, pb, 0), id, w - FW);
            }
        } else if (pool < 2) {
            m_role(p, ring, pool, id);
        } else {
            c_role(p, ring, pool - 2, id);
        }
        __syncthreads();
        if (tid == 0) { fence_gpu(); red_add(&g_ctl.fin, 1); }
        if ((pool == 2 || pool == 3) && !DEV_FREE) c_epilogue(p, pool - 2, id);
        if (tid == 0) { wait_ge(&g_ctl.fin, NCTA); fence_gpu(); misc[10] = ld_relaxed(&g_ctl.bad); }
        __syncthreads();
        if (pool == 4) p_cleanup(ring, id);
        run_fallback = misc[10] && !DEV_FREE;
    }
    if (run_fallback) fallback(p);
    if (tid == 0) {
        fence_gpu();
        if (atomicAdd(&g_ctl.exited, 1) == gridDim.x - 1) {
            uint32_t* c = (uint32_t*)&g_ctl;
            for (int k = 0; k < 32; k++) c[k] = 0;
        }
    }
}

cudaTextureObject_t make_tex(const void* ptr, size_t bytes, int words) {
    cudaResourceDesc rd = {};
    rd.resType = cudaResourceTypeLinear;
    rd.res.linear.devPtr = (void*)ptr;
    rd.res.linear.desc = words == 4 ? cudaCreateChannelDesc<uint4>() : cudaCreateChannelDesc<uint2>();
    rd.res.linear.sizeInBytes = bytes;
    cudaTextureDesc td = {};
    td.readMode = cudaReadModeElementType;
    cudaTextureObject_t t = 0;
    if (cudaCreateTextureObject(&t, &rd, &td, nullptr) != cudaSuccess) { cudaGetLastError(); return 0; }
    return t;
}

}

extern "C" void kernel_launch(void* const* d_in, const int* in_sizes, int n_in, void* d_out, int out_size) {
    static Prm p = {};
    static int grid = 0;
    const int E = in_sizes[3], T = in_sizes[1];
    if (grid == 0 || p.idx_in != d_in[1] || p.idx_out != d_in[2] || p.angle != d_in[4] || p.E != E || p.T != T) {
        int dev = 0, sms = 0;
        cudaGetDevice(&dev);
        cudaDeviceGetAttribute(&sms, cudaDevAttrMultiProcessorCount, dev);
        cudaFuncSetAttribute(gemnet_kernel, cudaFuncAttributeMaxDynamicSharedMemorySize, SMEM_BYTES);
        p.E = E; p.T = T;
        p.NS = (((T / 128 + NP * CB - 1) / (NP * CB)) * CB + CPS - 1) / CPS;
        if (p.NS < 3) p.NS = 3;
        p.NT = (p.NS + GR) & ~1;
        void* rp = nullptr;
        cudaGetSymbolAddress(&rp, g_ring);
        p.ring = (unsigned char*)(((uintptr_t)rp + ((2u << 20) - 1)) & ~(uintptr_t)((2u << 20) - 1));
        bool fast = sms >= NCTA && E <= (int)FAST_E && (E & 1) == 0 && T >= 128 && T <= (1 << 29);
        if (fast) {
            p.t_in = make_tex(d_in[1], (size_t)(T / 128) * 512, 4);
            p.t_out = make_tex(d_in[2], (size_t)(T / 128) * 512, 4);
            p.t_ang = make_tex(d_in[4], (size_t)(T / 128) * 256, 2);
            fast = p.t_in && p.t_out && p.t_ang;
        }
        p.force_bad = !fast;
        grid = fast ? NCTA : sms;
    }
    p.m = (const uint2*)d_in[0];
    p.idx_in = (const int*)d_in[1];
    p.idx_out = (const int*)d_in[2];
    p.dist = (const __nv_bfloat16*)d_in[3];
    p.angle = (const __nv_bfloat16*)d_in[4];
    p.centers = (const __nv_bfloat16*)d_in[5];
    p.freq = (const __nv_bfloat16*)d_in[6];
    p.w_rbf = (const __nv_bfloat16*)d_in[7];
    p.w_sbf = (const __nv_bfloat16*)d_in[8];
    p.w_down = (const __nv_bfloat16*)d_in[9];
    p.w_up = (const __nv_bfloat16*)d_in[10];
    p.out = (uint2*)d_out;
    gemnet_kernel<<<grid, THREADS, SMEM_BYTES>>>(p);
}
```

```cpp
#include <cuda_runtime.h>
#include <cuda_bf16.h>
#include <stdint.h>

namespace {

constexpr int NI = 12;
constexpr int UN = 3;
constexpr int NG = NI / UN;
constexpr int GR = 2 * NG;
constexpr int NCP = 18;
constexpr int NO = 2 * NCP;
constexpr int KS = 64;
constexpr int NB = UN * NCP;
constexpr int NBUF = 10;
constexpr int NMP = 2 * NI;
constexpr int NP = 48, NM = 2 * NMP, NC = NO, NCTA = NP + NM + NC;
#define CPS_ 25
constexpr int CPS = CPS_;
#define FW_ 24
constexpr int FW = FW_;
constexpr int NF = 4;
#define RA_ 3
#define RV_ 3
#define RB_ 4
constexpr int RA = RA_, RV = RV_, RB = RB_;
#define QN_ 96
#define QTRIG_ 48
constexpr int QN = QN_, QTRIG = QTRIG_;
#define MW_ 18
constexpr int MW = MW_;
#define MPF_ 6
constexpr int MPF = MPF_;
constexpr int THREADS = 896, NW = THREADS / 32;
#define DEV_FREE 0
#define SLEEP_ 50

constexpr int RING_BYTES = NP << 20;
constexpr int NPAGES = RING_BYTES >> 21;
constexpr int MAX_E = 1 << 20;
constexpr int SMEM_BYTES = 232448;

constexpr int SB = 1024;

constexpr int P_CNT = 0;
constexpr int P_BAR = P_CNT + NBUF * NB * 4;
constexpr int P_TKT = P_BAR + 2 * NBUF * 8;
constexpr int P_LATE = P_TKT + 128;
constexpr int P_B = (P_LATE + 256 + 127) / 128 * 128;
constexpr int P_Q = P_B + NBUF * NB * KS * 2;
constexpr int P_A = SMEM_BYTES - 256 - NBUF * NB * KS * 4;
static_assert(P_Q + FW * QN * 8 + 512 <= P_A && P_A % 128 == 0, "P smem");
constexpr int S_MISC = SMEM_BYTES - 256;
constexpr int S_AUX = S_MISC - 512;

constexpr unsigned FAST_E = 640000;
constexpr unsigned magic_of(unsigned long long d) { return (unsigned)(((1ull << 32) + d - 1) / d); }
constexpr bool magic_ok(unsigned long long d) { return (magic_of(d) * d - (1ull << 32)) * FAST_E < (1ull << 32); }
constexpr unsigned pick_rows(unsigned lo) {
    unsigned d = (lo + 3) & ~3u;
    while (!magic_ok(d)) d += 4;
    return d;
}
constexpr unsigned ROWS_I = pick_rows((FAST_E + NI - 1) / NI), ROWS_O = pick_rows((FAST_E + NO - 1) / NO);
constexpr unsigned MAG_I = magic_of(ROWS_I), MAG_O = magic_of(ROWS_O), HALF_O = ROWS_O * NCP;
constexpr int C_WRAP = ROWS_O * 8, C_TAB = ROWS_O * 12, TAB_N = 1025, TAB_LO = 0x3f80 - 1024, TAB_X = (S_AUX - C_TAB) / 16 - TAB_N;
static_assert(ROWS_I * 4 <= S_AUX && TAB_X >= 100 && ROWS_I <= 65536 && ROWS_O <= 32768, "tables");

constexpr int NPC = NM + NC;
constexpr int PC_ROWS = ((FAST_E + NPC - 1) / NPC + 3) & ~3;
constexpr int S_PC = C_WRAP + 128 - C_WRAP % 128;
static_assert(S_PC + PC_ROWS * 8 + 1024 <= S_AUX, "pre-pass");
struct __align__(128) Ctl {
    unsigned ticket[5];
    unsigned pagebits;
    unsigned pieces_done, late_done;
    unsigned bad;
    unsigned fin;
    unsigned bar[3];
    unsigned exited;
    unsigned pad[18];
    float stat[NPC][8];
};

struct Prm {
    const uint2* m; const int* idx_in; const int* idx_out; const __nv_bfloat16* dist; const __nv_bfloat16* angle;
    const __nv_bfloat16* centers; const __nv_bfloat16* freq; const __nv_bfloat16* w_rbf; const __nv_bfloat16* w_sbf;
    const __nv_bfloat16* w_down; const __nv_bfloat16* w_up; uint2* out;
    cudaTextureObject_t t_in, t_out, t_ang;
    int E, T;
    unsigned char* ring;
    int NS, NT;
    int force_bad;
};

__device__ __align__(128) unsigned char g_ring[RING_BYTES + (2 << 20)];
__device__ Ctl g_ctl;
constexpr int LATE_N = 64;
__device__ uint4 g_late_n[NP][16];
__device__ uint4 g_late[NO][NP][LATE_N][2];
__device__ float4 g_acc[MAX_E];
__device__ __align__(128) uint32_t g_md[2][NI * ROWS_I];
#define TS(k)
#define PROF_DECL
#define PROF(k)
#define PROF_END

extern __shared__ __align__(128) unsigned char smem[];

__device__ __forceinline__ float bf_lo(uint32_t w) { return __uint_as_float(w << 16); }
__device__ __forceinline__ float bf_hi(uint32_t w) { return __uint_as_float(w & 0xffff0000u); }
__device__ __forceinline__ float rbf16(float x) { return __bfloat162float(__float2bfloat16_rn(x)); }
__device__ __forceinline__ uint32_t pack_bf16(float hi, float lo) {
    uint32_t r; asm("cvt.rn.bf16x2.f32 %0, %1, %2;" : "=r"(r) : "f"(hi), "f"(lo)); return r;
}
__device__ __forceinline__ uint32_t prmt(uint32_t a, uint32_t b, uint32_t c) {
    uint32_t r; asm("prmt.b32 %0, %1, %2, %3;" : "=r"(r) : "r"(a), "r"(b), "r"(c)); return r;
}
__device__ __forceinline__ uint32_t ld_relaxed(const void* p) {
    uint32_t v; asm volatile("ld.relaxed.gpu.global.u32 %0, [%1];" : "=r"(v) : "l"(p) : "memory"); return v;
}
__device__ __forceinline__ uint2 ld_relaxed2(const void* p) {
    uint2 v; asm volatile("ld.relaxed.gpu.global.v2.u32 {%0,%1}, [%2];" : "=r"(v.x), "=r"(v.y) : "l"(p) : "memory"); return v;
}
__device__ __forceinline__ uint4 ld_relaxed4(const void* p) {
    uint4 v; asm volatile("ld.relaxed.gpu.global.v4.u32 {%0,%1,%2,%3}, [%4];" : "=r"(v.x), "=r"(v.y), "=r"(v.z), "=r"(v.w) : "l"(p) : "memory"); return v;
}
__device__ __forceinline__ void st_relaxed(void* p, uint32_t v) { asm volatile("st.relaxed.gpu.global.u32 [%0], %1;" ::"l"(p), "r"(v) : "memory"); }
__device__ __forceinline__ void st_relaxed16(void* p, uint32_t v) { asm volatile("st.relaxed.gpu.global.u16 [%0], %1;" ::"l"(p), "h"((uint16_t)v) : "memory"); }
__device__ __forceinline__ void red_add(void* p, uint32_t v) { asm volatile("red.relaxed.gpu.global.add.u32 [%0], %1;" ::"l"(p), "r"(v) : "memory"); }
__device__ __forceinline__ void fence_gpu() { asm volatile("fence.acq_rel.gpu;" ::: "memory"); }
__device__ __forceinline__ void fence_acquire() { asm volatile("fence.acquire.gpu;" ::: "memory"); }
__device__ __forceinline__ void fence_release() { asm volatile("fence.release.gpu;" ::: "memory"); }
__device__ __forceinline__ void mbar_init(uint32_t a, uint32_t n) { asm volatile("mbarrier.init.shared.b64 [%0], %1;" ::"r"(a), "r"(n) : "memory"); }
__device__ __forceinline__ void mbar_arrive(uint32_t a) { asm volatile("mbarrier.arrive.shared.b64 _, [%0];" ::"r"(a) : "memory"); }
__device__ __forceinline__ bool mbar_try(uint32_t a, uint32_t ph) {
    uint32_t ok;
    asm volatile("{.reg .pred p; mbarrier.try_wait.parity.shared.b64 p, [%1], %2, %3; selp.u32 %0, 1, 0, p;}" : "=r"(ok) : "r"(a), "r"(ph), "r"(2000) : "memory");
    return ok;
}
__device__ __forceinline__ bool mbar_test(uint32_t a, uint32_t ph) {
    uint32_t ok;
    asm volatile("{.reg .pred p; mbarrier.test_wait.parity.shared.b64 p, [%1], %2; selp.u32 %0, 1, 0, p;}" : "=r"(ok) : "r"(a), "r"(ph) : "memory");
    return ok;
}
constexpr int SPIN_MAX = 1 << 22;
__device__ __forceinline__ void mbar_wait(uint32_t a, uint32_t ph) {
    int it = 0;
    while (!mbar_try(a, ph)) { if (++it > SPIN_MAX) __trap(); }
}
__device__ __forceinline__ void backoff(int& it) { __nanosleep(SLEEP_); if (++it > SPIN_MAX) __trap(); }
__device__ __forceinline__ void wait_ge(const void* p, uint32_t v) {
    int it = 0;
    while (ld_relaxed(p) < v) backoff(it);
}

__device__ __forceinline__ bool elect_one() {
    uint32_t r; asm volatile("{.reg .pred p; elect.sync _|p, 0xffffffff; selp.u32 %0, 1, 0, p;}" : "=r"(r)); return r;
}
__device__ __forceinline__ void st_lane0(void* p, uint32_t v, int lane) {
    asm volatile("{.reg .pred p; setp.eq.s32 p, %2, 0; @p st.relaxed.gpu.global.u32 [%0], %1;}" ::"l"(p), "r"(v), "r"(lane) : "memory");
}
__device__ __forceinline__ void wait_all_ge(const void* p, uint32_t v) {
    int it = 0;
    while (!__all_sync(0xffffffffu, ld_relaxed(p) >= v)) backoff(it);
}
__device__ __forceinline__ void gather4(uint32_t (&v)[4], const uint4& a, int n) {
    asm volatile("{.reg .pred p0, p1, p2, p3;\n"
                 "setp.gt.s32 p0, %8, 0; setp.gt.s32 p1, %8, 1; setp.gt.s32 p2, %8, 2; setp.gt.s32 p3, %8, 3;\n"
                 "mov.u32 %0, 0; mov.u32 %1, 0; mov.u32 %2, 0; mov.u32 %3, 0;\n"
                 "@p0 dp2a.lo.u32.u32 %0, %4, 4, 0; @p1 dp2a.lo.u32.u32 %1, %5, 4, 0; @p2 dp2a.lo.u32.u32 %2, %6, 4, 0; @p3 dp2a.lo.u32.u32 %3, %7, 4, 0;\n"
                 "@p0 ld.shared.u32 %0, [%0+%9]; @p1 ld.shared.u32 %1, [%1+%9]; @p2 ld.shared.u32 %2, [%2+%9]; @p3 ld.shared.u32 %3, [%3+%9];}"
                 : "=&r"(v[0]), "=&r"(v[1]), "=&r"(v[2]), "=&r"(v[3]) : "r"(a.x), "r"(a.y), "r"(a.z), "r"(a.w), "r"(n), "n"(SB));
}

constexpr uint32_t R_V1 = 0x03000, R_A = 0x81000, R_B = 0x82000, R_UNIT = 0x4000, R_HI = 0x40000 - 8 * 256;
__device__ __forceinline__ uint32_t q_base(uint32_t q, uint32_t pagebits_x) { return (q << 20) | (((pagebits_x >> (q >> 1)) & 1u) << 12); }
__device__ __forceinline__ uint32_t slot_off(uint32_t s) { return (s << 16) | (((s + 1) & 2) << 11); }
constexpr uint32_t OFF_PF = R_B + 3 * R_UNIT, OFF_RDY = OFF_PF + 128, OFF_REL = OFF_PF + 256;
constexpr uint32_t OFF_PROBE = 3 * R_UNIT;
static_assert(RA <= 4 && RV <= 4 && RB <= 8 && RA <= RB && RV <= RB, "ring");

__device__ __forceinline__ uint32_t probe(unsigned char* p) {
    volatile uint32_t* sink = (volatile uint32_t*)(smem + S_MISC + 240);
    asm volatile("st.global.v4.u32 [%0], {%1,%1,%1,%1};" ::"l"(p), "r"(0) : "memory");
    asm volatile("st.global.v4.u32 [%0], {%1,%1,%1,%1};" ::"l"(p + 16), "r"(0) : "memory");
    uint32_t best = 0xffffffffu;
#pragma unroll 1
    for (int r = 0; r < 3; r++) {
        uint32_t t0, t1, v;
        asm volatile("mov.u32 %0, %%clock;" : "=r"(t0)::"memory");
        asm volatile("atom.relaxed.gpu.global.add.u32 %0, [%1], 1;" : "=r"(v) : "l"(p) : "memory");
        *sink = v;
        asm volatile("mov.u32 %0, %%clock;" : "=r"(t1)::"memory");
        best = min(best, t1 - t0);
    }
    return best;
}

struct Wts { float c[8], wr[32], ws[32], wd[16], wu[16]; };
__device__ __forceinline__ void load_wts(const Prm& p, Wts* w) {
    int t = threadIdx.x;
    if (t < 8) w->c[t] = __bfloat162float(p.centers[t]);
    if (t < 32) { w->wr[t] = __bfloat162float(p.w_rbf[t]); w->ws[t] = __bfloat162float(p.w_sbf[t]); }
    if (t < 16) { w->wd[t] = __bfloat162float(p.w_down[t]); w->wu[t] = __bfloat162float(p.w_up[t]); }
}
__device__ __forceinline__ void radial(const Wts* w, float d, float s[4], float g[4]) {
#pragma unroll
    for (int j = 0; j < 4; j++) s[j] = g[j] = 0.f;
#pragma unroll
    for (int r = 0; r < 8; r++) {
        float x = rbf16(d - w->c[r]);
        float b = rbf16(__expf(rbf16(-10.0f * rbf16(x * x))));
#pragma unroll
        for (int j = 0; j < 4; j++) { s[j] += b * w->ws[r * 4 + j]; g[j] += b * w->wr[r * 4 + j]; }
    }
}
__device__ __noinline__ uint4 radial_bf16(const Wts* w, uint32_t dbits) {
    float s[4], g[4];
    radial(w, __uint_as_float(dbits << 16), s, g);
    return make_uint4(pack_bf16(s[1], s[0]), pack_bf16(s[3], s[2]), pack_bf16(g[1], g[0]), pack_bf16(g[3], g[2]));
}
__device__ __forceinline__ uint2 finish_row(const float* wu, const float agg[4], const float g[4], uint2 r) {
    float o[4];
    const float mm[4] = {bf_lo(r.x), bf_hi(r.x), bf_lo(r.y), bf_hi(r.y)};
#pragma unroll
    for (int j = 0; j < 4; j++) o[j] = mm[j] + (agg[0] * wu[j] + agg[1] * wu[4 + j] + agg[2] * wu[8 + j] + agg[3] * wu[12 + j]) * g[j];
    return make_uint2(pack_bf16(o[1], o[0]), pack_bf16(o[3], o[2]));
}
__device__ __forceinline__ uint2 down_row(const float* wd, uint32_t x, uint32_t y) {
    const float a[4] = {bf_lo(x), bf_hi(x), bf_lo(y), bf_hi(y)};
    float d[4];
#pragma unroll
    for (int j = 0; j < 4; j++) d[j] = a[0] * wd[j] + a[1] * wd[4 + j] + a[2] * wd[8 + j] + a[3] * wd[12 + j];
    return make_uint2(pack_bf16(d[1], d[0]), pack_bf16(d[3], d[2]));
}

__device__ __forceinline__ void down_load(const Prm& p, int pc) {
    const int r0 = pc * PC_ROWS / 2, nr = max(min((pc + 1) * PC_ROWS, p.E) / 2 - r0, 0);
    const uint32_t bar = SB + S_MISC + 248;
    mbar_init(bar, 1);
    asm volatile("fence.proxy.async.shared::cta;" ::: "memory");
    asm volatile("mbarrier.arrive.expect_tx.shared.b64 _, [%0], %1;" ::"r"(bar), "r"(nr * 16) : "memory");
    for (int o = 0; o < nr; o += 640)
        asm volatile("cp.async.bulk.shared::cluster.global.mbarrier::complete_tx::bytes [%0], [%1], %2, [%3];"
                     ::"r"(SB + S_PC + o * 16), "l"((const uint4*)p.m + r0 + o), "r"(min(640, nr - o) * 16), "r"(bar) : "memory");
}
__device__ __forceinline__ void down_piece(const Prm& p, int pc, const float* wd) {
    const int tid = threadIdx.x, lane = tid & 31, w = tid >> 5;
    const int r0 = pc * PC_ROWS / 2, nr = max(min((pc + 1) * PC_ROWS, p.E) / 2 - r0, 0);
    mbar_wait(SB + S_MISC + 248, 0);
    uint32_t mx0 = 0, mx1 = 0; float ss[4] = {0.f, 0.f, 0.f, 0.f};
    for (int r = tid; r < nr; r += THREADS) {
        const uint4 v = ((const uint4*)(smem + S_PC))[r];
        const uint2 a = down_row(wd, v.x, v.y), b = down_row(wd, v.z, v.w);
        ((uint2*)g_md[0])[r0 + r] = make_uint2(a.x, b.x); ((uint2*)g_md[1])[r0 + r] = make_uint2(a.y, b.y);
        mx0 = __vimax3_u16x2(mx0, a.x & 0x7fff7fffu, b.x & 0x7fff7fffu); mx1 = __vimax3_u16x2(mx1, a.y & 0x7fff7fffu, b.y & 0x7fff7fffu);
        ss[0] += bf_lo(a.x) * bf_lo(a.x) + bf_lo(b.x) * bf_lo(b.x); ss[1] += bf_hi(a.x) * bf_hi(a.x) + bf_hi(b.x) * bf_hi(b.x);
        ss[2] += bf_lo(a.y) * bf_lo(a.y) + bf_lo(b.y) * bf_lo(b.y); ss[3] += bf_hi(a.y) * bf_hi(a.y) + bf_hi(b.y) * bf_hi(b.y);
    }
    uint32_t st[4] = {mx0 << 16, mx0 & 0xffff0000u, mx1 << 16, mx1 & 0xffff0000u};
    uint4* red = (uint4*)(smem + S_PC + PC_ROWS * 8);
    for (int pass = 0; pass < 2; pass++) {
#pragma unroll
        for (int ch = 0; ch < 4; ch++) {
            st[ch] = __reduce_max_sync(0xffffffffu, st[ch]);
#pragma unroll
            for (int o = 16; o; o >>= 1) ss[ch] += __shfl_xor_sync(0xffffffffu, ss[ch], o);
        }
        uint4* dst = pass ? (uint4*)g_ctl.stat[pc] : red + 2 * w;
        if (lane == 0) { dst[0] = make_uint4(st[0], st[1], st[2], st[3]); dst[1] = make_uint4(__float_as_uint(ss[0]), __float_as_uint(ss[1]), __float_as_uint(ss[2]), __float_as_uint(ss[3])); }
        if (pass) break;
        __syncthreads();
        const uint4 a = lane < NW ? red[2 * lane] : make_uint4(0, 0, 0, 0), b = lane < NW ? red[2 * lane + 1] : make_uint4(0, 0, 0, 0);
        __syncthreads();
        if (w != NW - 1) return;
        st[0] = a.x; st[1] = a.y; st[2] = a.z; st[3] = a.w;
        ss[0] = __uint_as_float(b.x); ss[1] = __uint_as_float(b.y); ss[2] = __uint_as_float(b.z); ss[3] = __uint_as_float(b.w);
    }
    if (lane == 0) { fence_release(); red_add(&g_ctl.pieces_done, 1); }
    __syncwarp();
}

#define KAPPA 3.3f
__device__ __forceinline__ void get_scales(const Prm& p, float sc[4], bool& bad) {
    const int lane = threadIdx.x & 31;
    uint32_t mxb[4] = {0, 0, 0, 0};
    float ss[4] = {0.f, 0.f, 0.f, 0.f};
#pragma unroll
    for (int k = 0; k < (NPC + 31) / 32; k++) {
        if (lane + 32 * k < NPC) {
            const uint4 a = ld_relaxed4(&g_ctl.stat[lane + 32 * k][0]), b = ld_relaxed4(&g_ctl.stat[lane + 32 * k][4]);
            mxb[0] = max(mxb[0], a.x); mxb[1] = max(mxb[1], a.y); mxb[2] = max(mxb[2], a.z); mxb[3] = max(mxb[3], a.w);
            ss[0] += __uint_as_float(b.x); ss[1] += __uint_as_float(b.y); ss[2] += __uint_as_float(b.z); ss[3] += __uint_as_float(b.w);
        }
    }
    bad = false;
    const float kdeg = fminf(KAPPA * sqrtf(fmaxf(0.5f * (float)p.T / (float)p.E, 1.0f)), 128.f);
#pragma unroll
    for (int ch = 0; ch < 4; ch++) {
        const float mx = __uint_as_float(__reduce_max_sync(0xffffffffu, mxb[ch]));
#pragma unroll
        for (int o = 16; o; o >>= 1) ss[ch] += __shfl_xor_sync(0xffffffffu, ss[ch], o);
        const float rms = sqrtf(ss[ch] / (float)p.E);
        const float range = fmaxf(2.001f * mx, kdeg * rms);
        if (!(mx <= 1e15f) || !(range <= 128.f * rms) || (mx > 0.f && mx < 1e-15f)) bad = true;
        sc[ch] = range > 0.f ? __uint_as_float(((__float_as_uint(range) + 0x7fffffu) & 0x7f800000u) - (15u << 23)) : 1.f;
    }
    if (bad) sc[0] = sc[1] = sc[2] = sc[3] = 1.f;
}

__device__ __forceinline__ float magic_lo(float step_lo) { return 12582912.f * step_lo; }
__device__ __forceinline__ float magic_hi(float step_lo, float step_hi) { return (float)(12582912 - (int)(__float_as_uint(magic_lo(step_lo)) >> 16)) * step_hi; }
__device__ __forceinline__ uint32_t term(uint32_t m, float c, float mag_lo, float mag_hi) {
    return (__float_as_uint(fmaf(bf_hi(m), c, mag_hi)) << 16) + __float_as_uint(fmaf(bf_lo(m), c, mag_lo));
}

constexpr int PER = 40;
__host__ __device__ constexpr uint32_t bar_done(uint32_t s) { return SB + P_BAR + (s % NBUF) * 16; }
__host__ __device__ constexpr uint32_t bar_free(uint32_t m) { return bar_done(m + NBUF - (GR - 1)) + 8; }
struct __align__(16) PTab { uint32_t e[PER][4]; };
constexpr PTab make_ptab() {
    PTab t = {};
    for (int s = 0; s < PER; s++) {
        for (int d = 0; d < GR; d++) {
            int gi = (s + d) % GR, buf = (s + d) % NBUF, X = gi & 1, g = gi >> 1;
            t.e[s][X] |= (uint32_t)(4 * UN * buf - g - 4 * X + 7) << (8 * g);
        }
        t.e[s][2] = bar_done(s);
        t.e[s][3] = (((s + GR - 1) / NBUF) & 1) ^ 1;
    }
    return t;
}
__constant__ PTab c_ptab = make_ptab();
constexpr int BIAS = 7 * NCP;
static_assert(NG == 4 && CPS >= FW, "group selection");

struct PCtx { uint32_t a0, a1; };
struct PElem { uint32_t b4, aw, ol, r2; };

__device__ __forceinline__ void p_bin(const PCtx& c, PElem& e, uint32_t i, uint32_t o) {
    uint32_t ib = __umulhi(i, MAG_I), ob = __umulhi(o, MAG_O), sel = ib & 3;
    asm("{.reg .pred p; setp.ge.u32 p, %1, %2; @p add.u32 %0, %0, 4;}" : "+r"(sel) : "r"(o), "n"(HALF_O));
    e.b4 = __dp4a(prmt(c.a0, c.a1, sel), (uint32_t)NCP, ib * NCP + ob * 4);
    e.aw = i - ib * ROWS_I;
    e.ol = o - ob * ROWS_O;
}
__device__ __forceinline__ void p_rank(PElem& e) {
    asm volatile("atom.shared.add.u32 %0, [%1+%2], 2;" : "=r"(e.r2) : "r"(e.b4), "n"(SB + P_CNT - BIAS) : "memory");
}
__device__ __forceinline__ void p_store(const PElem& e) {
    const uint32_t ab = e.b4 * (KS / 2) + e.r2;
    asm volatile("{.reg .pred p; setp.lt.u32 p, %4, %5; @p st.shared.u32 [%0+%6], %1; @p st.shared.u16 [%2+%7], %3;}"
                 ::"r"(ab * 2), "r"(e.aw), "r"(ab), "h"((uint16_t)e.ol), "r"(e.r2), "n"(KS * 2),
                   "n"(SB + P_A - BIAS * KS), "n"(SB + P_B - BIAS * (KS / 2)) : "memory");
}
__device__ __forceinline__ uint32_t cos2(uint32_t x) {
    x = __vminu2(x, 0x42804280u);
    return pack_bf16(__cosf(bf_hi(x)), __cosf(bf_lo(x)));
}

#define PD_ 2
#define CB_ 8
constexpr int CB = CB_;
struct PIn { uint4 i, o; uint2 a; };

struct PFill {
    PCtx c;
    uint32_t qb, qt, lt, f2, bar, par, xmax;
    uint32_t s0, lane, vb;
    bool open;
    __device__ __forceinline__ void fetch(const Prm& p, PIn& x, uint32_t ch) {
        const int v = ((ch & ~(CB - 1u)) * (NP - 1) + ch) * 32 + vb;
        asm volatile("{.reg .b32 d0, d1; tex.1d.v4.u32.s32 {%0,%1,d0,d1}, [%2, {%3}];}" : "=r"(x.a.x), "=r"(x.a.y) : "l"(p.t_ang), "r"(v));
        asm volatile("tex.1d.v4.u32.s32 {%0,%1,%2,%3}, [%4, {%5}];" : "=r"(x.i.x), "=r"(x.i.y), "=r"(x.i.z), "=r"(x.i.w) : "l"(p.t_in), "r"(v));
        asm volatile("tex.1d.v4.u32.s32 {%0,%1,%2,%3}, [%4, {%5}];" : "=r"(x.o.x), "=r"(x.o.y), "=r"(x.o.z), "=r"(x.o.w) : "l"(p.t_out), "r"(v));
    }
    __device__ __forceinline__ uint32_t ticket(uint32_t zero) {
        uint32_t t;
        asm volatile("atom.shared.add.u32 %0, [%1+%2], %3;" : "=r"(t) : "r"(lane * 4), "n"(SB + P_TKT), "r"((~lt & 1) | zero) : "memory");
        return t;
    }
    __device__ __forceinline__ uint32_t use_ticket(uint32_t t) {
        t = __reduce_or_sync(0xffffffffu, t);
        begin(t / CPS);
        return t + PD_ * FW;
    }
    __device__ __forceinline__ void begin(uint32_t step) {
        const uint4 t = ((const uint4*)c_ptab.e)[(step + s0) % PER];
        c.a0 = t.x; c.a1 = t.y; bar = t.z; par = t.w;
        open = mbar_test(bar + 8, par);
    }
    __device__ __forceinline__ void enter() { if (!open) mbar_wait(bar + 8, par); }
    __device__ __forceinline__ void end() {
        __syncwarp();
        asm volatile("{.reg .pred p; setp.eq.u32 p, %1, 0; @p mbarrier.arrive.shared.b64 _, [%0];}" ::"r"(bar), "r"(lt) : "memory");
    }
    __device__ __forceinline__ void push(bool f, uint32_t x, uint32_t y) {
        const uint32_t mask = __ballot_sync(0xffffffffu, f);
        asm volatile("{.reg .pred p; setp.ne.u32 p, %3, 0; @p st.shared.v2.u32 [%0], {%1,%2};}"
                     ::"r"(min(qt + __popc(mask & lt) * 8, qb + (QN - 1) * 8)), "r"(x), "r"(y), "r"((uint32_t)f) : "memory");
        qt += __popc(mask) * 8;
    }
    __device__ __forceinline__ void push3(bool f, uint32_t i, uint32_t o, uint32_t aw) { push(f, prmt(i, aw, 0x6210), prmt(o, aw, 0x7210)); }
    __device__ __forceinline__ uint32_t chunk(const PIn& x) {
        uint32_t x0, x1;
        const uint32_t tk = use_ticket(ticket(x.o.x >> 31));
        PElem e0, e1, e2, e3;
        p_bin(c, e0, x.i.x, x.o.x); p_bin(c, e1, x.i.y, x.o.y); p_bin(c, e2, x.i.z, x.o.z); p_bin(c, e3, x.i.w, x.o.w);
        asm volatile("" : "+r"(e0.b4), "+r"(e1.b4), "+r"(e2.b4), "+r"(e3.b4));
        enter();
        p_rank(e0); p_rank(e1); p_rank(e2); p_rank(e3);
        asm volatile("mul.rn.bf16x2 %0, %1, %2;" : "=r"(x0) : "r"(x.a.x), "r"(f2));
        asm volatile("mul.rn.bf16x2 %0, %1, %2;" : "=r"(x1) : "r"(x.a.y), "r"(f2));
        x0 &= 0x7fff7fffu; x1 &= 0x7fff7fffu;
        xmax = __vimax3_u16x2(xmax, x0, x1);
        const uint32_t c0 = cos2(x0), c1 = cos2(x1);
        e0.aw = prmt(e0.aw, c0, 0x5410); e1.aw = prmt(e1.aw, c0, 0x7610); e2.aw = prmt(e2.aw, c1, 0x5410); e3.aw = prmt(e3.aw, c1, 0x7610);
        p_store(e0); p_store(e1); p_store(e2); p_store(e3);
        if (qt - qb >= QTRIG * 8) retry(32);
        end();
        const uint32_t r01 = e0.r2 | e1.r2, r23 = e2.r2 | e3.r2;
        const bool f = (r01 | r23) >= KS * 2;
        if (__any_sync(0xffffffffu, f)) {
            const bool f0 = e0.r2 >= KS * 2, f1 = e1.r2 >= KS * 2, f2_ = e2.r2 >= KS * 2, f3 = e3.r2 >= KS * 2, f01 = r01 >= KS * 2;
            push3(f, f01 ? (f0 ? x.i.x : x.i.y) : (f2_ ? x.i.z : x.i.w), f01 ? (f0 ? x.o.x : x.o.y) : (f2_ ? x.o.z : x.o.w),
                  f01 ? (f0 ? e0.aw : e1.aw) : (f2_ ? e2.aw : e3.aw));
            const uint32_t s2 = max(max(min(e0.r2, e1.r2), min(e2.r2, e3.r2)), min(r01, r23));
            if (__any_sync(0xffffffffu, s2 >= KS * 2)) {
                push3(f1 && f0, x.i.y, x.o.y, e1.aw); push3(f2_ && f01, x.i.z, x.o.z, e2.aw); push3(f3 && (f01 || f2_), x.i.w, x.o.w, e3.aw);
            }
        }
        return tk;
    }
    __device__ __forceinline__ void retry(uint32_t take) {
        if (qt - qb > QN * 8) { st_relaxed(&g_ctl.bad, 1); qt = qb + QN * 8; }
        uint2 e, r, r1;
        __syncwarp();
        asm volatile("ld.shared.v2.u32 {%0,%1}, [%2];" : "=r"(e.x), "=r"(e.y) : "r"(qb + lane * 8) : "memory");
        asm volatile("ld.shared.v2.u32 {%0,%1}, [%2];" : "=r"(r.x), "=r"(r.y) : "r"(qb + (lane + take) * 8) : "memory");
        qt -= take * 8;
        const bool more = qt - qb > 256;
        if (more) asm volatile("ld.shared.v2.u32 {%0,%1}, [%2];" : "=r"(r1.x), "=r"(r1.y) : "r"(qb + (lane + take) * 8 + 256) : "memory");
        __syncwarp();
        if (more && qb + lane * 8 + 256 < qt) asm volatile("st.shared.v2.u32 [%0], {%1,%2};" ::"r"(qb + lane * 8 + 256), "r"(r1.x), "r"(r1.y) : "memory");
        if (qb + lane * 8 < qt) asm volatile("st.shared.v2.u32 [%0], {%1,%2};" ::"r"(qb + lane * 8), "r"(r.x), "r"(r.y) : "memory");
        PElem el;
        el.r2 = 0;
        if (take == 32 || lane < take) {
            p_bin(c, el, e.x & 0xffffffu, e.y & 0xffffffu);
            el.aw = prmt(el.aw, prmt(e.x, e.y, 0x0073), 0x5410);
            p_rank(el);
            p_store(el);
        }
        push(el.r2 >= KS * 2, e.x, e.y);
    }
};

__device__ __forceinline__ void p_filler(const Prm& p, int q, int w) {
    PFill F;
    const int lane = threadIdx.x & 31;
    const uint32_t NS = p.NS, cend = p.T >> 7, nv = NS * CPS, nc = cend / (NP * CB) * CB + min(max((int)(cend % (NP * CB)) - q * CB, 0), CB);
    static_assert(QN <= 96, "retry moves two batches");
    F.lt = __shfl_sync(0xffffffffu, (1u << lane) - 1u, lane);
    F.lane = __shfl_sync(0xffffffffu, lane, lane);
    F.vb = __shfl_sync(0xffffffffu, q * (32 * CB) + lane, lane);
    F.f2 = __shfl_sync(0xffffffffu, __bfloat16_as_ushort(p.freq[0]) * 0x10001u, 0);
    F.qb = F.qt = SB + P_Q + w * (QN * 8);
    F.s0 = q % GR; F.xmax = 0;
    uint32_t c0 = w, c1 = w + FW;
    PIn x0, x1;
    F.fetch(p, x0, c0);
#pragma unroll 1
    while (c0 < nc) {
        F.fetch(p, x1, c1);
        c0 = F.chunk(x0);
        if (c1 >= nc) break;
        F.fetch(p, x0, c0);
        c1 = F.chunk(x1);
    }
    int left = (c0 < nv) + (c1 < nv);
#pragma unroll 1
    while (left > 0) { left -= F.use_ticket(F.ticket(0)) >= nv; F.enter(); F.end(); }
    if (q == 0 && w < 8) {
        const int t = cend * 128 + w * 16 + lane;
        const bool f = t < p.T && lane < 16;
        uint32_t i = 0, o = 0, x = 0;
        if (f) { i = p.idx_in[t]; o = p.idx_out[t]; asm("mul.rn.bf16x2 %0, %1, %2;" : "=r"(x) : "r"(__bfloat16_as_ushort(p.angle[t]) * 0x10001u), "r"(F.f2)); }
        F.xmax = __vmaxu2(F.xmax, x & 0x7fff7fffu);
        if (F.qt - F.qb >= 32 * 8) { F.begin(NS); F.enter(); F.retry(32); }
        F.push3(f, i, o, cos2(x & 0x7fff7fffu));
    }
    TS(8);
    F.begin(NS); F.enter();
    for (uint32_t nq = min((F.qt - F.qb) >> 3, (uint32_t)QN); nq > 0;) { uint32_t take = min(nq, 32u); F.retry(take); nq -= take; }
    F.end();
    if (CPS > FW && w < CPS - FW) F.end();
    if ((F.xmax + 0x3d803d80u) & 0x80008000u) st_relaxed(&g_ctl.bad, 1);
    TS(9);
    uint32_t* late = (uint32_t*)(smem + P_LATE);
    const float* sc = (const float*)(smem + S_MISC);
    mbar_wait(SB + S_MISC + 248, 0);
    __syncwarp();
    for (uint32_t a = F.qb + lane * 8; a < F.qt; a += 256) {
        uint2 e;
        asm volatile("ld.shared.v2.u32 {%0,%1}, [%2];" : "=r"(e.x), "=r"(e.y) : "r"(a) : "memory");
        const uint32_t i = e.x & 0xffffffu, o = e.y & 0xffffffu, ob = __umulhi(o, MAG_O);
        const float c = __uint_as_float(prmt(e.x, e.y, 0x7300) & 0xffff0000u);
        const uint32_t m0 = ld_relaxed(&g_md[0][i]), m1 = ld_relaxed(&g_md[1][i]);
        const uint32_t k = atomicAdd(&late[ob], 1);
        if (k < LATE_N) g_late[ob][q][k][0] = g_late[ob][q][k][1] = make_uint4(o - ob * ROWS_O, term(m0, c, magic_lo(sc[0]), magic_hi(sc[0], sc[1])), term(m1, c, magic_lo(sc[2]), magic_hi(sc[2], sc[3])), 0);
        else st_relaxed(&g_ctl.bad, 1);
    }
    asm volatile("bar.sync 2, %0;" ::"n"(FW * 32) : "memory");
    if (w == 0) {
        if (lane < 16) g_late_n[q][lane] = ((const uint4*)late)[lane];
        __syncwarp();
        if (lane == 0) { fence_release(); red_add(&g_ctl.late_done, 1); }
    }
}

template <int N> __device__ __forceinline__ void p_stamp(const uint32_t (&st)[N], uint32_t off, uint32_t bit, bool set) {
    if (set) {
#pragma unroll
        for (int j = 0; j < N; j++) asm volatile("red.shared.or.b32 [%0], %1;" ::"r"(st[j] + off), "r"(bit) : "memory");
    } else {
#pragma unroll
        for (int j = 0; j < N; j++) asm volatile("red.shared.and.b32 [%0], %1;" ::"r"(st[j] + off), "r"(~bit) : "memory");
    }
}
__device__ __forceinline__ void bulk_store(void* dst, uint32_t src, uint32_t bytes) {
    asm volatile("cp.async.bulk.global.shared::cta.bulk_group [%0], [%1], %2;" ::"l"(dst), "r"(src), "r"(bytes) : "memory");
}
__device__ __forceinline__ void p_flusher(const Prm& p, unsigned char* ring, uint32_t pagebits, int q, int f) {
    const int lane = threadIdx.x & 31;
    const uint32_t NS = p.NS, NT = p.NT, s0 = q % GR;
    uint32_t sta[4], stb[2];
#pragma unroll
    for (int j = 0; j < 4; j++) {
        const int pp = min(8 * j + (lane >> 2), 26), bin = min(32 * j + lane, NB - 1);
        sta[j] = SB + P_A + pp * 512 + (lane & 3) * 160 + ((pp % 9) & 3) * 4;
        if (j < 2) stb[j] = SB + P_B + bin * 128 + ((bin % NCP) & 15) * 8;
    }
    const uint32_t pfo = OFF_PF + (lane / 6) * 32 + (lane & 1) * 16 + ((lane % 6) >> 1) * 4, pfc = (lane >> 1) * 6 + (lane & 1);
    const uint32_t wto = lane < NCP ? OFF_REL + lane * 4 : OFF_RDY + (lane % 6) * 4;
    PROF_DECL
#pragma unroll 1
    for (uint32_t n = f; n < NT; n += NF) {
        const uint32_t buf = (n + s0) % NBUF, h = n >> 1, lap = h / RB;
        const uint32_t qb = q_base(q, pagebits) ^ (((n + q) & 1) << 12), bb = qb ^ slot_off(h % RB);
        if (n == 2 * NF - 1) {
            float sc[4]; bool bad;
            wait_ge(&g_ctl.pieces_done, NPC);
            fence_acquire();
            get_scales(p, sc, bad);
            if (lane == 0) { *(float4*)(smem + S_MISC) = make_float4(sc[0], sc[1], sc[2], sc[3]); mbar_arrive(SB + S_MISC + 248); }
            __syncwarp();
        }
        if (h >= RA && !DEV_FREE) {
            const uint32_t hw = lane < NCP ? h : h + RB - RA;
            wait_all_ge(ring + (qb ^ slot_off(hw % RB) ^ wto), hw / RB);
        }
        PROF(0);
#pragma unroll
        for (int d = 2; d >= 0; d--) {
            const int nl = (int)min(n, NS) - d;
            if (nl >= 0) mbar_wait(bar_done(nl + s0), ((nl + s0) / NBUF) & 1);
        }
        PROF(1);
        uint32_t* cnt = (uint32_t*)(smem + P_CNT) + buf * NB;
        {
            const uint32_t oa = buf * (NB * KS * 4), ob = buf * (NB * KS * 2);
            unsigned char* da = ring + (qb ^ slot_off(h % RA) ^ R_A);
            unsigned char* db = ring + (bb ^ R_B);
            p_stamp(sta, oa, 0x40000000u, (h / RA) & 1);
            p_stamp(stb, ob, 0x8000u, lap & 1);
            __syncwarp();
            if (elect_one()) {
                asm volatile("fence.proxy.async.shared::cta;" ::: "memory");
#pragma unroll
                for (int u = 0; u < UN; u++) {
                    bulk_store(da + u * R_UNIT, SB + P_A + oa + u * (NCP * KS * 4), 8 * KS * 4);
                    bulk_store(da + u * R_UNIT + 0x40000, SB + P_A + oa + (u * NCP + 8) * (KS * 4), (NCP - 8) * KS * 4);
                }
#pragma unroll
                for (int u = 0; u < UN; u++) bulk_store(db + u * R_UNIT, SB + P_B + ob + u * (NCP * KS * 2), NCP * KS * 2);
            }
            __syncwarp();
        }
        uint32_t wm = (lap + 1) << 21;
        if (lane < NCP) {
#pragma unroll
            for (int u = 0; u < 3; u++) wm |= min(cnt[pfc + 2 * u] >> 1, (uint32_t)KS) << (7 * u);
        }
        __syncwarp();
        const uint32_t c0 = n + NBUF < NT ? 0 : KS * 2;
        if (lane < NB / 2) ((uint2*)cnt)[lane] = make_uint2(c0, c0);
        PROF(3);
        asm volatile("cp.async.bulk.commit_group;" ::: "memory");
        asm volatile("cp.async.bulk.wait_group 0;" ::: "memory");
        __syncwarp();
        PROF(2);
        const bool safe = h < RB;
        if (!safe && lane < NCP) st_relaxed(ring + (bb ^ pfo), wm);
        if (n > 0) mbar_wait(bar_free(n - 1 + s0), ((n - 1 + s0) / NBUF) & 1);
        if (lane == 0) mbar_arrive(bar_free(buf));
        if (safe) {
            fence_release();
            if (lane < NCP) st_relaxed(ring + (bb ^ pfo), wm);
        }
        PROF(4);
    }
    PROF_END;
}
__device__ __forceinline__ void p_cleanup(unsigned char* ring, int q) {
    const int k = threadIdx.x / 24;
    if (k < 2 * RB) *(uint4*)(ring + ((q << 20) ^ ((k & 1) << 12) ^ slot_off(k >> 1) ^ OFF_PF) + (threadIdx.x % 24) * 16) = make_uint4(0, 0, 0, 0);
}

__device__ __forceinline__ void m_role(const Prm& p, unsigned char* ring, int X, int id) {
    const int tid = threadIdx.x, lane = tid & 31, w = __shfl_sync(0xffffffffu, tid >> 5, 0);
    const int ib = id >> 1, ty = id & 1;
    float* scs = (float*)(smem + S_MISC);
    if (w == 0) {
        const uint32_t bar = SB + S_AUX;
        if (lane == 0) mbar_init(bar, 1);
        wait_ge(&g_ctl.pieces_done, NPC);
        fence_acquire();
        if (lane == 0) {
            asm volatile("fence.proxy.async.global;" ::: "memory");
            asm volatile("fence.proxy.async.shared::cta;" ::: "memory");
            asm volatile("mbarrier.arrive.expect_tx.shared.b64 _, [%0], %1;" ::"r"(bar), "r"(ROWS_I * 4) : "memory");
            constexpr uint32_t PART = (ROWS_I * 4 / 8 + 127) / 128 * 128;
            for (uint32_t o = 0; o < ROWS_I * 4; o += PART)
                asm volatile("cp.async.bulk.shared::cluster.global.mbarrier::complete_tx::bytes [%0], [%1], %2, [%3];"
                             ::"r"(SB + o), "l"((const char*)(g_md[ty] + ib * ROWS_I) + o), "r"(min(PART, ROWS_I * 4 - o)), "r"(bar) : "memory");
        }
        __syncwarp();
            float sc[4]; bool bad;
        get_scales(p, sc, bad);
            if (bad) st_relaxed(&g_ctl.bad, 1);
        int it = 0; uint32_t pb;
        while (!((pb = ld_relaxed(&g_ctl.pagebits)) >> 31)) backoff(it);
        if (lane == 0) { scs[0] = sc[0]; scs[1] = sc[1]; scs[2] = sc[2]; scs[3] = sc[3]; ((uint32_t*)scs)[4] = X ? ~pb : pb; ((uint32_t*)scs)[5] = bad; }
        mbar_wait(bar, 0);
    }
    __syncthreads();
    if (((uint32_t*)scs)[5]) {
        for (int k = tid; k < (int)ROWS_I; k += THREADS) ((uint32_t*)smem)[k] = 0;
        __syncthreads();
    }
    const uint32_t NT = p.NT;
    if (w >= MW) return;
    const uint32_t pagebits = ((uint32_t*)scs)[4];
    const int half = lane >> 4, k4 = (lane & 15) * 4;
    const float mag_lo = magic_lo(scs[2 * ty]), mag_hi = magic_hi(scs[2 * ty], scs[2 * ty + 1]), bias = 16384.f * scs[2 * ty + 1];
    const int il = ib / NG, gi = (ib % NG) * 2 + X;
    const uint32_t a_off = R_A + il * R_UNIT + lane * 16, v_off = ty * R_V1 + il * R_UNIT + lane * 16;
    const uint32_t f_off = OFF_PF + il * 32 + half * 16, r_off = OFF_REL + (lane % NCP) * 4;
    const uint32_t j = w % (NP / GR);
    PROF_DECL
#pragma unroll 1
    for (uint32_t n = w / (NP / GR); n < NT; n += MW / (NP / GR)) {
        const uint32_t q = ((gi - n) & (GR - 1)) + GR * j, h = n >> 1;
        const uint32_t qb = q_base(q, pagebits), bb = qb ^ slot_off(h % RB);
        const uint32_t tag = (h / RB + 1) << 21;
        uint4 cw; int it = 0;
        while (true) {
            cw = ld_relaxed4(ring + (bb ^ f_off));
            if (__all_sync(0xffffffffu, min(min(cw.x, cw.y), cw.z) >= tag)) break;
            if (DEV_FREE) { cw.x = (cw.x & 1) + (63 | 57 << 7 | 50 << 14); cw.y = (cw.y & 1) + (53 | 61 << 7 | 57 << 14); cw.z = (cw.z & 1) + (59 | 52 << 7 | 57 << 14); break; }
            backoff(it);
        }
        PROF(0);
        {
            const unsigned char* pa = ring + (qb ^ slot_off(h % RA) ^ a_off);
            unsigned char* pv = ring + (qb ^ slot_off(h % RV) ^ v_off);
            const uint32_t hv = h + RB - RV;
            const unsigned char* prel = ring + (qb ^ slot_off(hv % RB) ^ r_off);
            const uint32_t rel = ld_relaxed(prel);
            const uint32_t vlap = h / RV;
            const float mag_hi0 = fmaf(bias, (vlap & 1) ? 3.f : 1.f, mag_hi);
            const uint32_t stamp = ((h / RA) & (0x40100401u >> lane) & 1) << 30;
            uint4 a[9];
#define M_LOAD(ps) a[ps] = ld_relaxed4(pa + (ps) * 512 + ((ps) < 4 ? 0 : R_HI))
#pragma unroll
            for (int ps = 0; ps < MPF; ps++) M_LOAD(ps);
            if (!__all_sync(0xffffffffu, rel >= hv / RB) && !DEV_FREE) wait_all_ge(prel, hv / RB);
            PROF(3);
#define M_STAMP(ps) (((ps) & 3) == 0 ? a[ps].x : ((ps) & 3) == 1 ? a[ps].y : ((ps) & 3) == 2 ? a[ps].z : a[ps].w)
#pragma unroll
            for (int g = 0; g < 9; g += 3) {
                while (true) {
                    M_STAMP(g) ^= stamp; M_STAMP(g + 1) ^= stamp; M_STAMP(g + 2) ^= stamp;
                    if (!__any_sync(0xffffffffu, ((M_STAMP(g) | M_STAMP(g + 1) | M_STAMP(g + 2)) & 0x40000000u) != 0)) break;
                    if (DEV_FREE) { M_STAMP(g) &= 0xbfffffffu; M_STAMP(g + 1) &= 0xbfffffffu; M_STAMP(g + 2) &= 0xbfffffffu; break; }
                    if (++it > SPIN_MAX) __trap();
                    M_LOAD(g); M_LOAD(g + 1); M_LOAD(g + 2);
                }
                uint32_t mv[3][4];
#pragma unroll
                for (int u = 0; u < 3; u++) gather4(mv[u], a[g + u], (int)(((g == 0 ? cw.x : g == 3 ? cw.y : cw.z) >> (7 * u)) & 0x7f) - k4);
#pragma unroll
                for (int u = 0; u < 3; u++) {
                    const int ps = g + u;
                    asm volatile("st.global.v4.u32 [%0], {%1,%2,%3,%4};" ::"l"(pv + ps * 512 + (ps < 4 ? 0 : R_HI)),
                                 "r"(term(mv[u][0], bf_hi(a[ps].x), mag_lo, mag_hi0)), "r"(term(mv[u][1], bf_hi(a[ps].y), mag_lo, mag_hi)),
                                 "r"(term(mv[u][2], bf_hi(a[ps].z), mag_lo, mag_hi)), "r"(term(mv[u][3], bf_hi(a[ps].w), mag_lo, mag_hi)) : "memory");
                    if (ps + MPF < 9) M_LOAD(ps + MPF);
                }
            }
            if (vlap == 0) fence_release();
        }
        st_lane0(ring + (bb ^ (OFF_RDY + (2 * il + ty) * 4)), cw.x >> 21, lane);
        PROF(1);
    }
    PROF_END;
}

__device__ __noinline__ void c_wrap(uint32_t row, int par, uint32_t old, uint32_t w) {
    const uint32_t nw = old + w, ov = ~(old ^ w) & (old ^ nw);
    int d = 0;
    if (ov & 0x8000u) d += (w & 0x8000u) ? -1 : 1;
    if (ov & 0x80000000u) d += (w & 0x80000000u) ? -16 : 16;
    if (d != 0) {
        uint32_t c;
        asm volatile("atom.shared.add.u32 %0, [%1], %2;" : "=r"(c) : "r"(SB + C_WRAP + row * 4), "r"(d << (8 * par)) : "memory");
        c = (c >> (8 * par)) + d;
        if (((c + 1) & 0xe) == 0 || ((c + 16) & 0xe0) == 0) st_relaxed(&g_ctl.bad, 1);
    }
}

#define CGRP 4
struct CTask { uint4 v[3]; uint2 b[3]; };
struct CWork {
    unsigned char* ring;
    uint32_t v_off, b_off, f_off, r_off, acc;
    uint32_t lap1, sv, sb, vtag, fw, stamp;
    int lane, dev_free;
    template <int ODD> __device__ __forceinline__ void issue(CTask& t) {
        if (!__all_sync(0xffffffffu, fw >= lap1)) {
            int it = 0;
            do {
                if (dev_free) break;
                backoff(it);
                fw = ld_relaxed(ring + (f_off ^ slot_off(sb) ^ (ODD << 20)));
            } while (!__all_sync(0xffffffffu, fw >= lap1));
        }
        {
            const unsigned char* pv = ring + (v_off ^ slot_off(sv) ^ (ODD << 20));
            const unsigned char* pb = ring + (b_off ^ slot_off(sb) ^ (ODD << 20));
#pragma unroll
            for (int ps = 0; ps < 3; ps++) {
                t.v[ps] = ld_relaxed4(pv + ps * R_UNIT);
                t.b[ps] = ld_relaxed2(pb + ps * R_UNIT);
            }
        }
        fw = ld_relaxed(ring + (f_off ^ slot_off(ODD ? (sb + 1 == RB ? 0 : sb + 1) : sb) ^ (!ODD << 20)));
    }
    template <int ODD> __device__ __forceinline__ void arrive(CTask& t) {
        {
            int it = 0;
            while (true) {
#pragma unroll
                for (int ps = 0; ps < 3; ps++) t.b[ps].x ^= stamp;
                if (!__any_sync(0xffffffffu, (((t.v[0].x ^ vtag) | (t.v[1].x ^ vtag) | (t.v[2].x ^ vtag)) & 0x80000000u) | ((t.b[0].x | t.b[1].x | t.b[2].x) & 0x8000u))) break;
                if (dev_free) { for (int ps = 0; ps < 3; ps++) { t.v[ps].x = (t.v[ps].x & 0x7fffffffu) | (vtag & 0x80000000u); t.b[ps].x &= 0xffff7fffu; } break; }
                if (++it > SPIN_MAX) __trap();
#pragma unroll
                for (int ps = 0; ps < 3; ps++) {
                    t.v[ps] = ld_relaxed4(ring + (v_off ^ slot_off(sv) ^ (ODD << 20)) + ps * R_UNIT);
                    t.b[ps] = ld_relaxed2(ring + (b_off ^ slot_off(sb) ^ (ODD << 20)) + ps * R_UNIT);
                }
            }
#pragma unroll
            for (int ps = 0; ps < 3; ps++) t.v[ps].x -= vtag;
        }
        st_lane0(ring + (r_off ^ slot_off(sb) ^ (ODD << 20)), lap1, lane);
        if (ODD) {
            if (++sv == RV) { sv = 0; vtag ^= 0x80000000u; }
            if (++sb == RB) { sb = 0; lap1++; stamp ^= (((b_off >> 3) ^ (b_off >> 7)) & 15) == 0 ? 0x8000u : 0u; }
        }
    }
    __device__ __forceinline__ void add(const CTask& t) {
        const uint32_t vw[12] = {t.v[0].x, t.v[0].y, t.v[0].z, t.v[0].w, t.v[1].x, t.v[1].y, t.v[1].z, t.v[1].w, t.v[2].x, t.v[2].y, t.v[2].z, t.v[2].w};
        const uint32_t bw[6] = {t.b[0].x, t.b[0].y, t.b[1].x, t.b[1].y, t.b[2].x, t.b[2].y};
#pragma unroll
        for (int g = 0; g < 12; g += CGRP) {
            uint32_t old[CGRP], ov = 0;
#pragma unroll
            for (int e = g; e < g + CGRP; e++)
                asm volatile("atom.shared.add.u32 %0, [%1], %2;" : "=r"(old[e - g]) : "r"((e & 1) ? __dp2a_hi(bw[e >> 1], 0x08000008u, acc) : __dp2a_lo(bw[e >> 1], 0x08000008u, acc)), "r"(vw[e]) : "memory");
#pragma unroll
            for (int e = g; e < g + CGRP; e++) ov |= ~(old[e - g] ^ vw[e]) & (old[e - g] ^ (old[e - g] + vw[e]));
            if (__any_sync(0xffffffffu, ov & 0x80008000u)) {
#pragma unroll
                for (int e = g; e < g + CGRP; e++) c_wrap((e & 1) ? bw[e >> 1] >> 16 : bw[e >> 1] & 0xffffu, lane >> 4, old[e - g], vw[e]);
            }
        }
    }
};

__device__ __forceinline__ void c_role(const Prm& p, unsigned char* ring, int X, int c) {
    const int tid = threadIdx.x, lane = tid & 31, w = __shfl_sync(0xffffffffu, tid >> 5, 0);
    uint32_t* misc = (uint32_t*)(smem + S_MISC);
    Wts* wt = (Wts*)(smem + S_AUX);
    load_wts(p, wt);
    if (tid == 0) misc[6] = TAB_N;
    __syncthreads();
    if (w == 0) {
        float sc[4]; bool bad;
        wait_ge(&g_ctl.pieces_done, NPC);
        fence_acquire();
        get_scales(p, sc, bad);
        const float s = (lane & 2) ? ((lane & 1) ? sc[3] : sc[2]) : ((lane & 1) ? sc[1] : sc[0]);
        wt->ws[lane] *= s;
        int it = 0; uint32_t pb;
        while (!((pb = ld_relaxed(&g_ctl.pagebits)) >> 31)) backoff(it);
        misc[4] = X ? ~pb : pb;
    } else {
        const int r0 = (X * NCP + c) * ROWS_O, nr = min((int)ROWS_O, p.E - r0);
#pragma unroll 4
        for (int r = tid - 32; r < (int)ROWS_O / 2; r += THREADS - 32) {
            const uint32_t d2 = 2 * r < nr ? __ldg((const uint32_t*)(p.dist + r0) + r) : TAB_LO * 0x10001u;
            uint32_t e[2] = {(d2 & 0xffff) - TAB_LO, (d2 >> 16) - TAB_LO};
#pragma unroll
            for (int k = 0; k < 2; k++)
                if (e[k] >= TAB_N) {
                    const uint32_t d = e[k] + TAB_LO;
                    if ((d & 0x7f80) == 0x7f80) st_relaxed(&g_ctl.bad, 1);
                    e[k] = min(atomicAdd(&misc[6], 1u), 0xffffu);
                    if (e[k] < TAB_N + TAB_X) ((uint32_t*)(smem + C_TAB))[e[k] * 4] = d;
                }
            ((uint2*)(smem + C_WRAP))[r] = make_uint2(e[0] << 16 | 0x8888u, e[1] << 16 | 0x8888u);
        }
    }
    __syncthreads();
    if (w >= NP / 2) {
        const int nt = min(misc[6], (uint32_t)(TAB_N + TAB_X));
        for (int k = tid - NP * 16; k < nt; k += THREADS - NP * 16)
            ((uint4*)(smem + C_TAB))[k] = radial_bf16(wt, k < TAB_N ? TAB_LO + k : ((uint32_t*)(smem + C_TAB))[k * 4]);
        if (DEV_FREE) return;
        for (int it = 0; ld_relaxed(&g_ctl.late_done) == 0; it++) { __nanosleep(1000); if (it > SPIN_MAX) __trap(); }
        const int ob = X * NCP + c, nr = min((int)ROWS_O, p.E - ob * (int)ROWS_O);
        if (tid == THREADS - 1 && nr > 0) asm volatile("cp.async.bulk.prefetch.L2.global [%0], %1;" ::"l"(p.m + ob * ROWS_O), "r"(nr * 8) : "memory");
        for (int it = 0; ld_relaxed(&g_ctl.late_done) < NP; it++) { __nanosleep(100); if (it > SPIN_MAX) __trap(); }
        TS(9);
        fence_acquire();
        constexpr int LQ = NP / (2 * (NW - NP / 2));
        const int q0 = (tid - NP * 16) >> 4;
        uint32_t n[LQ], nmax = 0;
#pragma unroll
        for (int j = 0; j < LQ; j++) n[j] = ld_relaxed((const uint32_t*)g_late_n[q0 * LQ + j] + ob);
#pragma unroll
        for (int j = 0; j < LQ; j++) { n[j] = min(n[j], (uint32_t)LATE_N); nmax = max(nmax, n[j]); }
        nmax = __reduce_max_sync(0xffffffffu, nmax);
        for (uint32_t k = lane & 15; k < ((nmax + 15) & ~15u); k += 16) {
            uint4 e[LQ];
            uint32_t o0[LQ], o1[LQ], ov = 0;
#pragma unroll
            for (int j = 0; j < LQ; j++) { e[j] = make_uint4(lane, 0, 0, 0); if (k < n[j]) e[j] = ld_relaxed4(g_late[ob][q0 * LQ + j][k]); }
#pragma unroll
            for (int j = 0; j < LQ; j++) { o0[j] = atomicAdd((uint32_t*)smem + 2 * e[j].x, e[j].y); o1[j] = atomicAdd((uint32_t*)smem + 2 * e[j].x + 1, e[j].z); }
#pragma unroll
            for (int j = 0; j < LQ; j++) ov |= (~(o0[j] ^ e[j].y) & (o0[j] ^ (o0[j] + e[j].y))) | (~(o1[j] ^ e[j].z) & (o1[j] ^ (o1[j] + e[j].z)));
            if (ov & 0x80008000u) {
#pragma unroll
                for (int j = 0; j < LQ; j++) { c_wrap(e[j].x, 0, o0[j], e[j].y); c_wrap(e[j].x, 1, o1[j], e[j].z); }
            }
        }
        __syncwarp();
        TS(10);
    }
    const uint32_t pagebits = misc[4];
    if (w >= NP / 2) return;
    CWork W;
    const int par = lane >> 4;
    W.ring = ring; W.lane = __shfl_sync(0xffffffffu, lane, lane); W.dev_free = DEV_FREE;
    const uint32_t qb = q_base(2 * w + X, pagebits), k = lane & 15;
    W.acc = __shfl_sync(0xffffffffu, SB + par * 4, lane);
    W.v_off = __shfl_sync(0xffffffffu, qb ^ (par * R_V1 + (c < 8 ? 0 : R_HI) + c * 256 + k * 16), lane);
    W.b_off = __shfl_sync(0xffffffffu, qb ^ (R_B + c * 128 + k * 8), lane);
    W.f_off = __shfl_sync(0xffffffffu, qb ^ (OFF_RDY + (lane % 6) * 4), lane);
    W.r_off = qb ^ (OFF_REL + c * 4);
    W.lap1 = 1; W.sv = W.sb = W.fw = W.stamp = 0; W.vtag = 0x40000000u;
    const uint32_t NT = p.NT;
    CTask A, B;
    PROF_DECL
    W.issue<0>(A);
#pragma unroll 1
    for (uint32_t n = 2;; n += 2) {
        W.arrive<0>(A); PROF(1); W.issue<1>(B); PROF(0); W.add(A);
        W.arrive<1>(B);
        if (n >= NT) break;
        PROF(1); W.issue<0>(A); PROF(0); W.add(B);
    }
    W.add(B);
    TS(8);
    PROF_END;
}

__device__ __forceinline__ uint32_t bf2_mul(uint32_t a, uint32_t b) { uint32_t r; asm("mul.rn.bf16x2 %0, %1, %2;" : "=r"(r) : "r"(a), "r"(b)); return r; }
__device__ __forceinline__ uint32_t bf2_fma(uint32_t a, uint32_t b, uint32_t c) { uint32_t r; asm("fma.rn.bf16x2 %0, %1, %2, %3;" : "=r"(r) : "r"(a), "r"(b), "r"(c)); return r; }
__device__ __forceinline__ uint32_t c_agg(uint32_t a, uint32_t s, uint32_t wr, bool wrapped) {
    int x0 = (short)a, x1 = ((int)a >> 16) + ((a >> 15) & 1);
    if (wrapped) { const int w0 = (int)(wr & 15) - 8, w1 = (int)((wr >> 4) & 15) - 8; x0 += 65536 * w0; x1 += 65536 * w1 - w0; }
    return pack_bf16((float)x1 * bf_hi(s), (float)x0 * bf_lo(s));
}
__device__ __forceinline__ void c_epilogue(const Prm& p, int X, int c) {
    const int tid = threadIdx.x, lane = tid & 31;
    const Wts* wt = (const Wts*)(smem + S_AUX);
    uint32_t bw[4];
#pragma unroll
    for (int k = 0; k < 4; k++) {
        const int col = (k >> 1) * 2 + ((lane >> 2) & 1), row = (k & 1) * 2;
        bw[k] = (lane >> 3) == (lane & 3) ? pack_bf16(wt->wu[(row + 1) * 4 + col], wt->wu[row * 4 + col]) : 0u;
    }
    const int r0 = (X * NCP + c) * ROWS_O, np = max(min((int)ROWS_O, p.E - r0), 0) / 2;
    const uint4* mp = (const uint4*)(p.m + r0);
    uint4* op = (uint4*)(p.out + r0);
    constexpr int EB = 5;
#pragma unroll 1
    for (int rb = tid; rb - lane < np; rb += EB * THREADS) {
        uint4 mr[EB];
#pragma unroll
        for (int k = 0; k < EB; k++) mr[k] = __ldg(mp + min(rb + k * THREADS, np - 1));
#pragma unroll
        for (int k = 0; k < EB; k++) {
            const int r = min(rb + k * THREADS, np - 1);
            const uint4 a = ((const uint4*)smem)[r];
            const uint2 wr = ((const uint2*)(smem + C_WRAP))[r];
            const uint4 t0 = ((const uint4*)(smem + C_TAB))[min(wr.x >> 16, (uint32_t)(TAB_N + TAB_X - 1))];
            const uint4 t1 = ((const uint4*)(smem + C_TAB))[min(wr.y >> 16, (uint32_t)(TAB_N + TAB_X - 1))];
            const bool wrapped = __any_sync(0xffffffffu, prmt(wr.x, wr.y, 0x5410) != 0x88888888u);
            uint32_t a0, a1, a2, a3;
            if (wrapped) { a0 = c_agg(a.x, t0.x, wr.x, true); a2 = c_agg(a.y, t0.y, wr.x >> 8, true); a1 = c_agg(a.z, t1.x, wr.y, true); a3 = c_agg(a.w, t1.y, wr.y >> 8, true); }
            else { a0 = c_agg(a.x, t0.x, 0, false); a2 = c_agg(a.y, t0.y, 0, false); a1 = c_agg(a.z, t1.x, 0, false); a3 = c_agg(a.w, t1.y, 0, false); }
            float u[8];
#pragma unroll
            for (int h = 0; h < 2; h++)
                asm("mma.sync.aligned.m16n8k16.row.col.f32.bf16.bf16.f32 {%0,%1,%2,%3}, {%4,%5,%6,%7}, {%8,%9}, {%10,%10,%10,%10};"
                    : "=f"(u[4 * h]), "=f"(u[4 * h + 1]), "=f"(u[4 * h + 2]), "=f"(u[4 * h + 3])
                    : "r"(a0), "r"(a1), "r"(a2), "r"(a3), "r"(bw[2 * h]), "r"(bw[2 * h + 1]), "f"(0.f));
            const uint4 o = make_uint4(bf2_fma(pack_bf16(u[1], u[0]), t0.z, mr[k].x), bf2_fma(pack_bf16(u[5], u[4]), t0.w, mr[k].y),
                                       bf2_fma(pack_bf16(u[3], u[2]), t1.z, mr[k].z), bf2_fma(pack_bf16(u[7], u[6]), t1.w, mr[k].w));
            if (rb + k * THREADS < np) op[r] = o;
        }
    }
    if (((const uint32_t*)(smem + S_MISC))[6] > TAB_N + TAB_X) {
        for (int r = 2 * tid; r < 2 * np; r += (r & 1) ? 2 * THREADS - 1 : 1) {
            const uint32_t wr = ((const uint32_t*)(smem + C_WRAP))[r];
            if ((wr >> 16) < TAB_N + TAB_X) continue;
            const uint4 t = radial_bf16(wt, __bfloat16_as_ushort(p.dist[r0 + r]));
            const uint2 a = ((const uint2*)smem)[r];
            const uint32_t a0 = c_agg(a.x, t.x, wr, true), a1 = c_agg(a.y, t.y, wr >> 8, true);
            const float agg[4] = {bf_lo(a0), bf_hi(a0), bf_lo(a1), bf_hi(a1)}, g[4] = {bf_lo(t.z), bf_hi(t.z), bf_lo(t.w), bf_hi(t.w)};
            p.out[r0 + r] = finish_row(wt->wu, agg, g, p.m[r0 + r]);
        }
    }
}

__device__ __forceinline__ void grid_bar(unsigned* ctr) {
    __syncthreads();
    if (threadIdx.x == 0) { fence_gpu(); red_add(ctr, 1); wait_ge(ctr, gridDim.x); fence_gpu(); }
    __syncthreads();
}
__device__ __noinline__ void fallback(const Prm& p) {
    const int gt = blockIdx.x * THREADS + threadIdx.x, gs = gridDim.x * THREADS;
    Wts* wt = (Wts*)smem;
    __syncthreads();
    load_wts(p, wt);
    for (int e = gt; e < p.E; e += gs) g_acc[e] = make_float4(0.f, 0.f, 0.f, 0.f);
    grid_bar(&g_ctl.bar[0]);
    const float f = __bfloat162float(p.freq[0]);
    for (int t = gt; t < p.T; t += gs) {
        uint2 r = __ldg(p.m + p.idx_in[t]);
        float c = rbf16(cosf(rbf16(f * __bfloat162float(p.angle[t]))));
        asm volatile("red.global.add.v4.f32 [%0], {%1,%2,%3,%4};" ::"l"(g_acc + p.idx_out[t]), "f"(bf_lo(r.x) * c),
                     "f"(bf_hi(r.x) * c), "f"(bf_lo(r.y) * c), "f"(bf_hi(r.y) * c) : "memory");
    }
    grid_bar(&g_ctl.bar[1]);
    for (int e = gt; e < p.E; e += gs) {
        float4 a4 = __ldcg(g_acc + e);
        float a[4] = {a4.x, a4.y, a4.z, a4.w}, s[4], g[4];
        radial(wt, __bfloat162float(p.dist[e]), s, g);
        float agg[4];
#pragma unroll
        for (int j = 0; j < 4; j++) agg[j] = s[j] * (a[0] * wt->wd[j] + a[1] * wt->wd[4 + j] + a[2] * wt->wd[8 + j] + a[3] * wt->wd[12 + j]);
        p.out[e] = finish_row(wt->wu, agg, g, p.m[e]);
    }
}

__device__ __forceinline__ void smem_init(bool isp, int from, int to) {
    for (int k = from / 16 + threadIdx.x; k < to / 16; k += THREADS) {
        const bool b = isp && k >= P_B / 16 && k < P_Q / 16;
        const uint32_t z = b ? (k & 7) * 0x20002u : 0u, y = b ? z + 0x10001u : 0u;
        ((uint4*)smem)[k] = make_uint4(z, z, y, y);
    }
}

__global__ void __launch_bounds__(THREADS, 1) gemnet_kernel(const __grid_constant__ Prm p) {
    const int tid = threadIdx.x, lane = tid & 31, w = __shfl_sync(0xffffffffu, tid >> 5, 0);
    uint32_t* misc = (uint32_t*)(smem + S_MISC);
    bool run_fallback = true;
    if (!p.force_bad && __cvta_generic_to_shared(smem) == SB) {
        unsigned char* const ring = p.ring;
        uint32_t smid; asm("mov.u32 %0, %%smid;" : "=r"(smid));
        const int cls = smid < NM ? 0 : (smid < NM + NP - 4 || (smid >= 124 && smid < 128)) ? 2 : 1;
        if (lane == 0) {
            if (w < 2 && (cls != 2 || blockIdx.x == 0)) misc[16 + w] = probe(ring + OFF_PROBE + w * 4096 + ((blockIdx.x >> 7) << 20) + (blockIdx.x & 127) * 32);
            else if (blockIdx.x == 0 && w <= NPAGES) misc[16 + w] = probe(ring + ((size_t)(w - 1) << 21) + OFF_PROBE);
        }
        float wd[16];
        if (cls != 2 || blockIdx.x == 0) __syncthreads();
        if (tid == 0) {
            int pool = cls == 2 ? 4 : cls * 2 + (misc[16] > misc[17]), id = 0;
            for (int k = 0; k < 7; k++) {
                int cap = pool < 2 ? NMP : pool < 4 ? NCP : NP;
                id = atomicAdd(&g_ctl.ticket[pool], 1);
                if (id < cap) break;
                pool = k == 0 ? (pool == 4 ? 0 : pool ^ 1) : k - 1;
            }
            misc[8] = pool; misc[9] = id;
            if (pool != 4) down_load(p, pool < 2 ? pool * NMP + id : NM + (pool - 2) * NCP + id);
        }
        if (blockIdx.x == 0 && tid == 32) {
            uint32_t pb = 0x80000000u;
            for (int k = 1; k < NPAGES; k++) pb |= (uint32_t)((2 * misc[17 + k] > misc[16] + misc[17]) != (misc[16] > misc[17])) << k;
            st_relaxed(&g_ctl.pagebits, pb);
        }
#pragma unroll
        for (int k = 0; k < 16; k++) wd[k] = __bfloat162float(p.w_down[k]);
        if (cls == 2) smem_init(true, 0, S_PC);
        __syncthreads();
        const int pool = misc[8], id = misc[9];
        if (pool >= 2 && (pool < 4 || cls != 2)) smem_init(pool == 4, 0, S_PC);
        if (pool != 4) down_piece(p, pool < 2 ? pool * NMP + id : NM + (pool - 2) * NCP + id, wd);
        if (DEV_FREE && !(DEV_FREE & (pool == 4 ? 1 : pool < 2 ? 2 : 4))) {
        } else if (pool == 4) {
            smem_init(true, S_PC, S_MISC);
            __syncthreads();
            if (tid < 2 * NBUF) {
                const uint32_t a = tid < NBUF ? bar_done(tid) : bar_free(tid), cnt = tid < NBUF ? CPS : 1;
                mbar_init(a, cnt);
                if (tid % NBUF < id % GR) asm volatile("mbarrier.arrive.shared.b64 _, [%0], %1;" ::"r"(a), "r"(cnt) : "memory");
            }
            if (tid == 32) mbar_init(SB + S_MISC + 248, 1);
            __syncthreads();
            if (w < FW) p_filler(p, id, w);
            else if (w < FW + NF) {
                int it = 0; uint32_t pb;
                while (!((pb = ld_relaxed(&g_ctl.pagebits)) >> 31)) backoff(it);
                p_flusher(p, ring, __shfl_sync(0xffffffffu, pb, 0), id, w - FW);
            }
        } else if (pool < 2) {
            m_role(p, ring, pool, id);
        } else {
            c_role(p, ring, pool - 2, id);
        }
        __syncthreads();
        if (tid == 0) { fence_gpu(); red_add(&g_ctl.fin, 1); }
        if ((pool == 2 || pool == 3) && !DEV_FREE) c_epilogue(p, pool - 2, id);
        if (tid == 0) { wait_ge(&g_ctl.fin, NCTA); fence_gpu(); misc[10] = ld_relaxed(&g_ctl.bad); }
        __syncthreads();
        if (pool == 4) p_cleanup(ring, id);
        run_fallback = misc[10] && !DEV_FREE;
    }
    if (run_fallback) fallback(p);
    if (tid == 0) {
        fence_gpu();
        if (atomicAdd(&g_ctl.exited, 1) == gridDim.x - 1) {
            uint32_t* c = (uint32_t*)&g_ctl;
            for (int k = 0; k < 32; k++) c[k] = 0;
        }
    }
}

cudaTextureObject_t make_tex(const void* ptr, size_t bytes, int words) {
    cudaResourceDesc rd = {};
    rd.resType = cudaResourceTypeLinear;
    rd.res.linear.devPtr = (void*)ptr;
    rd.res.linear.desc = words == 4 ? cudaCreateChannelDesc<uint4>() : cudaCreateChannelDesc<uint2>();
    rd.res.linear.sizeInBytes = bytes;
    cudaTextureDesc td = {};
    td.readMode = cudaReadModeElementType;
    cudaTextureObject_t t = 0;
    if (cudaCreateTextureObject(&t, &rd, &td, nullptr) != cudaSuccess) { cudaGetLastError(); return 0; }
    return t;
}

}

extern "C" void kernel_launch(void* const* d_in, const int* in_sizes, int n_in, void* d_out, int out_size) {
    static Prm p = {};
    static int grid = 0;
    const int E = in_sizes[3], T = in_sizes[1];
    if (grid == 0 || p.idx_in != d_in[1] || p.idx_out != d_in[2] || p.angle != d_in[4] || p.E != E || p.T != T) {
        int dev = 0, sms = 0;
        cudaGetDevice(&dev);
        cudaDeviceGetAttribute(&sms, cudaDevAttrMultiProcessorCount, dev);
        cudaFuncSetAttribute(gemnet_kernel, cudaFuncAttributeMaxDynamicSharedMemorySize, SMEM_BYTES);
        p.E = E; p.T = T;
        p.NS = (((T / 128 + NP * CB - 1) / (NP * CB)) * CB + CPS - 1) / CPS;
        if (p.NS < 3) p.NS = 3;
        p.NT = (p.NS + GR) & ~1;
        void* rp = nullptr;
        cudaGetSymbolAddress(&rp, g_ring);
        p.ring = (unsigned char*)(((uintptr_t)rp + ((2u << 20) - 1)) & ~(uintptr_t)((2u << 20) - 1));
        bool fast = sms >= NCTA && E <= (int)FAST_E && (E & 1) == 0 && T >= 128 && T <= (1 << 29);
        if (fast) {
            p.t_in = make_tex(d_in[1], (size_t)(T / 128) * 512, 4);
            p.t_out = make_tex(d_in[2], (size_t)(T / 128) * 512, 4);
            p.t_ang = make_tex(d_in[4], (size_t)(T / 128) * 256, 2);
            fast = p.t_in && p.t_out && p.t_ang;
        }
        p.force_bad = !fast;
        grid = fast ? NCTA : sms;
    }
    p.m = (const uint2*)d_in[0];
    p.idx_in = (const int*)d_in[1];
    p.idx_out = (const int*)d_in[2];
    p.dist = (const __nv_bfloat16*)d_in[3];
    p.angle = (const __nv_bfloat16*)d_in[4];
    p.centers = (const __nv_bfloat16*)d_in[5];
    p.freq = (const __nv_bfloat16*)d_in[6];
    p.w_rbf = (const __nv_bfloat16*)d_in[7];
    p.w_sbf = (const __nv_bfloat16*)d_in[8];
    p.w_down = (const __nv_bfloat16*)d_in[9];
    p.w_up = (const __nv_bfloat16*)d_in[10];
    p.out = (uint2*)d_out;
    gemnet_kernel<<<grid, THREADS, SMEM_BYTES>>>(p);
}
```

```cpp
#include <cuda_runtime.h>
#include <cuda_bf16.h>
#include <stdint.h>

namespace {

constexpr int NI = 12;
constexpr int UN = 3;
constexpr int NG = NI / UN;
constexpr int GR = 2 * NG;
constexpr int NCP = 18;
constexpr int NO = 2 * NCP;
constexpr int KS = 64;
constexpr int NB = UN * NCP;
constexpr int NBUF = 10;
constexpr int NMP = 2 * NI;
constexpr int NP = 48, NM = 2 * NMP, NC = NO, NCTA = NP + NM + NC;
#define CPS_ 25
constexpr int CPS = CPS_;
#define FW_ 24
constexpr int FW = FW_;
constexpr int NF = 4;
#define RA_ 3
#define RV_ 3
#define RB_ 4
constexpr int RA = RA_, RV = RV_, RB = RB_;
#define QN_ 96
#define QTRIG_ 48
constexpr int QN = QN_, QTRIG = QTRIG_;
#define MW_ 18
constexpr int MW = MW_;
#define MPF_ 6
constexpr int MPF = MPF_;
constexpr int THREADS = 896, NW = THREADS / 32;
#define DEV_FREE 0
#define SLEEP_ 50

constexpr int RING_BYTES = NP << 20;
constexpr int NPAGES = RING_BYTES >> 21;
constexpr int MAX_E = 1 << 20;
constexpr int SMEM_BYTES = 232448;

constexpr int SB = 1024;

constexpr int P_CNT = 0;
constexpr int P_BAR = P_CNT + NBUF * NB * 4;
constexpr int P_TKT = P_BAR + 2 * NBUF * 8;
constexpr int P_LATE = P_TKT + 128;
constexpr int P_B = (P_LATE + 256 + 127) / 128 * 128;
constexpr int P_Q = P_B + NBUF * NB * KS * 2;
constexpr int P_A = SMEM_BYTES - 256 - NBUF * NB * KS * 4;
static_assert(P_Q + FW * QN * 8 + 512 <= P_A && P_A % 128 == 0, "P smem");
constexpr int S_MISC = SMEM_BYTES - 256;
constexpr int S_AUX = S_MISC - 512;

constexpr unsigned FAST_E = 640000;
constexpr unsigned magic_of(unsigned long long d) { return (unsigned)(((1ull << 32) + d - 1) / d); }
constexpr bool magic_ok(unsigned long long d) { return (magic_of(d) * d - (1ull << 32)) * FAST_E < (1ull << 32); }
constexpr unsigned pick_rows(unsigned lo, unsigned al) {
    unsigned d = (lo + al - 1) / al * al;
    while (!magic_ok(d)) d += al;
    return d;
}
constexpr unsigned ROWS_I = pick_rows((FAST_E + NI - 1) / NI, 32), ROWS_O = pick_rows((FAST_E + NO - 1) / NO, 16);
constexpr unsigned MAG_I = magic_of(ROWS_I), MAG_O = magic_of(ROWS_O), HALF_O = ROWS_O * NCP;
constexpr int C_WRAP = ROWS_O * 8, C_TAB = ROWS_O * 12, TAB_N = 1025, TAB_LO = 0x3f80 - 1024, TAB_X = (S_AUX - C_TAB) / 16 - TAB_N;
static_assert(ROWS_I * 4 <= S_AUX && TAB_X >= 100 && ROWS_I <= 65536 && ROWS_O <= 32768, "tables");

constexpr int NPC = NM + NC;
constexpr int PC_ROWS = ((FAST_E + NPC - 1) / NPC + 31) & ~31;
constexpr int S_PC = C_WRAP + 128 - C_WRAP % 128;
static_assert(S_PC + PC_ROWS * 8 + 1024 <= S_AUX, "pre-pass");
struct Ctl {
    __align__(128) unsigned long long sides[2];
    __align__(128) unsigned pagebits;
    __align__(128) unsigned pieces_done;
    __align__(128) unsigned late_done;
    __align__(128) unsigned fin;
    unsigned bad;
    __align__(128) unsigned bar[2];
    unsigned exited;
    __align__(128) float stat[NPC][8];
};

struct Prm {
    const uint2* m; const int* idx_in; const int* idx_out; const __nv_bfloat16* dist; const __nv_bfloat16* angle;
    const __nv_bfloat16* centers; const __nv_bfloat16* freq; const __nv_bfloat16* w_rbf; const __nv_bfloat16* w_sbf;
    const __nv_bfloat16* w_down; const __nv_bfloat16* w_up; uint2* out;
    cudaTextureObject_t t_in, t_out, t_ang;
    int E, T;
    unsigned char* ring;
    int NS, NT;
    int force_bad;
};

__device__ __align__(128) unsigned char g_ring[RING_BYTES + (2 << 20)];
__device__ Ctl g_ctl;
constexpr int LATE_N = 64;
__device__ uint4 g_late_n[NP][16];
__device__ uint4 g_late[NO][NP][LATE_N][2];
__device__ float4 g_acc[MAX_E];
__device__ __align__(128) uint32_t g_md[2][NI * ROWS_I];
#define TS(k)
#define PROF_DECL
#define PROF(k)
#define PROF_END

extern __shared__ __align__(128) unsigned char smem[];

__device__ __forceinline__ float bf_lo(uint32_t w) { return __uint_as_float(w << 16); }
__device__ __forceinline__ float bf_hi(uint32_t w) { return __uint_as_float(w & 0xffff0000u); }
__device__ __forceinline__ float rbf16(float x) { return __bfloat162float(__float2bfloat16_rn(x)); }
__device__ __forceinline__ uint32_t pack_bf16(float hi, float lo) {
    uint32_t r; asm("cvt.rn.bf16x2.f32 %0, %1, %2;" : "=r"(r) : "f"(hi), "f"(lo)); return r;
}
__device__ __forceinline__ uint32_t prmt(uint32_t a, uint32_t b, uint32_t c) {
    uint32_t r; asm("prmt.b32 %0, %1, %2, %3;" : "=r"(r) : "r"(a), "r"(b), "r"(c)); return r;
}
__device__ __forceinline__ uint32_t ld_relaxed(const void* p) {
    uint32_t v; asm volatile("ld.relaxed.gpu.global.u32 %0, [%1];" : "=r"(v) : "l"(p) : "memory"); return v;
}
__device__ __forceinline__ uint2 ld_relaxed2(const void* p) {
    uint2 v; asm volatile("ld.relaxed.gpu.global.v2.u32 {%0,%1}, [%2];" : "=r"(v.x), "=r"(v.y) : "l"(p) : "memory"); return v;
}
__device__ __forceinline__ uint4 ld_relaxed4(const void* p) {
    uint4 v; asm volatile("ld.relaxed.gpu.global.v4.u32 {%0,%1,%2,%3}, [%4];" : "=r"(v.x), "=r"(v.y), "=r"(v.z), "=r"(v.w) : "l"(p) : "memory"); return v;
}
__device__ __forceinline__ void st_relaxed(void* p, uint32_t v) { asm volatile("st.relaxed.gpu.global.u32 [%0], %1;" ::"l"(p), "r"(v) : "memory"); }
__device__ __forceinline__ void st_relaxed16(void* p, uint32_t v) { asm volatile("st.relaxed.gpu.global.u16 [%0], %1;" ::"l"(p), "h"((uint16_t)v) : "memory"); }
__device__ __forceinline__ void red_add(void* p, uint32_t v) { asm volatile("red.relaxed.gpu.global.add.u32 [%0], %1;" ::"l"(p), "r"(v) : "memory"); }
__device__ __forceinline__ void fence_gpu() { asm volatile("fence.acq_rel.gpu;" ::: "memory"); }
__device__ __forceinline__ void fence_acquire() { asm volatile("fence.acquire.gpu;" ::: "memory"); }
__device__ __forceinline__ void fence_release() { asm volatile("fence.release.gpu;" ::: "memory"); }
__device__ __forceinline__ void mbar_init(uint32_t a, uint32_t n) { asm volatile("mbarrier.init.shared.b64 [%0], %1;" ::"r"(a), "r"(n) : "memory"); }
__device__ __forceinline__ void mbar_arrive(uint32_t a) { asm volatile("mbarrier.arrive.shared.b64 _, [%0];" ::"r"(a) : "memory"); }
__device__ __forceinline__ bool mbar_try(uint32_t a, uint32_t ph) {
    uint32_t ok;
    asm volatile("{.reg .pred p; mbarrier.try_wait.parity.shared.b64 p, [%1], %2, %3; selp.u32 %0, 1, 0, p;}" : "=r"(ok) : "r"(a), "r"(ph), "r"(2000) : "memory");
    return ok;
}
__device__ __forceinline__ bool mbar_test(uint32_t a, uint32_t ph) {
    uint32_t ok;
    asm volatile("{.reg .pred p; mbarrier.test_wait.parity.shared.b64 p, [%1], %2; selp.u32 %0, 1, 0, p;}" : "=r"(ok) : "r"(a), "r"(ph) : "memory");
    return ok;
}
constexpr int SPIN_MAX = 1 << 22;
__device__ __forceinline__ void mbar_wait(uint32_t a, uint32_t ph) {
    int it = 0;
    while (!mbar_try(a, ph)) { if (++it > SPIN_MAX) __trap(); }
}
__device__ __forceinline__ void backoff(int& it) { __nanosleep(SLEEP_); if (++it > SPIN_MAX) __trap(); }
__device__ __forceinline__ void wait_ge(const void* p, uint32_t v) {
    int it = 0;
    while (ld_relaxed(p) < v) backoff(it);
}

__device__ __forceinline__ bool elect_one() {
    uint32_t r; asm volatile("{.reg .pred p; elect.sync _|p, 0xffffffff; selp.u32 %0, 1, 0, p;}" : "=r"(r)); return r;
}
__device__ __forceinline__ void st_lane0(void* p, uint32_t v, int lane) {
    asm volatile("{.reg .pred p; setp.eq.s32 p, %2, 0; @p st.relaxed.gpu.global.u32 [%0], %1;}" ::"l"(p), "r"(v), "r"(lane) : "memory");
}
__device__ __forceinline__ void wait_all_ge(const void* p, uint32_t v) {
    int it = 0;
    while (!__all_sync(0xffffffffu, ld_relaxed(p) >= v)) backoff(it);
}
__device__ __forceinline__ void gather4(uint32_t (&v)[4], const uint4& a, int n) {
    asm volatile("{.reg .pred p0, p1, p2, p3;\n"
                 "setp.gt.s32 p0, %8, 0; setp.gt.s32 p1, %8, 1; setp.gt.s32 p2, %8, 2; setp.gt.s32 p3, %8, 3;\n"
                 "mov.u32 %0, 0; mov.u32 %1, 0; mov.u32 %2, 0; mov.u32 %3, 0;\n"
                 "@p0 dp2a.lo.u32.u32 %0, %4, 4, 0; @p1 dp2a.lo.u32.u32 %1, %5, 4, 0; @p2 dp2a.lo.u32.u32 %2, %6, 4, 0; @p3 dp2a.lo.u32.u32 %3, %7, 4, 0;\n"
                 "@p0 ld.shared.u32 %0, [%0+%9]; @p1 ld.shared.u32 %1, [%1+%9]; @p2 ld.shared.u32 %2, [%2+%9]; @p3 ld.shared.u32 %3, [%3+%9];}"
                 : "=&r"(v[0]), "=&r"(v[1]), "=&r"(v[2]), "=&r"(v[3]) : "r"(a.x), "r"(a.y), "r"(a.z), "r"(a.w), "r"(n), "n"(SB));
}

constexpr uint32_t R_V1 = 0x03000, R_A = 0x81000, R_B = 0x82000, R_UNIT = 0x4000, R_HI = 0x40000 - 8 * 256;
__device__ __forceinline__ uint32_t q_base(uint32_t q, uint32_t pagebits_x) { return (q << 20) | (((pagebits_x >> (q >> 1)) & 1u) << 12); }
__device__ __forceinline__ uint32_t slot_off(uint32_t s) { return (s << 16) | (((s + 1) & 2) << 11); }
constexpr uint32_t OFF_PF = R_B + 3 * R_UNIT, OFF_RDY = OFF_PF + 128, OFF_REL = OFF_PF + 256;
constexpr uint32_t OFF_PROBE = 3 * R_UNIT;
static_assert(RA <= 4 && RV <= 4 && RB <= 8 && RA <= RB && RV <= RB, "ring");

__device__ __forceinline__ uint32_t probe(unsigned char* p) {
    volatile uint32_t* sink = (volatile uint32_t*)(smem + S_MISC + 240);
    asm volatile("st.global.v4.u32 [%0], {%1,%1,%1,%1};" ::"l"(p), "r"(0) : "memory");
    asm volatile("st.global.v4.u32 [%0], {%1,%1,%1,%1};" ::"l"(p + 16), "r"(0) : "memory");
    uint32_t best = 0xffffffffu;
#pragma unroll 1
    for (int r = 0; r < 3; r++) {
        uint32_t t0, t1, v;
        asm volatile("mov.u32 %0, %%clock;" : "=r"(t0)::"memory");
        asm volatile("atom.relaxed.gpu.global.add.u32 %0, [%1], 1;" : "=r"(v) : "l"(p) : "memory");
        *sink = v;
        asm volatile("mov.u32 %0, %%clock;" : "=r"(t1)::"memory");
        best = min(best, t1 - t0);
    }
    return best;
}

struct Wts { float c[8], wr[32], ws[32], wd[16], wu[16]; };
__device__ __forceinline__ void load_wts(const Prm& p, Wts* w) {
    int t = threadIdx.x;
    if (t < 8) w->c[t] = __bfloat162float(p.centers[t]);
    if (t < 32) { w->wr[t] = __bfloat162float(p.w_rbf[t]); w->ws[t] = __bfloat162float(p.w_sbf[t]); }
    if (t < 16) { w->wd[t] = __bfloat162float(p.w_down[t]); w->wu[t] = __bfloat162float(p.w_up[t]); }
}
__device__ __forceinline__ void radial(const Wts* w, float d, float s[4], float g[4]) {
#pragma unroll
    for (int j = 0; j < 4; j++) s[j] = g[j] = 0.f;
#pragma unroll
    for (int r = 0; r < 8; r++) {
        float x = rbf16(d - w->c[r]);
        float b = rbf16(__expf(rbf16(-10.0f * rbf16(x * x))));
#pragma unroll
        for (int j = 0; j < 4; j++) { s[j] += b * w->ws[r * 4 + j]; g[j] += b * w->wr[r * 4 + j]; }
    }
}
__device__ __noinline__ uint4 radial_bf16(const Wts* w, uint32_t dbits) {
    float s[4], g[4];
    radial(w, __uint_as_float(dbits << 16), s, g);
    return make_uint4(pack_bf16(s[1], s[0]), pack_bf16(s[3], s[2]), pack_bf16(g[1], g[0]), pack_bf16(g[3], g[2]));
}
__device__ __forceinline__ uint2 finish_row(const float* wu, const float agg[4], const float g[4], uint2 r) {
    float o[4];
    const float mm[4] = {bf_lo(r.x), bf_hi(r.x), bf_lo(r.y), bf_hi(r.y)};
#pragma unroll
    for (int j = 0; j < 4; j++) o[j] = mm[j] + (agg[0] * wu[j] + agg[1] * wu[4 + j] + agg[2] * wu[8 + j] + agg[3] * wu[12 + j]) * g[j];
    return make_uint2(pack_bf16(o[1], o[0]), pack_bf16(o[3], o[2]));
}
__device__ __forceinline__ uint2 down_row(const float* wd, uint32_t x, uint32_t y) {
    const float a[4] = {bf_lo(x), bf_hi(x), bf_lo(y), bf_hi(y)};
    float d[4];
#pragma unroll
    for (int j = 0; j < 4; j++) d[j] = a[0] * wd[j] + a[1] * wd[4 + j] + a[2] * wd[8 + j] + a[3] * wd[12 + j];
    return make_uint2(pack_bf16(d[1], d[0]), pack_bf16(d[3], d[2]));
}

__device__ __forceinline__ void down_load(const Prm& p, int pc) {
    const int r0 = pc * PC_ROWS / 2, nr = max(min((pc + 1) * PC_ROWS, p.E) / 2 - r0, 0);
    const uint32_t bar = SB + S_MISC + 248;
    mbar_init(bar, 1);
    asm volatile("fence.proxy.async.shared::cta;" ::: "memory");
    asm volatile("mbarrier.arrive.expect_tx.shared.b64 _, [%0], %1;" ::"r"(bar), "r"(nr * 16) : "memory");
    for (int o = 0; o < nr; o += 640)
        asm volatile("cp.async.bulk.shared::cluster.global.mbarrier::complete_tx::bytes [%0], [%1], %2, [%3];"
                     ::"r"(SB + S_PC + o * 16), "l"((const uint4*)p.m + r0 + o), "r"(min(640, nr - o) * 16), "r"(bar) : "memory");
}
__device__ __forceinline__ void down_piece(const Prm& p, int pc, const float* wd) {
    const int tid = threadIdx.x, lane = tid & 31, w = __shfl_sync(0xffffffffu, tid >> 5, 0);
    const int r0 = pc * PC_ROWS / 2, nr = max(min((pc + 1) * PC_ROWS, p.E) / 2 - r0, 0);
    TS(0);
    mbar_wait(SB + S_MISC + 248, 0);
    TS(1);
    uint32_t mx0 = 0, mx1 = 0; float ss[4] = {0.f, 0.f, 0.f, 0.f};
    for (int r = tid; r < nr; r += THREADS) {
        const uint4 v = ((const uint4*)(smem + S_PC))[r];
        const uint2 a = down_row(wd, v.x, v.y), b = down_row(wd, v.z, v.w);
        ((uint2*)g_md[0])[r0 + r] = make_uint2(a.x, b.x); ((uint2*)g_md[1])[r0 + r] = make_uint2(a.y, b.y);
        mx0 = __vimax3_u16x2(mx0, a.x & 0x7fff7fffu, b.x & 0x7fff7fffu); mx1 = __vimax3_u16x2(mx1, a.y & 0x7fff7fffu, b.y & 0x7fff7fffu);
        ss[0] += bf_lo(a.x) * bf_lo(a.x) + bf_lo(b.x) * bf_lo(b.x); ss[1] += bf_hi(a.x) * bf_hi(a.x) + bf_hi(b.x) * bf_hi(b.x);
        ss[2] += bf_lo(a.y) * bf_lo(a.y) + bf_lo(b.y) * bf_lo(b.y); ss[3] += bf_hi(a.y) * bf_hi(a.y) + bf_hi(b.y) * bf_hi(b.y);
    }
    TS(2);
    uint32_t st[4] = {mx0 << 16, mx0 & 0xffff0000u, mx1 << 16, mx1 & 0xffff0000u};
    uint4* red = (uint4*)(smem + S_PC + PC_ROWS * 8);
    for (int pass = 0; pass < 2; pass++) {
#pragma unroll
        for (int ch = 0; ch < 4; ch++) {
            st[ch] = __reduce_max_sync(0xffffffffu, st[ch]);
#pragma unroll
            for (int o = 16; o; o >>= 1) ss[ch] += __shfl_xor_sync(0xffffffffu, ss[ch], o);
        }
        uint4* dst = pass ? (uint4*)g_ctl.stat[pc] : red + 2 * w;
        if (lane == 0) { dst[0] = make_uint4(st[0], st[1], st[2], st[3]); dst[1] = make_uint4(__float_as_uint(ss[0]), __float_as_uint(ss[1]), __float_as_uint(ss[2]), __float_as_uint(ss[3])); }
        if (pass) break;
        __syncthreads();
        if (w != NW - 1) return;
        const uint4 a = lane < NW ? red[2 * lane] : make_uint4(0, 0, 0, 0), b = lane < NW ? red[2 * lane + 1] : make_uint4(0, 0, 0, 0);
        st[0] = a.x; st[1] = a.y; st[2] = a.z; st[3] = a.w;
        ss[0] = __uint_as_float(b.x); ss[1] = __uint_as_float(b.y); ss[2] = __uint_as_float(b.z); ss[3] = __uint_as_float(b.w);
    }
    TS(3);
}

#define KAPPA 3.3f
__device__ __forceinline__ void get_scales(const Prm& p, float sc[4], bool& bad) {
    const int lane = threadIdx.x & 31;
    uint32_t mxb[4] = {0, 0, 0, 0};
    float ss[4] = {0.f, 0.f, 0.f, 0.f};
#pragma unroll
    for (int k = 0; k < (NPC + 31) / 32; k++) {
        if (lane + 32 * k < NPC) {
            const uint4 a = ld_relaxed4(&g_ctl.stat[lane + 32 * k][0]), b = ld_relaxed4(&g_ctl.stat[lane + 32 * k][4]);
            mxb[0] = max(mxb[0], a.x); mxb[1] = max(mxb[1], a.y); mxb[2] = max(mxb[2], a.z); mxb[3] = max(mxb[3], a.w);
            ss[0] += __uint_as_float(b.x); ss[1] += __uint_as_float(b.y); ss[2] += __uint_as_float(b.z); ss[3] += __uint_as_float(b.w);
        }
    }
    bad = false;
    const float kdeg = fminf(KAPPA * sqrtf(fmaxf(0.5f * (float)p.T / (float)p.E, 1.0f)), 128.f);
#pragma unroll
    for (int ch = 0; ch < 4; ch++) {
        const float mx = __uint_as_float(__reduce_max_sync(0xffffffffu, mxb[ch]));
#pragma unroll
        for (int o = 16; o; o >>= 1) ss[ch] += __shfl_xor_sync(0xffffffffu, ss[ch], o);
        const float rms = sqrtf(ss[ch] / (float)p.E);
        const float range = fmaxf(2.001f * mx, kdeg * rms);
        if (!(mx <= 1e15f) || !(range <= 128.f * rms) || (mx > 0.f && mx < 1e-15f)) bad = true;
        sc[ch] = range > 0.f ? __uint_as_float(((__float_as_uint(range) + 0x7fffffu) & 0x7f800000u) - (15u << 23)) : 1.f;
    }
    if (bad) sc[0] = sc[1] = sc[2] = sc[3] = 1.f;
}

__device__ __forceinline__ float magic_lo(float step_lo) { return 12582912.f * step_lo; }
__device__ __forceinline__ float magic_hi(float step_lo, float step_hi) { return (float)(12582912 - (int)(__float_as_uint(magic_lo(step_lo)) >> 16)) * step_hi; }
__device__ __forceinline__ uint32_t term(uint32_t m, float c, float mag_lo, float mag_hi) {
    return (__float_as_uint(fmaf(bf_hi(m), c, mag_hi)) << 16) + __float_as_uint(fmaf(bf_lo(m), c, mag_lo));
}

constexpr int PER = 40;
__host__ __device__ constexpr uint32_t bar_done(uint32_t s) { return SB + P_BAR + (s % NBUF) * 16; }
__host__ __device__ constexpr uint32_t bar_free(uint32_t m) { return bar_done(m + NBUF - (GR - 1)) + 8; }
struct __align__(16) PTab { uint32_t e[PER][4]; };
constexpr PTab make_ptab() {
    PTab t = {};
    for (int s = 0; s < PER; s++) {
        for (int d = 0; d < GR; d++) {
            int gi = (s + d) % GR, buf = (s + d) % NBUF, X = gi & 1, g = gi >> 1;
            t.e[s][X] |= (uint32_t)(4 * UN * buf - g - 4 * X + 7) << (8 * g);
        }
        t.e[s][2] = bar_done(s);
        t.e[s][3] = (((s + GR - 1) / NBUF) & 1) ^ 1;
    }
    return t;
}
__constant__ PTab c_ptab = make_ptab();
constexpr int BIAS = 7 * NCP;
static_assert(NG == 4 && CPS >= FW, "group selection");

struct PCtx { uint32_t a0, a1; };
struct PElem { uint32_t b4, aw, ol, r2; };

__device__ __forceinline__ void p_bin(const PCtx& c, PElem& e, uint32_t i, uint32_t o) {
    uint32_t ib = __umulhi(i, MAG_I), ob = __umulhi(o, MAG_O), sel = ib & 3;
    asm("{.reg .pred p; setp.ge.u32 p, %1, %2; @p add.u32 %0, %0, 4;}" : "+r"(sel) : "r"(o), "n"(HALF_O));
    e.b4 = __dp4a(prmt(c.a0, c.a1, sel), (uint32_t)NCP, ib * NCP + ob * 4);
    e.aw = i - ib * ROWS_I;
    e.ol = o - ob * ROWS_O;
}
__device__ __forceinline__ void p_rank(PElem& e) {
    asm volatile("atom.shared.add.u32 %0, [%1+%2], 2;" : "=r"(e.r2) : "r"(e.b4), "n"(SB + P_CNT - BIAS) : "memory");
}
__device__ __forceinline__ void p_store(const PElem& e) {
    const uint32_t ab = e.b4 * (KS / 2) + e.r2;
    asm volatile("{.reg .pred p; setp.lt.u32 p, %4, %5; @p st.shared.u32 [%0+%6], %1; @p st.shared.u16 [%2+%7], %3;}"
                 ::"r"(ab * 2), "r"(e.aw), "r"(ab), "h"((uint16_t)e.ol), "r"(e.r2), "n"(KS * 2),
                   "n"(SB + P_A - BIAS * KS), "n"(SB + P_B - BIAS * (KS / 2)) : "memory");
}
__device__ __forceinline__ uint32_t cos2(uint32_t x) {
    x = __vminu2(x, 0x42804280u);
    return pack_bf16(__cosf(bf_hi(x)), __cosf(bf_lo(x)));
}

#define PD_ 2
#define CB_ 8
constexpr int CB = CB_;
struct PIn { uint4 i, o; uint2 a; };

struct PFill {
    PCtx c;
    uint32_t qb, qt, lt, f2, bar, par, xmax;
    uint32_t s0, lane, vb;
    bool open;
    __device__ __forceinline__ void fetch(const Prm& p, PIn& x, uint32_t ch) {
        const int v = ((ch & ~(CB - 1u)) * (NP - 1) + ch) * 32 + vb;
        asm volatile("{.reg .b32 d0, d1; tex.1d.v4.u32.s32 {%0,%1,d0,d1}, [%2, {%3}];}" : "=r"(x.a.x), "=r"(x.a.y) : "l"(p.t_ang), "r"(v));
        asm volatile("tex.1d.v4.u32.s32 {%0,%1,%2,%3}, [%4, {%5}];" : "=r"(x.i.x), "=r"(x.i.y), "=r"(x.i.z), "=r"(x.i.w) : "l"(p.t_in), "r"(v));
        asm volatile("tex.1d.v4.u32.s32 {%0,%1,%2,%3}, [%4, {%5}];" : "=r"(x.o.x), "=r"(x.o.y), "=r"(x.o.z), "=r"(x.o.w) : "l"(p.t_out), "r"(v));
    }
    __device__ __forceinline__ uint32_t ticket(uint32_t zero) {
        uint32_t t;
        asm volatile("atom.shared.add.u32 %0, [%1+%2], %3;" : "=r"(t) : "r"(lane * 4), "n"(SB + P_TKT), "r"((~lt & 1) | zero) : "memory");
        return t;
    }
    __device__ __forceinline__ uint32_t use_ticket(uint32_t t) {
        t = __reduce_or_sync(0xffffffffu, t);
        begin(t / CPS);
        return t + PD_ * FW;
    }
    __device__ __forceinline__ void begin(uint32_t step) {
        const uint4 t = ((const uint4*)c_ptab.e)[(step + s0) % PER];
        c.a0 = t.x; c.a1 = t.y; bar = t.z; par = t.w;
        open = mbar_test(bar + 8, par);
    }
    __device__ __forceinline__ void enter() { if (!open) mbar_wait(bar + 8, par); }
    __device__ __forceinline__ void end() {
        __syncwarp();
        asm volatile("{.reg .pred p; setp.eq.u32 p, %1, 0; @p mbarrier.arrive.shared.b64 _, [%0];}" ::"r"(bar), "r"(lt) : "memory");
    }
    __device__ __forceinline__ void push(bool f, uint32_t x, uint32_t y) {
        const uint32_t mask = __ballot_sync(0xffffffffu, f);
        asm volatile("{.reg .pred p; setp.ne.u32 p, %3, 0; @p st.shared.v2.u32 [%0], {%1,%2};}"
                     ::"r"(min(qt + __popc(mask & lt) * 8, qb + (QN - 1) * 8)), "r"(x), "r"(y), "r"((uint32_t)f) : "memory");
        qt += __popc(mask) * 8;
    }
    __device__ __forceinline__ void push3(bool f, uint32_t i, uint32_t o, uint32_t aw) { push(f, prmt(i, aw, 0x6210), prmt(o, aw, 0x7210)); }
    __device__ __forceinline__ uint32_t chunk(const PIn& x) {
        uint32_t x0, x1;
        const uint32_t tk = use_ticket(ticket(x.o.x >> 31));
        PElem e0, e1, e2, e3;
        p_bin(c, e0, x.i.x, x.o.x); p_bin(c, e1, x.i.y, x.o.y); p_bin(c, e2, x.i.z, x.o.z); p_bin(c, e3, x.i.w, x.o.w);
        asm volatile("" : "+r"(e0.b4), "+r"(e1.b4), "+r"(e2.b4), "+r"(e3.b4));
        enter();
        p_rank(e0); p_rank(e1); p_rank(e2); p_rank(e3);
        asm volatile("mul.rn.bf16x2 %0, %1, %2;" : "=r"(x0) : "r"(x.a.x), "r"(f2));
        asm volatile("mul.rn.bf16x2 %0, %1, %2;" : "=r"(x1) : "r"(x.a.y), "r"(f2));
        x0 &= 0x7fff7fffu; x1 &= 0x7fff7fffu;
        xmax = __vimax3_u16x2(xmax, x0, x1);
        const uint32_t c0 = cos2(x0), c1 = cos2(x1);
        e0.aw = prmt(e0.aw, c0, 0x5410); e1.aw = prmt(e1.aw, c0, 0x7610); e2.aw = prmt(e2.aw, c1, 0x5410); e3.aw = prmt(e3.aw, c1, 0x7610);
        p_store(e0); p_store(e1); p_store(e2); p_store(e3);
        if (qt - qb >= QTRIG * 8) retry(32);
        end();
        const uint32_t r01 = e0.r2 | e1.r2, r23 = e2.r2 | e3.r2;
        const bool f = (r01 | r23) >= KS * 2;
        if (__any_sync(0xffffffffu, f)) {
            const bool f0 = e0.r2 >= KS * 2, f1 = e1.r2 >= KS * 2, f2_ = e2.r2 >= KS * 2, f3 = e3.r2 >= KS * 2, f01 = r01 >= KS * 2;
            push3(f, f01 ? (f0 ? x.i.x : x.i.y) : (f2_ ? x.i.z : x.i.w), f01 ? (f0 ? x.o.x : x.o.y) : (f2_ ? x.o.z : x.o.w),
                  f01 ? (f0 ? e0.aw : e1.aw) : (f2_ ? e2.aw : e3.aw));
            const uint32_t s2 = max(max(min(e0.r2, e1.r2), min(e2.r2, e3.r2)), min(r01, r23));
            if (__any_sync(0xffffffffu, s2 >= KS * 2)) {
                push3(f1 && f0, x.i.y, x.o.y, e1.aw); push3(f2_ && f01, x.i.z, x.o.z, e2.aw); push3(f3 && (f01 || f2_), x.i.w, x.o.w, e3.aw);
            }
        }
        return tk;
    }
    __device__ __forceinline__ void retry(uint32_t take) {
        if (qt - qb > QN * 8) { st_relaxed(&g_ctl.bad, 1); qt = qb + QN * 8; }
        uint2 e, r, r1;
        __syncwarp();
        asm volatile("ld.shared.v2.u32 {%0,%1}, [%2];" : "=r"(e.x), "=r"(e.y) : "r"(qb + lane * 8) : "memory");
        asm volatile("ld.shared.v2.u32 {%0,%1}, [%2];" : "=r"(r.x), "=r"(r.y) : "r"(qb + (lane + take) * 8) : "memory");
        qt -= take * 8;
        const bool more = qt - qb > 256;
        if (more) asm volatile("ld.shared.v2.u32 {%0,%1}, [%2];" : "=r"(r1.x), "=r"(r1.y) : "r"(qb + (lane + take) * 8 + 256) : "memory");
        __syncwarp();
        if (more && qb + lane * 8 + 256 < qt) asm volatile("st.shared.v2.u32 [%0], {%1,%2};" ::"r"(qb + lane * 8 + 256), "r"(r1.x), "r"(r1.y) : "memory");
        if (qb + lane * 8 < qt) asm volatile("st.shared.v2.u32 [%0], {%1,%2};" ::"r"(qb + lane * 8), "r"(r.x), "r"(r.y) : "memory");
        PElem el;
        el.r2 = 0;
        if (take == 32 || lane < take) {
            p_bin(c, el, e.x & 0xffffffu, e.y & 0xffffffu);
            el.aw = prmt(el.aw, prmt(e.x, e.y, 0x0073), 0x5410);
            p_rank(el);
            p_store(el);
        }
        push(el.r2 >= KS * 2, e.x, e.y);
    }
};

__device__ __forceinline__ void p_filler(const Prm& p, int q, int w) {
    PFill F;
    const int lane = threadIdx.x & 31;
    const uint32_t NS = p.NS, cend = p.T >> 7, nv = NS * CPS, nc = cend / (NP * CB) * CB + min(max((int)(cend % (NP * CB)) - q * CB, 0), CB);
    static_assert(QN <= 96, "retry moves two batches");
    F.lt = __shfl_sync(0xffffffffu, (1u << lane) - 1u, lane);
    F.lane = __shfl_sync(0xffffffffu, lane, lane);
    F.vb = __shfl_sync(0xffffffffu, q * (32 * CB) + lane, lane);
    F.f2 = __shfl_sync(0xffffffffu, __bfloat16_as_ushort(p.freq[0]) * 0x10001u, 0);
    F.qb = F.qt = SB + P_Q + w * (QN * 8);
    F.s0 = q % GR; F.xmax = 0;
    uint32_t c0 = w, c1 = w + FW;
    PIn x0, x1;
    F.fetch(p, x0, c0);
#pragma unroll 1
    while (c0 < nc) {
        F.fetch(p, x1, c1);
        c0 = F.chunk(x0);
        if (c1 >= nc) break;
        F.fetch(p, x0, c0);
        c1 = F.chunk(x1);
    }
    int left = (c0 < nv) + (c1 < nv);
#pragma unroll 1
    while (left > 0) { left -= F.use_ticket(F.ticket(0)) >= nv; F.enter(); F.end(); }
    if (q == 0 && w < 8) {
        const int t = cend * 128 + w * 16 + lane;
        const bool f = t < p.T && lane < 16;
        uint32_t i = 0, o = 0, x = 0;
        if (f) { i = p.idx_in[t]; o = p.idx_out[t]; asm("mul.rn.bf16x2 %0, %1, %2;" : "=r"(x) : "r"(__bfloat16_as_ushort(p.angle[t]) * 0x10001u), "r"(F.f2)); }
        F.xmax = __vmaxu2(F.xmax, x & 0x7fff7fffu);
        if (F.qt - F.qb >= 32 * 8) { F.begin(NS); F.enter(); F.retry(32); }
        F.push3(f, i, o, cos2(x & 0x7fff7fffu));
    }
    F.begin(NS); F.enter();
    for (uint32_t nq = min((F.qt - F.qb) >> 3, (uint32_t)QN); nq > 0;) { uint32_t take = min(nq, 32u); F.retry(take); nq -= take; }
    F.end();
    if (CPS > FW && w < CPS - FW) F.end();
    if ((F.xmax + 0x3d803d80u) & 0x80008000u) st_relaxed(&g_ctl.bad, 1);
    uint32_t* late = (uint32_t*)(smem + P_LATE);
    const float* sc = (const float*)(smem + S_MISC);
    mbar_wait(SB + S_MISC + 232, 0);
    __syncwarp();
    for (uint32_t a = F.qb + lane * 8; a < F.qt; a += 256) {
        uint2 e;
        asm volatile("ld.shared.v2.u32 {%0,%1}, [%2];" : "=r"(e.x), "=r"(e.y) : "r"(a) : "memory");
        const uint32_t i = e.x & 0xffffffu, o = e.y & 0xffffffu, ob = __umulhi(o, MAG_O);
        const float c = __uint_as_float(prmt(e.x, e.y, 0x7300) & 0xffff0000u);
        const uint32_t m0 = ld_relaxed(&g_md[0][i]), m1 = ld_relaxed(&g_md[1][i]);
        const uint32_t k = atomicAdd(&late[ob], 1);
        if (k < LATE_N) g_late[ob][q][k][0] = g_late[ob][q][k][1] = make_uint4(o - ob * ROWS_O, term(m0, c, magic_lo(sc[0]), magic_hi(sc[0], sc[1])), term(m1, c, magic_lo(sc[2]), magic_hi(sc[2], sc[3])), 0);
        else st_relaxed(&g_ctl.bad, 1);
    }
    asm volatile("bar.sync 2, %0;" ::"n"(FW * 32) : "memory");
    if (w == 0) {
        if (lane < 16) g_late_n[q][lane] = ((const uint4*)late)[lane];
        __syncwarp();
        if (lane == 0) { fence_release(); red_add(&g_ctl.late_done, 1); }
    }
}

template <int N> __device__ __forceinline__ void p_stamp(const uint32_t (&st)[N], uint32_t off, uint32_t bit, bool set) {
    if (set) {
#pragma unroll
        for (int j = 0; j < N; j++) asm volatile("red.shared.or.b32 [%0], %1;" ::"r"(st[j] + off), "r"(bit) : "memory");
    } else {
#pragma unroll
        for (int j = 0; j < N; j++) asm volatile("red.shared.and.b32 [%0], %1;" ::"r"(st[j] + off), "r"(~bit) : "memory");
    }
}
__device__ __forceinline__ void bulk_store(void* dst, uint32_t src, uint32_t bytes) {
    asm volatile("cp.async.bulk.global.shared::cta.bulk_group [%0], [%1], %2;" ::"l"(dst), "r"(src), "r"(bytes) : "memory");
}
__device__ __forceinline__ void p_flusher(const Prm& p, unsigned char* ring, uint32_t pagebits, int q, int f) {
    const int lane = threadIdx.x & 31;
    const uint32_t NS = p.NS, NT = p.NT, s0 = q % GR;
    uint32_t sta[4], stb[2];
#pragma unroll
    for (int j = 0; j < 4; j++) {
        const int pp = min(8 * j + (lane >> 2), 26), bin = min(32 * j + lane, NB - 1);
        sta[j] = SB + P_A + pp * 512 + (lane & 3) * 160 + ((pp % 9) & 3) * 4;
        if (j < 2) stb[j] = SB + P_B + bin * 128 + ((bin % NCP) & 15) * 8;
    }
    const uint32_t pfo = OFF_PF + (lane / 6) * 32 + (lane & 1) * 16 + ((lane % 6) >> 1) * 4, pfc = (lane >> 1) * 6 + (lane & 1);
    const uint32_t wto = lane < NCP ? OFF_REL + lane * 4 : OFF_RDY + (lane % 6) * 4;
    PROF_DECL
#pragma unroll 1
    for (uint32_t n = f; n < NT; n += NF) {
        const uint32_t buf = (n + s0) % NBUF, h = n >> 1, lap = h / RB;
        const uint32_t qb = q_base(q, pagebits) ^ (((n + q) & 1) * 0x101000u), bb = qb ^ slot_off(h % RB);
        if (n == 2 * NF - 1) {
            float sc[4]; bool bad;
            wait_ge(&g_ctl.pieces_done, NPC);
            fence_acquire();
            get_scales(p, sc, bad);
            if (lane == 0) { *(float4*)(smem + S_MISC) = make_float4(sc[0], sc[1], sc[2], sc[3]); mbar_arrive(SB + S_MISC + 232); }
            __syncwarp();
        }
        if (h >= RA && !DEV_FREE) {
            const uint32_t hw = lane < NCP ? h : h + RB - RA;
            wait_all_ge(ring + (qb ^ slot_off(hw % RB) ^ wto), hw / RB);
        }
        PROF(0);
#pragma unroll
        for (int d = 2; d >= 0; d--) {
            const int nl = (int)min(n, NS) - d;
            if (nl >= 0) mbar_wait(bar_done(nl + s0), ((nl + s0) / NBUF) & 1);
        }
        PROF(1);
        uint32_t* cnt = (uint32_t*)(smem + P_CNT) + buf * NB;
        {
            const uint32_t oa = buf * (NB * KS * 4), ob = buf * (NB * KS * 2);
            unsigned char* da = ring + (qb ^ slot_off(h % RA) ^ R_A);
            unsigned char* db = ring + (bb ^ R_B);
            p_stamp(sta, oa, 0x40000000u, (h / RA) & 1);
            p_stamp(stb, ob, 0x8000u, lap & 1);
            __syncwarp();
            if (elect_one()) {
                asm volatile("fence.proxy.async.shared::cta;" ::: "memory");
#pragma unroll
                for (int u = 0; u < UN; u++) {
                    bulk_store(da + u * R_UNIT, SB + P_A + oa + u * (NCP * KS * 4), 8 * KS * 4);
                    bulk_store(da + u * R_UNIT + 0x40000, SB + P_A + oa + (u * NCP + 8) * (KS * 4), (NCP - 8) * KS * 4);
                }
#pragma unroll
                for (int u = 0; u < UN; u++) bulk_store(db + u * R_UNIT, SB + P_B + ob + u * (NCP * KS * 2), NCP * KS * 2);
            }
            __syncwarp();
        }
        uint32_t wm = (lap + 1) << 21;
        if (lane < NCP) {
#pragma unroll
            for (int u = 0; u < 3; u++) wm |= min(cnt[pfc + 2 * u] >> 1, (uint32_t)KS) << (7 * u);
        }
        __syncwarp();
        const uint32_t c0 = n + NBUF < NT ? 0 : KS * 2;
        if (lane < NB / 2) ((uint2*)cnt)[lane] = make_uint2(c0, c0);
        PROF(3);
        asm volatile("cp.async.bulk.commit_group;" ::: "memory");
        asm volatile("cp.async.bulk.wait_group 0;" ::: "memory");
        __syncwarp();
        PROF(2);
        const bool safe = h < RB;
        if (!safe && lane < NCP) st_relaxed(ring + (bb ^ pfo), wm);
        if (n > 0) mbar_wait(bar_free(n - 1 + s0), ((n - 1 + s0) / NBUF) & 1);
        if (lane == 0) mbar_arrive(bar_free(buf));
        if (safe) {
            fence_release();
            if (lane < NCP) st_relaxed(ring + (bb ^ pfo), wm);
        }
        PROF(4);
    }
    PROF_END;
}
__device__ __forceinline__ void p_cleanup(unsigned char* ring, int q) {
    const int k = threadIdx.x / 24;
    if (k < 2 * RB) *(uint4*)(ring + ((q << 20) ^ ((k & 1) << 12) ^ slot_off(k >> 1) ^ OFF_PF) + (threadIdx.x % 24) * 16) = make_uint4(0, 0, 0, 0);
}

__device__ __forceinline__ void m_role(const Prm& p, unsigned char* ring, int X, int id) {
    const int tid = threadIdx.x, lane = tid & 31, w = __shfl_sync(0xffffffffu, tid >> 5, 0);
    const int ib = id >> 1, ty = id & 1;
    float* scs = (float*)(smem + S_MISC);
    if (w < 2) {
        const uint32_t bar = SB + S_AUX;
        uint32_t pb = 0;
        if (tid == 0) mbar_init(bar, 1);
        for (int it = 0; w == 1 && !((pb = ld_relaxed(&g_ctl.pagebits)) >> 31);) backoff(it);
        wait_ge(&g_ctl.pieces_done, NPC);
        TS(5);
        fence_acquire();
        if (tid == 0) {
            asm volatile("fence.proxy.async.global;" ::: "memory");
            asm volatile("fence.proxy.async.shared::cta;" ::: "memory");
            asm volatile("mbarrier.arrive.expect_tx.shared.b64 _, [%0], %1;" ::"r"(bar), "r"(ROWS_I * 4) : "memory");
            constexpr uint32_t PART = (ROWS_I * 4 / 8 + 127) / 128 * 128;
            for (uint32_t o = 0; o < ROWS_I * 4; o += PART)
                asm volatile("cp.async.bulk.shared::cluster.global.mbarrier::complete_tx::bytes [%0], [%1], %2, [%3];"
                             ::"r"(SB + o), "l"((const char*)(g_md[ty] + ib * ROWS_I) + o), "r"(min(PART, ROWS_I * 4 - o)), "r"(bar) : "memory");
        }
        __syncwarp();
        if (w == 0) { mbar_wait(bar, 0); TS(7); }
        else {
            float sc[4]; bool bad;
            get_scales(p, sc, bad);
            if (bad) st_relaxed(&g_ctl.bad, 1);
            if (lane == 0) { scs[0] = sc[0]; scs[1] = sc[1]; scs[2] = sc[2]; scs[3] = sc[3]; ((uint32_t*)scs)[4] = X ? ~pb : pb; ((uint32_t*)scs)[5] = bad; }
            TS(6);
        }
    }
    __syncthreads();
    if (((uint32_t*)scs)[5]) {
        for (int k = tid; k < (int)ROWS_I; k += THREADS) ((uint32_t*)smem)[k] = 0;
        __syncthreads();
    }
    const uint32_t NT = p.NT;
    if (w >= MW) return;
    const uint32_t pagebits = ((uint32_t*)scs)[4];
    const int half = lane >> 4, k4 = (lane & 15) * 4;
    const float mag_lo = magic_lo(scs[2 * ty]), mag_hi = magic_hi(scs[2 * ty], scs[2 * ty + 1]), bias = 16384.f * scs[2 * ty + 1];
    const int il = ib / NG, gi = (ib % NG) * 2 + X;
    const uint32_t a_off = R_A + il * R_UNIT + lane * 16, v_off = ty * R_V1 + il * R_UNIT + lane * 16;
    const uint32_t f_off = OFF_PF + il * 32 + half * 16, r_off = OFF_REL + (lane % NCP) * 4;
    const uint32_t j = w % (NP / GR);
    PROF_DECL
#pragma unroll 1
    for (uint32_t n = w / (NP / GR); n < NT; n += MW / (NP / GR)) {
        const uint32_t q = ((gi - n) & (GR - 1)) + GR * j, h = n >> 1;
        const uint32_t qb = q_base(q ^ X, pagebits), bb = qb ^ slot_off(h % RB);
        const uint32_t tag = (h / RB + 1) << 21;
        uint4 cw; int it = 0;
        while (true) {
            cw = ld_relaxed4(ring + (bb ^ f_off));
            if (__all_sync(0xffffffffu, min(min(cw.x, cw.y), cw.z) >= tag)) break;
            if (DEV_FREE) { cw.x = (cw.x & 1) + (63 | 57 << 7 | 50 << 14); cw.y = (cw.y & 1) + (53 | 61 << 7 | 57 << 14); cw.z = (cw.z & 1) + (59 | 52 << 7 | 57 << 14); break; }
            backoff(it);
        }
        PROF(0);
        {
            const unsigned char* pa = ring + (qb ^ slot_off(h % RA) ^ a_off);
            unsigned char* pv = ring + (qb ^ slot_off(h % RV) ^ v_off);
            const uint32_t hv = h + RB - RV;
            const unsigned char* prel = ring + (qb ^ slot_off(hv % RB) ^ r_off);
            const uint32_t rel = ld_relaxed(prel);
            const uint32_t vlap = h / RV;
            const float mag_hi0 = fmaf(bias, (vlap & 1) ? 3.f : 1.f, mag_hi);
            const uint32_t stamp = ((h / RA) & (0x40100401u >> lane) & 1) << 30;
            uint4 a[9];
#define M_LOAD(ps) a[ps] = ld_relaxed4(pa + (ps) * 512 + ((ps) < 4 ? 0 : R_HI))
#pragma unroll
            for (int ps = 0; ps < MPF; ps++) M_LOAD(ps);
            if (!__all_sync(0xffffffffu, rel >= hv / RB) && !DEV_FREE) wait_all_ge(prel, hv / RB);
            PROF(3);
#define M_STAMP(ps) (((ps) & 3) == 0 ? a[ps].x : ((ps) & 3) == 1 ? a[ps].y : ((ps) & 3) == 2 ? a[ps].z : a[ps].w)
#pragma unroll
            for (int g = 0; g < 9; g += 3) {
                while (true) {
                    M_STAMP(g) ^= stamp; M_STAMP(g + 1) ^= stamp; M_STAMP(g + 2) ^= stamp;
                    if (!__any_sync(0xffffffffu, ((M_STAMP(g) | M_STAMP(g + 1) | M_STAMP(g + 2)) & 0x40000000u) != 0)) break;
                    if (DEV_FREE) { M_STAMP(g) &= 0xbfffffffu; M_STAMP(g + 1) &= 0xbfffffffu; M_STAMP(g + 2) &= 0xbfffffffu; break; }
                    if (++it > SPIN_MAX) __trap();
                    M_LOAD(g); M_LOAD(g + 1); M_LOAD(g + 2);
                }
                uint32_t mv[3][4];
#pragma unroll
                for (int u = 0; u < 3; u++) gather4(mv[u], a[g + u], (int)(((g == 0 ? cw.x : g == 3 ? cw.y : cw.z) >> (7 * u)) & 0x7f) - k4);
#pragma unroll
                for (int u = 0; u < 3; u++) {
                    const int ps = g + u;
                    asm volatile("st.global.v4.u32 [%0], {%1,%2,%3,%4};" ::"l"(pv + ps * 512 + (ps < 4 ? 0 : R_HI)),
                                 "r"(term(mv[u][0], bf_hi(a[ps].x), mag_lo, mag_hi0)), "r"(term(mv[u][1], bf_hi(a[ps].y), mag_lo, mag_hi)),
                                 "r"(term(mv[u][2], bf_hi(a[ps].z), mag_lo, mag_hi)), "r"(term(mv[u][3], bf_hi(a[ps].w), mag_lo, mag_hi)) : "memory");
                    if (ps + MPF < 9) M_LOAD(ps + MPF);
                }
            }
            if (vlap == 0) fence_release();
        }
        st_lane0(ring + (bb ^ (OFF_RDY + (2 * il + ty) * 4)), cw.x >> 21, lane);
        PROF(1);
    }
    PROF_END;
}

__device__ __forceinline__ void c_wrap(uint32_t ad, uint32_t old, uint32_t w) {
    const uint32_t ov = ~(old ^ w) & (old ^ (old + w)), sh = (ad & 4) * 2;
    const int d = (int)(((ov >> 15) & 1) + ((ov >> 27) & 16)) - (int)((((ov & w) >> 14) & 2) + (((ov & w) >> 26) & 32));
    uint32_t c;
    asm volatile("atom.shared.add.u32 %0, [%1+%2], %3;" : "=r"(c) : "r"((ad >> 3) * 4), "n"(SB / 2 + C_WRAP), "r"(d << sh) : "memory");
    c = (c >> sh) + d;
    asm volatile("{.reg .pred p; setp.eq.u32 p, %1, 0; @p st.relaxed.gpu.global.u32 [%0], 1;}" ::"l"(&g_ctl.bad), "r"(min((c + 1) & 0xe, (c + 16) & 0xe0)) : "memory");
}

#define CGRP 6
struct CTask { uint4 v[3]; uint2 b[3]; };
struct CWork {
    unsigned char *pv, *pb, *pf;
    uint32_t acc, lap1, sv, sb, vtag, fw, stamp;
    static __device__ __forceinline__ unsigned char* flip(unsigned char* p, uint32_t bits) { return (unsigned char*)((uintptr_t)p ^ bits); }
    static __device__ __forceinline__ uint32_t step(uint32_t s, uint32_t r) { return slot_off(s) ^ slot_off(s + 1 == r ? 0 : s + 1); }
    uint32_t last; int dev_free;
    __device__ __forceinline__ void load(CTask& t, int odd) {
#pragma unroll
        for (int ps = 0; ps < 3; ps++) { t.v[ps] = ld_relaxed4(pv + ps * R_UNIT + (odd << 20)); t.b[ps] = ld_relaxed2(pb + ps * R_UNIT + (odd << 20)); }
    }
    template <int ODD> __device__ __forceinline__ void issue(CTask& t) {
        if (!__all_sync(0xffffffffu, fw + last >= lap1)) {
            int it = 0;
            do {
                if (dev_free) break;
                backoff(it);
                fw = ld_relaxed(pf + (ODD << 20));
            } while (!__all_sync(0xffffffffu, fw + last >= lap1));
        }
        load(t, ODD);
        fw = ld_relaxed(ODD ? flip(pf, step(sb, RB)) : pf + (1 << 20));
    }
    template <int ODD> __device__ __forceinline__ void arrive(CTask& t) {
        int it = 0;
        while (true) {
#pragma unroll
            for (int ps = 0; ps < 3; ps++) { t.b[ps].x ^= stamp; t.v[ps].x ^= vtag; }
            if (!__any_sync(0xffffffffu, ((t.v[0].x | t.v[1].x | t.v[2].x) & 0x80000000u) | ((t.b[0].x | t.b[1].x | t.b[2].x) & 0x8000u))) break;
            if (dev_free) { for (int ps = 0; ps < 3; ps++) { t.v[ps].x &= 0x7fffffffu; t.b[ps].x &= 0xffff7fffu; } break; }
            if (++it > SPIN_MAX) __trap();
            load(t, ODD);
        }
        asm volatile("{.reg .pred p; setp.ne.u32 p, %2, 0; @p st.relaxed.gpu.global.u32 [%0], %1;}" ::"l"(pf + (ODD << 20)), "r"(lap1), "r"((uint32_t)last) : "memory");
        if (ODD) {
            pv = flip(pv, step(sv, RV)); pb = flip(pb, step(sb, RB)); pf = flip(pf, step(sb, RB));
            if (++sv == RV) { sv = 0; vtag ^= 0x80000000u; }
            if (++sb == RB) { sb = 0; lap1++; stamp ^= ((((uintptr_t)pb >> 4) ^ (uintptr_t)pb) & 0x78) == 0 ? 0x8000u : 0u; }
        }
    }
    __device__ __forceinline__ void add(const CTask& t) {
        const uint32_t vw[12] = {t.v[0].x - 0x40000000u, t.v[0].y, t.v[0].z, t.v[0].w, t.v[1].x - 0x40000000u, t.v[1].y, t.v[1].z, t.v[1].w, t.v[2].x - 0x40000000u, t.v[2].y, t.v[2].z, t.v[2].w};
        const uint32_t bw[6] = {t.b[0].x, t.b[0].y, t.b[1].x, t.b[1].y, t.b[2].x, t.b[2].y};
#pragma unroll
        for (int g = 0; g < 12; g += CGRP) {
            uint32_t old[CGRP], ov = 0;
#pragma unroll
            for (int e = g; e < g + CGRP; e++)
                asm volatile("atom.shared.add.u32 %0, [%1], %2;" : "=r"(old[e - g]) : "r"((e & 1) ? __dp2a_hi(bw[e >> 1], 0x08000008u, acc) : __dp2a_lo(bw[e >> 1], 0x08000008u, acc)), "r"(vw[e]) : "memory");
#pragma unroll
            for (int e = g; e < g + CGRP; e++) ov |= ~(old[e - g] ^ vw[e]) & (old[e - g] ^ (old[e - g] + vw[e]));
            if (__any_sync(0xffffffffu, ov & 0x80008000u)) {
#pragma unroll
                for (int e = g; e < g + CGRP; e++) c_wrap((e & 1) ? __dp2a_hi(bw[e >> 1], 0x08000008u, acc) : __dp2a_lo(bw[e >> 1], 0x08000008u, acc), old[e - g], vw[e]);
            }
        }
    }
};

__device__ __forceinline__ void c_role(const Prm& p, unsigned char* ring, int X, int c) {
    const int tid = threadIdx.x, lane = tid & 31, w = __shfl_sync(0xffffffffu, tid >> 5, 0);
    uint32_t* misc = (uint32_t*)(smem + S_MISC);
    Wts* wt = (Wts*)(smem + S_AUX);
    load_wts(p, wt);
    if (tid == 0) misc[6] = TAB_N;
    __syncthreads();
    if (w == 0) {
        float sc[4]; bool bad;
        wait_ge(&g_ctl.pieces_done, NPC);
        fence_acquire();
        get_scales(p, sc, bad);
        const float s = (lane & 2) ? ((lane & 1) ? sc[3] : sc[2]) : ((lane & 1) ? sc[1] : sc[0]);
        wt->ws[lane] *= s;
        int it = 0; uint32_t pb;
        while (!((pb = ld_relaxed(&g_ctl.pagebits)) >> 31)) backoff(it);
        misc[4] = X ? ~pb : pb;
    } else {
        const int r0 = (X * NCP + c) * ROWS_O, nr = min((int)ROWS_O, p.E - r0);
#pragma unroll 4
        for (int r = tid - 32; r < (int)ROWS_O / 2; r += THREADS - 32) {
            const uint32_t d2 = 2 * r < nr ? __ldg((const uint32_t*)(p.dist + r0) + r) : TAB_LO * 0x10001u;
            uint32_t e[2] = {(d2 & 0xffff) - TAB_LO, (d2 >> 16) - TAB_LO};
#pragma unroll
            for (int k = 0; k < 2; k++)
                if (e[k] >= TAB_N) {
                    const uint32_t d = e[k] + TAB_LO;
                    if ((d & 0x7f80) == 0x7f80) st_relaxed(&g_ctl.bad, 1);
                    e[k] = min(atomicAdd(&misc[6], 1u), 0xffffu);
                    if (e[k] < TAB_N + TAB_X) ((uint32_t*)(smem + C_TAB))[e[k] * 4] = d;
                }
            ((uint2*)(smem + C_WRAP))[r] = make_uint2(e[0] << 16 | 0x8888u, e[1] << 16 | 0x8888u);
        }
    }
    __syncthreads();
    if (w >= NP / 2) {
        const int nt = min(misc[6], (uint32_t)(TAB_N + TAB_X));
        for (int k = tid - NP * 16; k < nt; k += THREADS - NP * 16)
            ((uint4*)(smem + C_TAB))[k] = radial_bf16(wt, k < TAB_N ? TAB_LO + k : ((uint32_t*)(smem + C_TAB))[k * 4]);
        if (DEV_FREE) return;
        for (int it = 0; ld_relaxed(&g_ctl.late_done) == 0; it++) { __nanosleep(1000); if (it > SPIN_MAX) __trap(); }
        const int ob = X * NCP + c, nr = min((int)ROWS_O, p.E - ob * (int)ROWS_O);
        if (tid == THREADS - 1 && nr > 0) asm volatile("cp.async.bulk.prefetch.L2.global [%0], %1;" ::"l"(p.m + ob * ROWS_O), "r"(nr * 8) : "memory");
        for (int it = 0; ld_relaxed(&g_ctl.late_done) < NP; it++) { __nanosleep(100); if (it > SPIN_MAX) __trap(); }
            fence_acquire();
        constexpr int LQ = NP / (2 * (NW - NP / 2));
        const int q0 = (tid - NP * 16) >> 4;
        uint32_t n[LQ], nmax = 0;
#pragma unroll
        for (int j = 0; j < LQ; j++) n[j] = ld_relaxed((const uint32_t*)g_late_n[q0 * LQ + j] + ob);
#pragma unroll
        for (int j = 0; j < LQ; j++) { n[j] = min(n[j], (uint32_t)LATE_N); nmax = max(nmax, n[j]); }
        nmax = __reduce_max_sync(0xffffffffu, nmax);
        for (uint32_t k = lane & 15; k < ((nmax + 15) & ~15u); k += 16) {
            uint4 e[LQ];
            uint32_t o0[LQ], o1[LQ], ov = 0;
#pragma unroll
            for (int j = 0; j < LQ; j++) { e[j] = make_uint4(lane, 0, 0, 0); if (k < n[j]) e[j] = ld_relaxed4(g_late[ob][q0 * LQ + j][k]); }
#pragma unroll
            for (int j = 0; j < LQ; j++) { o0[j] = atomicAdd((uint32_t*)smem + 2 * e[j].x, e[j].y); o1[j] = atomicAdd((uint32_t*)smem + 2 * e[j].x + 1, e[j].z); }
#pragma unroll
            for (int j = 0; j < LQ; j++) ov |= (~(o0[j] ^ e[j].y) & (o0[j] ^ (o0[j] + e[j].y))) | (~(o1[j] ^ e[j].z) & (o1[j] ^ (o1[j] + e[j].z)));
            if (ov & 0x80008000u) {
#pragma unroll
                for (int j = 0; j < LQ; j++) { c_wrap(SB + e[j].x * 8, o0[j], e[j].y); c_wrap(SB + e[j].x * 8 + 4, o1[j], e[j].z); }
            }
        }
        __syncwarp();
        }
    const uint32_t pagebits = misc[4];
    if (w >= NP / 2) return;
    CWork W;
    const int par = lane >> 4;
    W.dev_free = DEV_FREE;
    const uint32_t qb = q_base(2 * w, pagebits), k = lane & 15;
    W.last = __shfl_sync(0xffffffffu, lane == 31, lane);
    W.acc = __shfl_sync(0xffffffffu, SB + par * 4, lane);
    W.pv = ring + (qb ^ (par * R_V1 + (c < 8 ? 0 : R_HI) + c * 256 + k * 16));
    W.pb = ring + (qb ^ (R_B + c * 128 + k * 8));
    W.pf = ring + (qb ^ (lane == 31 ? OFF_REL + c * 4 : OFF_RDY + (lane % 6) * 4));
    W.lap1 = 1; W.sv = W.sb = W.fw = W.stamp = W.vtag = 0;
    const uint32_t NT = p.NT;
    CTask A, B;
    PROF_DECL
    W.issue<0>(A);
#pragma unroll 1
    for (uint32_t n = 2;; n += 2) {
        W.arrive<0>(A); PROF(1); W.issue<1>(B); PROF(0); W.add(A);
        W.arrive<1>(B);
        if (n >= NT) break;
        PROF(1); W.issue<0>(A); PROF(0); W.add(B);
    }
    W.add(B);
    PROF_END;
}

__device__ __forceinline__ uint32_t bf2_mul(uint32_t a, uint32_t b) { uint32_t r; asm("mul.rn.bf16x2 %0, %1, %2;" : "=r"(r) : "r"(a), "r"(b)); return r; }
__device__ __forceinline__ uint32_t bf2_fma(uint32_t a, uint32_t b, uint32_t c) { uint32_t r; asm("fma.rn.bf16x2 %0, %1, %2, %3;" : "=r"(r) : "r"(a), "r"(b), "r"(c)); return r; }
__device__ __forceinline__ uint32_t c_agg(uint32_t a, uint32_t s, uint32_t wr, bool wrapped) {
    int x0 = (short)a, x1 = ((int)a >> 16) + ((a >> 15) & 1);
    if (wrapped) { const int w0 = (int)(wr & 15) - 8, w1 = (int)((wr >> 4) & 15) - 8; x0 += 65536 * w0; x1 += 65536 * w1 - w0; }
    return pack_bf16((float)x1 * bf_hi(s), (float)x0 * bf_lo(s));
}
__device__ __forceinline__ void c_epilogue(const Prm& p, int X, int c) {
    const int tid = threadIdx.x, lane = tid & 31;
    const Wts* wt = (const Wts*)(smem + S_AUX);
    uint32_t bw[4];
#pragma unroll
    for (int k = 0; k < 4; k++) {
        const int col = (k >> 1) * 2 + ((lane >> 2) & 1), row = (k & 1) * 2;
        bw[k] = (lane >> 3) == (lane & 3) ? pack_bf16(wt->wu[(row + 1) * 4 + col], wt->wu[row * 4 + col]) : 0u;
    }
    const int r0 = (X * NCP + c) * ROWS_O, np = max(min((int)ROWS_O, p.E - r0), 0) / 2;
    const uint4* mp = (const uint4*)(p.m + r0);
    uint4* op = (uint4*)(p.out + r0);
    constexpr int EB = 5;
#pragma unroll 1
    for (int rb = tid; rb - lane < np; rb += EB * THREADS) {
        uint4 mr[EB];
#pragma unroll
        for (int k = 0; k < EB; k++) mr[k] = __ldg(mp + min(rb + k * THREADS, np - 1));
#pragma unroll
        for (int k = 0; k < EB; k++) {
            const int r = min(rb + k * THREADS, np - 1);
            const uint4 a = ((const uint4*)smem)[r];
            const uint2 wr = ((const uint2*)(smem + C_WRAP))[r];
            const uint4 t0 = ((const uint4*)(smem + C_TAB))[min(wr.x >> 16, (uint32_t)(TAB_N + TAB_X - 1))];
            const uint4 t1 = ((const uint4*)(smem + C_TAB))[min(wr.y >> 16, (uint32_t)(TAB_N + TAB_X - 1))];
            const bool wrapped = __any_sync(0xffffffffu, prmt(wr.x, wr.y, 0x5410) != 0x88888888u);
            uint32_t a0, a1, a2, a3;
            if (wrapped) { a0 = c_agg(a.x, t0.x, wr.x, true); a2 = c_agg(a.y, t0.y, wr.x >> 8, true); a1 = c_agg(a.z, t1.x, wr.y, true); a3 = c_agg(a.w, t1.y, wr.y >> 8, true); }
            else { a0 = c_agg(a.x, t0.x, 0, false); a2 = c_agg(a.y, t0.y, 0, false); a1 = c_agg(a.z, t1.x, 0, false); a3 = c_agg(a.w, t1.y, 0, false); }
            float u[8];
#pragma unroll
            for (int h = 0; h < 2; h++)
                asm("mma.sync.aligned.m16n8k16.row.col.f32.bf16.bf16.f32 {%0,%1,%2,%3}, {%4,%5,%6,%7}, {%8,%9}, {%10,%10,%10,%10};"
                    : "=f"(u[4 * h]), "=f"(u[4 * h + 1]), "=f"(u[4 * h + 2]), "=f"(u[4 * h + 3])
                    : "r"(a0), "r"(a1), "r"(a2), "r"(a3), "r"(bw[2 * h]), "r"(bw[2 * h + 1]), "f"(0.f));
            const uint4 o = make_uint4(bf2_fma(pack_bf16(u[1], u[0]), t0.z, mr[k].x), bf2_fma(pack_bf16(u[5], u[4]), t0.w, mr[k].y),
                                       bf2_fma(pack_bf16(u[3], u[2]), t1.z, mr[k].z), bf2_fma(pack_bf16(u[7], u[6]), t1.w, mr[k].w));
            if (rb + k * THREADS < np) op[r] = o;
        }
    }
    if (((const uint32_t*)(smem + S_MISC))[6] > TAB_N + TAB_X) {
        for (int r = 2 * tid; r < 2 * np; r += (r & 1) ? 2 * THREADS - 1 : 1) {
            const uint32_t wr = ((const uint32_t*)(smem + C_WRAP))[r];
            if ((wr >> 16) < TAB_N + TAB_X) continue;
            const uint4 t = radial_bf16(wt, __bfloat16_as_ushort(p.dist[r0 + r]));
            const uint2 a = ((const uint2*)smem)[r];
            const uint32_t a0 = c_agg(a.x, t.x, wr, true), a1 = c_agg(a.y, t.y, wr >> 8, true);
            const float agg[4] = {bf_lo(a0), bf_hi(a0), bf_lo(a1), bf_hi(a1)}, g[4] = {bf_lo(t.z), bf_hi(t.z), bf_lo(t.w), bf_hi(t.w)};
            p.out[r0 + r] = finish_row(wt->wu, agg, g, p.m[r0 + r]);
        }
    }
}

__device__ __forceinline__ void grid_bar(unsigned* ctr) {
    __syncthreads();
    if (threadIdx.x == 0) { fence_gpu(); red_add(ctr, 1); wait_ge(ctr, gridDim.x); fence_gpu(); }
    __syncthreads();
}
__device__ __noinline__ void fallback(const Prm& p) {
    const int gt = blockIdx.x * THREADS + threadIdx.x, gs = gridDim.x * THREADS;
    Wts* wt = (Wts*)smem;
    __syncthreads();
    load_wts(p, wt);
    for (int e = gt; e < p.E; e += gs) g_acc[e] = make_float4(0.f, 0.f, 0.f, 0.f);
    grid_bar(&g_ctl.bar[0]);
    const float f = __bfloat162float(p.freq[0]);
    for (int t = gt; t < p.T; t += gs) {
        uint2 r = __ldg(p.m + p.idx_in[t]);
        float c = rbf16(cosf(rbf16(f * __bfloat162float(p.angle[t]))));
        asm volatile("red.global.add.v4.f32 [%0], {%1,%2,%3,%4};" ::"l"(g_acc + p.idx_out[t]), "f"(bf_lo(r.x) * c),
                     "f"(bf_hi(r.x) * c), "f"(bf_lo(r.y) * c), "f"(bf_hi(r.y) * c) : "memory");
    }
    grid_bar(&g_ctl.bar[1]);
    for (int e = gt; e < p.E; e += gs) {
        float4 a4 = __ldcg(g_acc + e);
        float a[4] = {a4.x, a4.y, a4.z, a4.w}, s[4], g[4];
        radial(wt, __bfloat162float(p.dist[e]), s, g);
        float agg[4];
#pragma unroll
        for (int j = 0; j < 4; j++) agg[j] = s[j] * (a[0] * wt->wd[j] + a[1] * wt->wd[4 + j] + a[2] * wt->wd[8 + j] + a[3] * wt->wd[12 + j]);
        p.out[e] = finish_row(wt->wu, agg, g, p.m[e]);
    }
}

__device__ __forceinline__ void smem_init(bool isp, int from, int to) {
    for (int k = from / 16 + threadIdx.x; k < to / 16; k += THREADS) {
        const bool b = isp && k >= P_B / 16 && k < P_Q / 16;
        const uint32_t z = b ? (k & 7) * 0x20002u : 0u, y = b ? z + 0x10001u : 0u;
        ((uint4*)smem)[k] = make_uint4(z, z, y, y);
    }
}

__global__ void __launch_bounds__(THREADS, 1) gemnet_kernel(const __grid_constant__ Prm p) {
    const int tid = threadIdx.x, lane = tid & 31, w = __shfl_sync(0xffffffffu, tid >> 5, 0);
    uint32_t* misc = (uint32_t*)(smem + S_MISC);
    bool run_fallback = true;
    if (!p.force_bad && __cvta_generic_to_shared(smem) == SB) {
        unsigned char* const ring = p.ring;
        uint32_t vid, nsm;
        asm("mov.u32 %0, %%smid;" : "=r"(vid)); asm("mov.u32 %0, %%nsmid;" : "=r"(nsm));
        vid = __shfl_sync(0xffffffffu, nsm != NCTA ? blockIdx.x : vid, 0);
        constexpr uint32_t NPF = NP - 4, V1 = NM + NPF, VX = NCTA - 8;
        const int grp = vid < NM ? 0 : vid < V1 ? 2 : 1;
        const uint32_t v1 = vid - V1 - (vid >= VX + 4 ? 4 : 0);
        const uint32_t pos = grp == 0 ? vid : (vid & ~3u) == VX ? NC + ((vid ^ 2) & 3) : (v1 >> 1) + (v1 & 1) * NCP;
        const int piece = grp == 2 ? NPC : grp * NM + pos;
        if (grp != 2) {
            if (lane == 0) {
                if (w < 2) misc[16 + w] = probe(ring + OFF_PROBE + w * 4096 + ((vid >> 7) << 20) + (vid & 127) * 32);
                else if (vid == VX && w <= NPAGES) misc[16 + w] = probe(ring + ((size_t)(w - 1) << 21) + OFF_PROBE);
            }
            __syncthreads();
            if (tid == 0) {
                atomicAdd(&g_ctl.sides[grp], (1ull << 56) | ((unsigned long long)(misc[16] > misc[17]) << pos));
                if (piece < NPC) down_load(p, piece);
            }
            if (vid == VX && tid == 32) {
                uint32_t pb = 0x80000000u;
                for (int k = 1; k < NPAGES; k++) pb |= (uint32_t)((2 * misc[17 + k] > misc[16] + misc[17]) != (misc[16] > misc[17])) << k;
                st_relaxed(&g_ctl.pagebits, pb);
            }
            if (w == 2) {
                const uint32_t n = grp ? NC + 4 : NM, cap = grp ? NCP : NMP;
                uint2 v; int it = 0;
                while (((v = ld_relaxed2(&g_ctl.sides[grp])).y >> 24) < n) backoff(it);
                const unsigned long long all = (1ull << n) - 1, far = (((unsigned long long)v.y << 32) | v.x) & all;
                const uint32_t side = (far >> pos) & 1, n1 = __popcll(far), no = side ? n - n1 : n1;
                uint32_t pool = grp * 2 + side, id = __popcll((side ? far : ~far) & ((1ull << pos) - 1));
                if (id >= cap) {
                    id -= cap;
                    if (no < cap && id < cap - no) { pool ^= 1; id += no; }
                    else { pool = 4; id = NPF + (no < cap ? id - (cap - no) : side ? id + (no - cap) : id); }
                }
                misc[8] = pool; misc[9] = id;
            }
        } else if (tid == 0) { misc[8] = 4; misc[9] = vid - NM; }
        if (grp != 0) smem_init(piece >= NPC, 0, S_PC);
        if (piece < NPC) {
            float wd[16];
#pragma unroll
            for (int k = 0; k < 16; k++) wd[k] = __bfloat162float(p.w_down[k]);
            __syncthreads();
            down_piece(p, piece, wd);
        }
        __syncthreads();
        const int pool = __reduce_or_sync(0xffffffffu, misc[8]), id = __reduce_or_sync(0xffffffffu, misc[9]);
        if (piece < NPC && tid == THREADS - 32) { fence_release(); red_add(&g_ctl.pieces_done, 1); }
        TS(4);
        if (DEV_FREE && !(DEV_FREE & (pool == 4 ? 1 : pool < 2 ? 2 : 4))) {
        } else if (pool == 4) {
            smem_init(true, piece < NPC ? 0 : S_PC, S_MISC);
            __syncthreads();
            if (tid < 2 * NBUF) {
                const uint32_t a = tid < NBUF ? bar_done(tid) : bar_free(tid), cnt = tid < NBUF ? CPS : 1;
                mbar_init(a, cnt);
                if (tid % NBUF < id % GR) asm volatile("mbarrier.arrive.shared.b64 _, [%0], %1;" ::"r"(a), "r"(cnt) : "memory");
            }
            if (tid == 32) mbar_init(SB + S_MISC + 232, 1);
            __syncthreads();
            if (w < FW) p_filler(p, id, w);
            else if (w < FW + NF) {
                int it = 0; uint32_t pb;
                while (!((pb = ld_relaxed(&g_ctl.pagebits)) >> 31)) backoff(it);
                p_flusher(p, ring, __shfl_sync(0xffffffffu, pb, 0), id, w - FW);
            }
        } else if (pool < 2) {
            m_role(p, ring, pool, id);
        } else {
            smem_init(false, 0, piece < NPC ? 0 : S_PC);
            c_role(p, ring, pool - 2, id);
        }
        __syncthreads();
        if (tid == 0) { fence_gpu(); red_add(&g_ctl.fin, 1); }
        if ((pool == 2 || pool == 3) && !DEV_FREE) c_epilogue(p, pool - 2, id);
        if (tid == 0) { wait_ge(&g_ctl.fin, NCTA); fence_gpu(); misc[10] = ld_relaxed(&g_ctl.bad); }
        __syncthreads();
        if (pool == 4) p_cleanup(ring, id);
        run_fallback = misc[10] && !DEV_FREE;
    }
    if (run_fallback) fallback(p);
    if (tid == 0) {
        fence_gpu();
        if (atomicAdd(&g_ctl.exited, 1) == gridDim.x - 1) {
            for (int k = 0; k < 6; k++) ((uint4*)&g_ctl)[k * 8] = make_uint4(0, 0, 0, 0);
        }
    }
}

cudaTextureObject_t make_tex(const void* ptr, size_t bytes, int words) {
    cudaResourceDesc rd = {};
    rd.resType = cudaResourceTypeLinear;
    rd.res.linear.devPtr = (void*)ptr;
    rd.res.linear.desc = words == 4 ? cudaCreateChannelDesc<uint4>() : cudaCreateChannelDesc<uint2>();
    rd.res.linear.sizeInBytes = bytes;
    cudaTextureDesc td = {};
    td.readMode = cudaReadModeElementType;
    cudaTextureObject_t t = 0;
    if (cudaCreateTextureObject(&t, &rd, &td, nullptr) != cudaSuccess) { cudaGetLastError(); return 0; }
    return t;
}

}

extern "C" void kernel_launch(void* const* d_in, const int* in_sizes, int n_in, void* d_out, int out_size) {
    static Prm p = {};
    static int grid = 0;
    const int E = in_sizes[3], T = in_sizes[1];
    if (grid == 0 || p.idx_in != d_in[1] || p.idx_out != d_in[2] || p.angle != d_in[4] || p.E != E || p.T != T) {
        int dev = 0, sms = 0;
        cudaGetDevice(&dev);
        cudaDeviceGetAttribute(&sms, cudaDevAttrMultiProcessorCount, dev);
        cudaFuncSetAttribute(gemnet_kernel, cudaFuncAttributeMaxDynamicSharedMemorySize, SMEM_BYTES);
        p.E = E; p.T = T;
        p.NS = (((T / 128 + NP * CB - 1) / (NP * CB)) * CB + CPS - 1) / CPS;
        if (p.NS < 3) p.NS = 3;
        p.NT = (p.NS + GR) & ~1;
        void* rp = nullptr;
        cudaGetSymbolAddress(&rp, g_ring);
        p.ring = (unsigned char*)(((uintptr_t)rp + ((2u << 20) - 1)) & ~(uintptr_t)((2u << 20) - 1));
        bool fast = sms >= NCTA && E <= (int)FAST_E && (E & 1) == 0 && T >= 128 && T <= (1 << 29);
        if (fast) {
            p.t_in = make_tex(d_in[1], (size_t)(T / 128) * 512, 4);
            p.t_out = make_tex(d_in[2], (size_t)(T / 128) * 512, 4);
            p.t_ang = make_tex(d_in[4], (size_t)(T / 128) * 256, 2);
            fast = p.t_in && p.t_out && p.t_ang;
        }
        p.force_bad = !fast;
        grid = fast ? NCTA : sms;
    }
    p.m = (const uint2*)d_in[0];
    p.idx_in = (const int*)d_in[1];
    p.idx_out = (const int*)d_in[2];
    p.dist = (const __nv_bfloat16*)d_in[3];
    p.angle = (const __nv_bfloat16*)d_in[4];
    p.centers = (const __nv_bfloat16*)d_in[5];
    p.freq = (const __nv_bfloat16*)d_in[6];
    p.w_rbf = (const __nv_bfloat16*)d_in[7];
    p.w_sbf = (const __nv_bfloat16*)d_in[8];
    p.w_down = (const __nv_bfloat16*)d_in[9];
    p.w_up = (const __nv_bfloat16*)d_in[10];
    p.out = (uint2*)d_out;
    gemnet_kernel<<<grid, THREADS, SMEM_BYTES>>>(p);
}
```

```cpp
#include <cuda_runtime.h>
#include <cuda_bf16.h>
#include <stdint.h>
#include <math.h>

namespace {

constexpr int NI = 12;
constexpr int UN = 3;
constexpr int NG = NI / UN;
constexpr int GR = 2 * NG;
constexpr int NCP = 18;
constexpr int NO = 2 * NCP;
constexpr int KS = 64;
constexpr int NB = UN * NCP;
constexpr int NBUF = 10;
constexpr int NMP = 2 * NI;
constexpr int NP = 48, NM = 2 * NMP, NC = NO, NCTA = NP + NM + NC;
#define CPS_ 25
constexpr int CPS = CPS_;
#define FW_ 24
constexpr int FW = FW_;
constexpr int NF = 4;
#define RA_ 3
#define RV_ 3
#define RB_ 4
constexpr int RA = RA_, RV = RV_, RB = RB_;
#define QN_ 96
#define QTRIG_ 48
constexpr int QN = QN_, QTRIG = QTRIG_;
#define MW_ 18
constexpr int MW = MW_;
constexpr int THREADS = 896, NW = THREADS / 32;
#define DEV_FREE 0
#define SLEEP_ 50

constexpr int RING_BYTES = NP << 20;
constexpr int NPAGES = RING_BYTES >> 21;
constexpr int MAX_E = 1 << 20;
constexpr int SMEM_BYTES = 232448;

constexpr int SB = 1024;

constexpr int P_CNT = 0;
constexpr int P_BAR = P_CNT + NBUF * NB * 4;
constexpr int P_TKT = P_BAR + 2 * NBUF * 8;
constexpr int P_LATE = P_TKT + 128;
constexpr int P_B = (P_LATE + 256 + 127) / 128 * 128;
constexpr int P_Q = P_B + NBUF * NB * KS * 2;
constexpr int P_A = SMEM_BYTES - 256 - NBUF * NB * KS * 4;
static_assert(P_Q + FW * QN * 8 + 512 <= P_A && P_A % 128 == 0, "P smem");
constexpr int S_MISC = SMEM_BYTES - 256;
constexpr int S_AUX = S_MISC - 512;

constexpr unsigned FAST_E = 640000;
constexpr unsigned magic_of(unsigned long long d) { return (unsigned)(((1ull << 32) + d - 1) / d); }
constexpr bool magic_ok(unsigned long long d) { return (magic_of(d) * d - (1ull << 32)) * FAST_E < (1ull << 32); }
constexpr unsigned pick_rows(unsigned lo, unsigned al) {
    unsigned d = (lo + al - 1) / al * al;
    while (!magic_ok(d)) d += al;
    return d;
}
constexpr unsigned ROWS_I = pick_rows((FAST_E + NI - 1) / NI, 32), ROWS_O = pick_rows((FAST_E + NO - 1) / NO, 16);
constexpr unsigned MAG_I = magic_of(ROWS_I), MAG_O = magic_of(ROWS_O), HALF_O = ROWS_O * NCP;
constexpr int C_WRAP = ROWS_O * 8, C_TAB = ROWS_O * 12, TAB_N = 1025, TAB_LO = 0x3f80 - 1024, TAB_X = (S_AUX - C_TAB) / 16 - TAB_N;
static_assert(ROWS_I * 4 + 4 <= S_AUX && TAB_X >= 100 && ROWS_I <= 65536 && ROWS_O <= 32768, "tables");

constexpr int NPC = NM + NC;
constexpr int PC_ROWS = ((FAST_E + NPC - 1) / NPC + 31) & ~31;
constexpr int S_PC = C_WRAP + 128 - C_WRAP % 128;
static_assert(S_PC + PC_ROWS * 8 + 1024 <= S_AUX, "pre-pass");
struct Ctl {
    __align__(128) unsigned long long sides[2];
    __align__(128) unsigned pagebits;
    __align__(128) unsigned pieces_done;
    __align__(128) unsigned late_done;
    __align__(128) unsigned fin;
    unsigned bad;
    __align__(128) unsigned bar[2];
    unsigned exited;
    __align__(128) float stat[NPC][8];
};

struct Prm {
    const uint2* m; const int* idx_in; const int* idx_out; const __nv_bfloat16* dist; const __nv_bfloat16* angle;
    const __nv_bfloat16* centers; const __nv_bfloat16* freq; const __nv_bfloat16* w_rbf; const __nv_bfloat16* w_sbf;
    const __nv_bfloat16* w_down; const __nv_bfloat16* w_up; uint2* out;
    cudaTextureObject_t t_in, t_out, t_ang;
    int E, T;
    unsigned char* ring;
    int NS, NT;
    float inv_e, kdeg;
    int force_bad;
};

__device__ __align__(128) unsigned char g_ring[RING_BYTES + (2 << 20)];
__device__ Ctl g_ctl;
constexpr int LATE_N = 64;
__device__ uint4 g_late_n[NP][16];
__device__ uint4 g_late[NO][NP][LATE_N][2];
__device__ float4 g_acc[MAX_E];
__device__ __align__(128) uint32_t g_md[2][NI * ROWS_I];
#define TS(k)
#define PROF_DECL
#define PROF(k)
#define PROF_END

extern __shared__ __align__(128) unsigned char smem[];

__device__ __forceinline__ float bf_lo(uint32_t w) { return __uint_as_float(w << 16); }
__device__ __forceinline__ float bf_hi(uint32_t w) { return __uint_as_float(w & 0xffff0000u); }
__device__ __forceinline__ float rbf16(float x) { return __bfloat162float(__float2bfloat16_rn(x)); }
__device__ __forceinline__ uint32_t pack_bf16(float hi, float lo) {
    uint32_t r; asm("cvt.rn.bf16x2.f32 %0, %1, %2;" : "=r"(r) : "f"(hi), "f"(lo)); return r;
}
__device__ __forceinline__ uint32_t prmt(uint32_t a, uint32_t b, uint32_t c) {
    uint32_t r; asm("prmt.b32 %0, %1, %2, %3;" : "=r"(r) : "r"(a), "r"(b), "r"(c)); return r;
}
__device__ __forceinline__ uint32_t ld_relaxed(const void* p) {
    uint32_t v; asm volatile("ld.relaxed.gpu.global.u32 %0, [%1];" : "=r"(v) : "l"(p) : "memory"); return v;
}
__device__ __forceinline__ uint2 ld_relaxed2(const void* p) {
    uint2 v; asm volatile("ld.relaxed.gpu.global.v2.u32 {%0,%1}, [%2];" : "=r"(v.x), "=r"(v.y) : "l"(p) : "memory"); return v;
}
__device__ __forceinline__ uint2 ld_relaxed64(const void* p) {
    uint2 v; asm volatile("{.reg .b64 t; ld.relaxed.gpu.global.b64 t, [%2]; mov.b64 {%0,%1}, t;}" : "=r"(v.x), "=r"(v.y) : "l"(p) : "memory"); return v;
}
__device__ __forceinline__ uint4 ld_relaxed4(const void* p) {
    uint4 v; asm volatile("ld.relaxed.gpu.global.v4.u32 {%0,%1,%2,%3}, [%4];" : "=r"(v.x), "=r"(v.y), "=r"(v.z), "=r"(v.w) : "l"(p) : "memory"); return v;
}
__device__ __forceinline__ void st_relaxed(void* p, uint32_t v) { asm volatile("st.relaxed.gpu.global.u32 [%0], %1;" ::"l"(p), "r"(v) : "memory"); }
__device__ __forceinline__ void st_relaxed16(void* p, uint32_t v) { asm volatile("st.relaxed.gpu.global.u16 [%0], %1;" ::"l"(p), "h"((uint16_t)v) : "memory"); }
__device__ __forceinline__ void st_relaxed64(void* p, unsigned long long v) { asm volatile("st.relaxed.gpu.global.b64 [%0], %1;" ::"l"(p), "l"(v) : "memory"); }
__device__ __forceinline__ void red_add(void* p, uint32_t v) { asm volatile("red.relaxed.gpu.global.add.u32 [%0], %1;" ::"l"(p), "r"(v) : "memory"); }
__device__ __forceinline__ void fence_gpu() { asm volatile("fence.acq_rel.gpu;" ::: "memory"); }
__device__ __forceinline__ void fence_acquire() { asm volatile("fence.acquire.gpu;" ::: "memory"); }
__device__ __forceinline__ void fence_release() { asm volatile("fence.release.gpu;" ::: "memory"); }
__device__ __forceinline__ void mbar_init(uint32_t a, uint32_t n) { asm volatile("mbarrier.init.shared.b64 [%0], %1;" ::"r"(a), "r"(n) : "memory"); }
__device__ __forceinline__ void mbar_arrive(uint32_t a) { asm volatile("mbarrier.arrive.shared.b64 _, [%0];" ::"r"(a) : "memory"); }
__device__ __forceinline__ bool mbar_try(uint32_t a, uint32_t ph) {
    uint32_t ok;
    asm volatile("{.reg .pred p; mbarrier.try_wait.parity.shared.b64 p, [%1], %2, %3; selp.u32 %0, 1, 0, p;}" : "=r"(ok) : "r"(a), "r"(ph), "r"(2000) : "memory");
    return ok;
}
__device__ __forceinline__ bool mbar_test(uint32_t a, uint32_t ph) {
    uint32_t ok;
    asm volatile("{.reg .pred p; mbarrier.test_wait.parity.shared.b64 p, [%1], %2; selp.u32 %0, 1, 0, p;}" : "=r"(ok) : "r"(a), "r"(ph) : "memory");
    return ok;
}
constexpr int SPIN_MAX = 1 << 22;
__device__ __forceinline__ void mbar_wait(uint32_t a, uint32_t ph) {
    int it = 0;
    while (!mbar_try(a, ph)) { if (++it > SPIN_MAX) __trap(); }
}
__device__ __forceinline__ void backoff(int& it) { __nanosleep(SLEEP_); if (++it > SPIN_MAX) __trap(); }
__device__ __forceinline__ void wait_ge(const void* p, uint32_t v) {
    int it = 0;
    while (ld_relaxed(p) < v) backoff(it);
}

#define RARE(x) __builtin_expect(!!(x), 0)
#define HOT __device__ __noinline__
__device__ __forceinline__ uint32_t uni(uint32_t x) { return __reduce_or_sync(0xffffffffu, x); }
__device__ __forceinline__ unsigned char* uni_ptr(unsigned char* p) { return (unsigned char*)(((uintptr_t)uni((uintptr_t)p >> 32) << 32) | uni((uint32_t)(uintptr_t)p)); }
__device__ __forceinline__ bool elect_one() {
    uint32_t r; asm volatile("{.reg .pred p; elect.sync _|p, 0xffffffff; selp.u32 %0, 1, 0, p;}" : "=r"(r)); return r;
}
__device__ __forceinline__ void st_lane0(void* p, uint32_t v, int lane) {
    asm volatile("{.reg .pred p; setp.eq.s32 p, %2, 0; @p st.relaxed.gpu.global.u32 [%0], %1;}" ::"l"(p), "r"(v), "r"(lane) : "memory");
}
__device__ __forceinline__ void wait_all_ge(const void* p, uint32_t v) {
    int it = 0;
    while (!__all_sync(0xffffffffu, ld_relaxed(p) >= v)) backoff(it);
}

constexpr uint32_t R_V1 = 0x03000, R_A = 0x81000, R_B = 0x82000, R_UNIT = 0x4000, R_HI = 0x40000 - 8 * 256;
__device__ __forceinline__ uint32_t q_base(uint32_t q, uint32_t pagebits_x) { return (q << 20) | (((pagebits_x >> (q >> 1)) & 1u) << 12); }
__device__ __forceinline__ uint32_t slot_off(uint32_t s) { return (s << 16) | (((s + 1) & 2) << 11); }
constexpr uint32_t OFF_PF = R_B + 3 * R_UNIT, OFF_RDY = OFF_PF + 128, OFF_REL = OFF_PF + 256;
constexpr uint32_t OFF_PROBE = 3 * R_UNIT;
static_assert(RA <= 4 && RV <= 4 && RB <= 8 && RA <= RB && RV <= RB, "ring");

__device__ __forceinline__ uint32_t probe(unsigned char* p) {
    volatile uint32_t* sink = (volatile uint32_t*)(smem + S_MISC + 240);
    asm volatile("st.global.v4.u32 [%0], {%1,%1,%1,%1};" ::"l"(p), "r"(0) : "memory");
    asm volatile("st.global.v4.u32 [%0], {%1,%1,%1,%1};" ::"l"(p + 16), "r"(0) : "memory");
    uint32_t best = 0xffffffffu;
#pragma unroll 1
    for (int r = 0; r < 3; r++) {
        uint32_t t0, t1, v;
        asm volatile("mov.u32 %0, %%clock;" : "=r"(t0)::"memory");
        asm volatile("atom.relaxed.gpu.global.add.u32 %0, [%1], 1;" : "=r"(v) : "l"(p) : "memory");
        *sink = v;
        asm volatile("mov.u32 %0, %%clock;" : "=r"(t1)::"memory");
        best = min(best, t1 - t0);
    }
    return best;
}

struct Wts { float c[8], wr[32], ws[32], wd[16], wu[16]; };
__device__ __forceinline__ void load_wts(const Prm& p, Wts* w) {
    int t = threadIdx.x;
    if (t < 8) w->c[t] = __bfloat162float(p.centers[t]);
    if (t < 32) { w->wr[t] = __bfloat162float(p.w_rbf[t]); w->ws[t] = __bfloat162float(p.w_sbf[t]); }
    if (t < 16) { w->wd[t] = __bfloat162float(p.w_down[t]); w->wu[t] = __bfloat162float(p.w_up[t]); }
}
__device__ __forceinline__ void radial(const Wts* w, float d, float s[4], float g[4]) {
#pragma unroll
    for (int j = 0; j < 4; j++) s[j] = g[j] = 0.f;
#pragma unroll
    for (int r = 0; r < 8; r++) {
        float x = rbf16(d - w->c[r]);
        float b = rbf16(__expf(rbf16(-10.0f * rbf16(x * x))));
#pragma unroll
        for (int j = 0; j < 4; j++) { s[j] += b * w->ws[r * 4 + j]; g[j] += b * w->wr[r * 4 + j]; }
    }
}
__device__ __noinline__ uint4 radial_bf16(const Wts* w, uint32_t dbits) {
    float s[4], g[4];
    radial(w, __uint_as_float(dbits << 16), s, g);
    return make_uint4(pack_bf16(s[1], s[0]), pack_bf16(s[3], s[2]), pack_bf16(g[1], g[0]), pack_bf16(g[3], g[2]));
}
__device__ __forceinline__ uint2 finish_row(const float* wu, const float agg[4], const float g[4], uint2 r) {
    float o[4];
    const float mm[4] = {bf_lo(r.x), bf_hi(r.x), bf_lo(r.y), bf_hi(r.y)};
#pragma unroll
    for (int j = 0; j < 4; j++) o[j] = mm[j] + (agg[0] * wu[j] + agg[1] * wu[4 + j] + agg[2] * wu[8 + j] + agg[3] * wu[12 + j]) * g[j];
    return make_uint2(pack_bf16(o[1], o[0]), pack_bf16(o[3], o[2]));
}
__device__ __forceinline__ uint2 down_row(const float* wd, uint32_t x, uint32_t y) {
    const float a[4] = {bf_lo(x), bf_hi(x), bf_lo(y), bf_hi(y)};
    float d[4];
#pragma unroll
    for (int j = 0; j < 4; j++) d[j] = a[0] * wd[j] + a[1] * wd[4 + j] + a[2] * wd[8 + j] + a[3] * wd[12 + j];
    return make_uint2(pack_bf16(d[1], d[0]), pack_bf16(d[3], d[2]));
}

__device__ __forceinline__ void down_load(const Prm& p, int pc) {
    const int r0 = pc * PC_ROWS / 2, nr = max(min((pc + 1) * PC_ROWS, p.E) / 2 - r0, 0);
    const uint32_t bar = SB + S_MISC + 248;
    mbar_init(bar, 1);
    asm volatile("fence.proxy.async.shared::cta;" ::: "memory");
    asm volatile("mbarrier.arrive.expect_tx.shared.b64 _, [%0], %1;" ::"r"(bar), "r"(nr * 16) : "memory");
    for (int o = 0; o < nr; o += 640)
        asm volatile("cp.async.bulk.shared::cluster.global.mbarrier::complete_tx::bytes [%0], [%1], %2, [%3];"
                     ::"r"(SB + S_PC + o * 16), "l"((const uint4*)p.m + r0 + o), "r"(min(640, nr - o) * 16), "r"(bar) : "memory");
}
__device__ __forceinline__ void down_piece(const Prm& p, int pc, const float* wd) {
    const int tid = threadIdx.x, lane = tid & 31, w = __shfl_sync(0xffffffffu, tid >> 5, 0);
    const int r0 = pc * PC_ROWS / 2, nr = max(min((pc + 1) * PC_ROWS, p.E) / 2 - r0, 0);
    TS(0);
    mbar_wait(SB + S_MISC + 248, 0);
    TS(1);
    uint32_t mx0 = 0, mx1 = 0; float ss[4] = {0.f, 0.f, 0.f, 0.f};
    for (int r = tid; r < nr; r += THREADS) {
        const uint4 v = ((const uint4*)(smem + S_PC))[r];
        const uint2 a = down_row(wd, v.x, v.y), b = down_row(wd, v.z, v.w);
        ((uint2*)g_md[0])[r0 + r] = make_uint2(a.x, b.x); ((uint2*)g_md[1])[r0 + r] = make_uint2(a.y, b.y);
        mx0 = __vimax3_u16x2(mx0, a.x & 0x7fff7fffu, b.x & 0x7fff7fffu); mx1 = __vimax3_u16x2(mx1, a.y & 0x7fff7fffu, b.y & 0x7fff7fffu);
        ss[0] += bf_lo(a.x) * bf_lo(a.x) + bf_lo(b.x) * bf_lo(b.x); ss[1] += bf_hi(a.x) * bf_hi(a.x) + bf_hi(b.x) * bf_hi(b.x);
        ss[2] += bf_lo(a.y) * bf_lo(a.y) + bf_lo(b.y) * bf_lo(b.y); ss[3] += bf_hi(a.y) * bf_hi(a.y) + bf_hi(b.y) * bf_hi(b.y);
    }
    TS(2);
    uint32_t st[4] = {mx0 << 16, mx0 & 0xffff0000u, mx1 << 16, mx1 & 0xffff0000u};
    uint4* red = (uint4*)(smem + S_PC + PC_ROWS * 8);
    for (int pass = 0; pass < 2; pass++) {
#pragma unroll
        for (int ch = 0; ch < 4; ch++) {
            st[ch] = __reduce_max_sync(0xffffffffu, st[ch]);
#pragma unroll
            for (int o = 16; o; o >>= 1) ss[ch] += __shfl_xor_sync(0xffffffffu, ss[ch], o);
        }
        uint4* dst = pass ? (uint4*)g_ctl.stat[pc] : red + 2 * w;
        if (lane == 0) { dst[0] = make_uint4(st[0], st[1], st[2], st[3]); dst[1] = make_uint4(__float_as_uint(ss[0]), __float_as_uint(ss[1]), __float_as_uint(ss[2]), __float_as_uint(ss[3])); }
        if (pass) break;
        __syncthreads();
        if (w != NW - 1) return;
        const uint4 a = lane < NW ? red[2 * lane] : make_uint4(0, 0, 0, 0), b = lane < NW ? red[2 * lane + 1] : make_uint4(0, 0, 0, 0);
        st[0] = a.x; st[1] = a.y; st[2] = a.z; st[3] = a.w;
        ss[0] = __uint_as_float(b.x); ss[1] = __uint_as_float(b.y); ss[2] = __uint_as_float(b.z); ss[3] = __uint_as_float(b.w);
    }
    TS(3);
}

#define MGRP 2
#define MPRED 1
#define MFPF 0
#define EB_ 4
#define KAPPA 3.3f
template <class F> __device__ __forceinline__ void get_scales(const Prm& p, float sc[4], bool& bad, F after_loads) {
    const int lane = threadIdx.x & 31;
    constexpr int NL = (NPC + 31) / 32;
    uint4 a[NL], b[NL];
#pragma unroll
    for (int k = 0; k < NL; k++) { const int pc = min(lane + 32 * k, NPC - 1); a[k] = ld_relaxed4(&g_ctl.stat[pc][0]); b[k] = ld_relaxed4(&g_ctl.stat[pc][4]); }
    after_loads();
    uint32_t mxb[4] = {0, 0, 0, 0};
    float ss[4] = {0.f, 0.f, 0.f, 0.f};
#pragma unroll
    for (int k = 0; k < NL; k++) {
        mxb[0] = max(mxb[0], a[k].x); mxb[1] = max(mxb[1], a[k].y); mxb[2] = max(mxb[2], a[k].z); mxb[3] = max(mxb[3], a[k].w);
        if (lane + 32 * k < NPC) { ss[0] += __uint_as_float(b[k].x); ss[1] += __uint_as_float(b[k].y); ss[2] += __uint_as_float(b[k].z); ss[3] += __uint_as_float(b[k].w); }
    }
    bad = false;
#pragma unroll
    for (int o = 16; o; o >>= 1) {
#pragma unroll
        for (int ch = 0; ch < 4; ch++) ss[ch] += __shfl_xor_sync(0xffffffffu, ss[ch], o);
    }
#pragma unroll
    for (int ch = 0; ch < 4; ch++) {
        const float mx = __uint_as_float(__reduce_max_sync(0xffffffffu, mxb[ch]));
        float rms;
        asm("sqrt.approx.f32 %0, %1;" : "=f"(rms) : "f"(ss[ch] * p.inv_e));
        const float range = fmaxf(2.001f * mx, p.kdeg * rms);
        if (!(mx <= 1e15f) || !(range <= 128.f * rms) || (mx > 0.f && mx < 1e-15f)) bad = true;
        sc[ch] = range > 0.f ? __uint_as_float(((__float_as_uint(range) + 0x7fffffu) & 0x7f800000u) - (15u << 23)) : 1.f;
    }
    if (bad) sc[0] = sc[1] = sc[2] = sc[3] = 1.f;
}

__device__ __forceinline__ float magic_lo(float step_lo) { return 12582912.f * step_lo; }
__device__ __forceinline__ float magic_hi(float step_lo, float step_hi) { return (float)(12582912 - (int)(__float_as_uint(magic_lo(step_lo)) >> 16)) * step_hi; }
__device__ __forceinline__ uint32_t term(uint32_t m, float c, float mag_lo, float mag_hi) {
    return (__float_as_uint(fmaf(bf_hi(m), c, mag_hi)) << 16) + __float_as_uint(fmaf(bf_lo(m), c, mag_lo));
}

constexpr int PER = 1024;
__host__ __device__ constexpr uint32_t bar_done(uint32_t s) { return SB + P_BAR + (s % NBUF) * 16; }
__host__ __device__ constexpr uint32_t bar_free(uint32_t m) { return bar_done(m + NBUF - (GR - 1)) + 8; }
struct __align__(16) PTab { uint32_t e[PER][4]; };
constexpr PTab make_ptab() {
    PTab t = {};
    for (int s = 0; s < PER; s++) {
        for (int d = 0; d < GR; d++) {
            int gi = (s + d) % GR, buf = (s + d) % NBUF, X = gi & 1, g = gi >> 1;
            t.e[s][X] |= (uint32_t)(4 * UN * buf - g - 4 * X + 7) << (8 * g);
        }
        t.e[s][2] = bar_done(s);
        t.e[s][3] = (((s + GR - 1) / NBUF) & 1) ^ 1;
    }
    return t;
}
__constant__ PTab c_ptab = make_ptab();
constexpr int BIAS = 7 * NCP;
static_assert(PER / 2 / RB < 255 && NG == 4 && CPS >= FW, "group selection");

struct PCtx { uint32_t a0, a1; };
struct PElem { uint32_t b4, aw, ol, r2; };

__device__ __forceinline__ void p_bin(const PCtx& c, PElem& e, uint32_t i, uint32_t o) {
    uint32_t ib = __umulhi(i, MAG_I), ob = __umulhi(o, MAG_O), sel = ib & 3;
    asm("{.reg .pred p; setp.ge.u32 p, %1, %2; @p add.u32 %0, %0, 4;}" : "+r"(sel) : "r"(o), "n"(HALF_O));
    e.b4 = __dp4a(prmt(c.a0, c.a1, sel), (uint32_t)NCP, ib * NCP + ob * 4);
    e.aw = i - ib * ROWS_I;
    e.ol = o - ob * ROWS_O;
}
__device__ __forceinline__ void p_rank(PElem& e) {
    asm volatile("atom.shared.add.u32 %0, [%1+%2], 2;" : "=r"(e.r2) : "r"(e.b4), "n"(SB + P_CNT - BIAS) : "memory");
}
__device__ __forceinline__ void p_store(const PElem& e) {
    const uint32_t ab = e.b4 * (KS / 2) + e.r2;
    asm volatile("{.reg .pred p; setp.lt.u32 p, %4, %5; @p st.shared.u32 [%0+%6], %1; @p st.shared.u16 [%2+%7], %3;}"
                 ::"r"(ab * 2), "r"(e.aw), "r"(ab), "h"((uint16_t)e.ol), "r"(e.r2), "n"(KS * 2),
                   "n"(SB + P_A - BIAS * KS), "n"(SB + P_B - BIAS * (KS / 2)) : "memory");
}
__device__ __forceinline__ uint32_t cos2(uint32_t x) {
    x = __vminu2(x, 0x42804280u);
    return pack_bf16(__cosf(bf_hi(x)), __cosf(bf_lo(x)));
}

#define CB_ 8
constexpr int CB = CB_;
struct PIn { uint4 i, o; uint2 a; };

struct PFill {
    PCtx c;
    uint32_t qb, qt, lt, f2, bar, par, xmax;
    uint32_t s0, lane, vb;
    unsigned long long t_in, t_out, t_ang;
    bool open;
    __device__ __forceinline__ void fetch(PIn& x, uint32_t ch) {
        const int v = ((ch & ~(CB - 1u)) * (NP - 1) + ch) * 32 + vb;
        asm volatile("{.reg .b32 d0, d1; tex.1d.v4.u32.s32 {%0,%1,d0,d1}, [%2, {%3}];}" : "=r"(x.a.x), "=r"(x.a.y) : "l"(t_ang), "r"(v));
        asm volatile("tex.1d.v4.u32.s32 {%0,%1,%2,%3}, [%4, {%5}];" : "=r"(x.i.x), "=r"(x.i.y), "=r"(x.i.z), "=r"(x.i.w) : "l"(t_in), "r"(v));
        asm volatile("tex.1d.v4.u32.s32 {%0,%1,%2,%3}, [%4, {%5}];" : "=r"(x.o.x), "=r"(x.o.y), "=r"(x.o.z), "=r"(x.o.w) : "l"(t_out), "r"(v));
    }
    __device__ __forceinline__ uint32_t ticket(uint32_t zero) {
        uint32_t t;
        asm volatile("atom.shared.add.u32 %0, [%1+%2], %3;" : "=r"(t) : "r"(lane * 4), "n"(SB + P_TKT), "r"((~lt & 1) | zero) : "memory");
        return t;
    }
    __device__ __forceinline__ uint32_t use_ticket(uint32_t t) {
        t = __reduce_or_sync(0xffffffffu, t);
        begin(t / CPS);
        return t + 2 * FW;
    }
    __device__ __forceinline__ void begin(uint32_t step) {
        const uint4 t = ((const uint4*)c_ptab.e)[step + s0];
        c.a0 = t.x; c.a1 = t.y; bar = t.z; par = t.w;
        open = mbar_test(bar + 8, par);
    }
    __device__ __forceinline__ void enter() { if (RARE(!open)) mbar_wait(bar + 8, par); }
    __device__ __forceinline__ void end() {
        __syncwarp();
        asm volatile("{.reg .pred p; setp.eq.u32 p, %1, 0; @p mbarrier.arrive.shared.b64 _, [%0];}" ::"r"(bar), "r"(lt) : "memory");
    }
    __device__ __forceinline__ void push(bool f, uint32_t x, uint32_t y) {
        const uint32_t mask = __ballot_sync(0xffffffffu, f);
        asm volatile("{.reg .pred p; setp.ne.u32 p, %3, 0; @p st.shared.v2.u32 [%0], {%1,%2};}"
                     ::"r"(min(qt + __popc(mask & lt) * 8, qb + (QN - 1) * 8)), "r"(x), "r"(y), "r"((uint32_t)f) : "memory");
        qt += __popc(mask) * 8;
    }
    __device__ __forceinline__ void push3(bool f, uint32_t i, uint32_t o, uint32_t aw) { push(f, prmt(i, aw, 0x6210), prmt(o, aw, 0x7210)); }
    __device__ __forceinline__ uint32_t chunk(const PIn& x) {
        uint32_t x0, x1;
        uint32_t tk = ticket(x.o.x >> 31);
        asm("mul.rn.bf16x2 %0, %1, %2;" : "=r"(x0) : "r"(x.a.x), "r"(f2));
        asm("mul.rn.bf16x2 %0, %1, %2;" : "=r"(x1) : "r"(x.a.y), "r"(f2));
        x0 &= 0x7fff7fffu; x1 &= 0x7fff7fffu;
        xmax = __vimax3_u16x2(xmax, x0, x1);
        const uint32_t c0 = cos2(x0), c1 = cos2(x1);
        tk = use_ticket(tk);
        PElem e0, e1, e2, e3;
        p_bin(c, e0, x.i.x, x.o.x); p_bin(c, e1, x.i.y, x.o.y); p_bin(c, e2, x.i.z, x.o.z); p_bin(c, e3, x.i.w, x.o.w);
        e0.aw = prmt(e0.aw, c0, 0x5410); e1.aw = prmt(e1.aw, c0, 0x7610); e2.aw = prmt(e2.aw, c1, 0x5410); e3.aw = prmt(e3.aw, c1, 0x7610);
        asm volatile("" : "+r"(e0.b4), "+r"(e1.b4), "+r"(e2.b4), "+r"(e3.b4), "+r"(e0.aw), "+r"(e1.aw), "+r"(e2.aw), "+r"(e3.aw));
        enter();
        p_rank(e0); p_rank(e1); p_rank(e2); p_rank(e3);
        p_store(e0); p_store(e1); p_store(e2); p_store(e3);
        if (RARE(qt - qb >= QTRIG * 8)) retry(32);
        end();
        const uint32_t r01 = e0.r2 | e1.r2, r23 = e2.r2 | e3.r2;
        const bool f = (r01 | r23) >= KS * 2;
        if (__any_sync(0xffffffffu, f)) {
            const bool f0 = e0.r2 >= KS * 2, f1 = e1.r2 >= KS * 2, f2_ = e2.r2 >= KS * 2, f3 = e3.r2 >= KS * 2, f01 = r01 >= KS * 2;
            push3(f, f01 ? (f0 ? x.i.x : x.i.y) : (f2_ ? x.i.z : x.i.w), f01 ? (f0 ? x.o.x : x.o.y) : (f2_ ? x.o.z : x.o.w),
                  f01 ? (f0 ? e0.aw : e1.aw) : (f2_ ? e2.aw : e3.aw));
            const uint32_t s2 = max(max(min(e0.r2, e1.r2), min(e2.r2, e3.r2)), min(r01, r23));
            if (RARE(__any_sync(0xffffffffu, s2 >= KS * 2))) {
                push3(f1 && f0, x.i.y, x.o.y, e1.aw); push3(f2_ && f01, x.i.z, x.o.z, e2.aw); push3(f3 && (f01 || f2_), x.i.w, x.o.w, e3.aw);
            }
        }
        return tk;
    }
    __device__ __forceinline__ void retry(uint32_t take) {
        if (qt - qb > QN * 8) { st_relaxed(&g_ctl.bad, 1); qt = qb + QN * 8; }
        uint2 e, r, r1;
        __syncwarp();
        asm volatile("ld.shared.v2.u32 {%0,%1}, [%2];" : "=r"(e.x), "=r"(e.y) : "r"(qb + lane * 8) : "memory");
        asm volatile("ld.shared.v2.u32 {%0,%1}, [%2];" : "=r"(r.x), "=r"(r.y) : "r"(qb + (lane + take) * 8) : "memory");
        qt -= take * 8;
        const bool more = qt - qb > 256;
        if (more) asm volatile("ld.shared.v2.u32 {%0,%1}, [%2];" : "=r"(r1.x), "=r"(r1.y) : "r"(qb + (lane + take) * 8 + 256) : "memory");
        __syncwarp();
        if (more && qb + lane * 8 + 256 < qt) asm volatile("st.shared.v2.u32 [%0], {%1,%2};" ::"r"(qb + lane * 8 + 256), "r"(r1.x), "r"(r1.y) : "memory");
        if (qb + lane * 8 < qt) asm volatile("st.shared.v2.u32 [%0], {%1,%2};" ::"r"(qb + lane * 8), "r"(r.x), "r"(r.y) : "memory");
        PElem el;
        el.r2 = 0;
        if (take == 32 || lane < take) {
            p_bin(c, el, e.x & 0xffffffu, e.y & 0xffffffu);
            el.aw = prmt(el.aw, prmt(e.x, e.y, 0x0073), 0x5410);
            p_rank(el);
            p_store(el);
        }
        push(el.r2 >= KS * 2, e.x, e.y);
    }
};

struct PArg { const int* idx_in; const int* idx_out; const __nv_bfloat16* angle; const __nv_bfloat16* freq; int T, NS; };
__device__ __forceinline__ void p_setup(PFill& F, const __nv_bfloat16* freq, int q, int w) {
    const int lane = threadIdx.x & 31;
    F.lt = __shfl_sync(0xffffffffu, (1u << lane) - 1u, lane);
    F.lane = __shfl_sync(0xffffffffu, lane, lane);
    F.f2 = uni(__bfloat16_as_ushort(freq[0]) * 0x10001u);
    F.qb = F.qt = SB + P_Q + w * (QN * 8);
    F.s0 = q % GR; F.xmax = 0;
}
HOT uint3 p_stream(const Prm& p, int q_) {
    PFill F;
    const int w = uni(threadIdx.x >> 5), q = uni(q_);
    p_setup(F, p.freq, q, w);
    F.vb = __shfl_sync(0xffffffffu, q * (32 * CB) + F.lane, F.lane);
    F.t_in = (uintptr_t)uni_ptr((unsigned char*)p.t_in); F.t_out = (uintptr_t)uni_ptr((unsigned char*)p.t_out); F.t_ang = (uintptr_t)uni_ptr((unsigned char*)p.t_ang);
    const uint32_t cend = uni(p.T >> 7), nv = uni(p.NS * CPS), nc = cend / (NP * CB) * CB + min(max((int)(cend % (NP * CB)) - q * CB, 0), CB);
    uint32_t c0 = w, c1 = w + FW;
    PIn x0, x1;
    F.fetch(x0, c0);
#pragma unroll 1
    while (c0 < nc) {
        F.fetch(x1, c1);
        c0 = F.chunk(x0);
        if (c1 >= nc) break;
        F.fetch(x0, c0);
        c1 = F.chunk(x1);
    }
    return make_uint3(F.qt, F.xmax, (c0 < nv) + (c1 < nv));
}
__device__ __noinline__ void p_finish(const PArg p, uint3 st) {
    PFill F;
    const int lane = threadIdx.x & 31, w = uni(threadIdx.x >> 5), q = uni(((volatile uint32_t*)(smem + S_MISC))[9]);
    static_assert(QN <= 96, "retry moves two batches");
    p_setup(F, p.freq, q, w);
    F.qt = uni(st.x); F.xmax = st.y;
    const uint32_t NS = p.NS, cend = p.T >> 7, nv = NS * CPS;
    int left = uni(st.z);
#pragma unroll 1
    while (left > 0) { left -= F.use_ticket(F.ticket(0)) >= nv; F.enter(); F.end(); }
    if (q == 0 && w < 8) {
        const int t = cend * 128 + w * 16 + lane;
        const bool f = t < p.T && lane < 16;
        uint32_t i = 0, o = 0, x = 0;
        if (f) { i = p.idx_in[t]; o = p.idx_out[t]; asm("mul.rn.bf16x2 %0, %1, %2;" : "=r"(x) : "r"(__bfloat16_as_ushort(p.angle[t]) * 0x10001u), "r"(F.f2)); }
        F.xmax = __vmaxu2(F.xmax, x & 0x7fff7fffu);
        if (F.qt - F.qb >= 32 * 8) { F.begin(NS); F.enter(); F.retry(32); }
        F.push3(f, i, o, cos2(x & 0x7fff7fffu));
    }
    F.begin(NS); F.enter();
    for (uint32_t nq = min((F.qt - F.qb) >> 3, (uint32_t)QN); nq > 0;) { uint32_t take = min(nq, 32u); F.retry(take); nq -= take; }
    F.end();
    if (CPS > FW && w < CPS - FW) F.end();
    if ((F.xmax + 0x3d803d80u) & 0x80008000u) st_relaxed(&g_ctl.bad, 1);
    uint32_t* late = (uint32_t*)(smem + P_LATE);
    const float* sc = (const float*)(smem + S_MISC);
    mbar_wait(SB + S_MISC + 232, 0);
    __syncwarp();
    for (uint32_t a = F.qb + lane * 8; a < F.qt; a += 256) {
        uint2 e;
        asm volatile("ld.shared.v2.u32 {%0,%1}, [%2];" : "=r"(e.x), "=r"(e.y) : "r"(a) : "memory");
        const uint32_t i = e.x & 0xffffffu, o = e.y & 0xffffffu, ob = __umulhi(o, MAG_O);
        const float c = __uint_as_float(prmt(e.x, e.y, 0x7300) & 0xffff0000u);
        const uint32_t m0 = ld_relaxed(&g_md[0][i]), m1 = ld_relaxed(&g_md[1][i]);
        const uint32_t k = atomicAdd(&late[ob], 1);
        if (k < LATE_N) g_late[ob][q][k][0] = g_late[ob][q][k][1] = make_uint4(o - ob * ROWS_O, term(m0, c, magic_lo(sc[0]), magic_hi(sc[0], sc[1])), term(m1, c, magic_lo(sc[2]), magic_hi(sc[2], sc[3])), 0);
        else st_relaxed(&g_ctl.bad, 1);
    }
    asm volatile("bar.sync 2, %0;" ::"n"(FW * 32) : "memory");
    if (w == 0) {
        if (lane < 16) g_late_n[q][lane] = ((const uint4*)late)[lane];
        __syncwarp();
        if (lane == 0) { fence_release(); red_add(&g_ctl.late_done, 1); }
    }
}

template <int N> __device__ __forceinline__ void p_stamp(const uint32_t (&st)[N], uint32_t off, uint32_t bit, bool set) {
    if (set) {
#pragma unroll
        for (int j = 0; j < N; j++) asm volatile("red.shared.or.b32 [%0], %1;" ::"r"(st[j] + off), "r"(bit) : "memory");
    } else {
#pragma unroll
        for (int j = 0; j < N; j++) asm volatile("red.shared.and.b32 [%0], %1;" ::"r"(st[j] + off), "r"(~bit) : "memory");
    }
}
__device__ __forceinline__ void bulk_store(void* dst, uint32_t src, uint32_t bytes) {
    asm volatile("cp.async.bulk.global.shared::cta.bulk_group [%0], [%1], %2;" ::"l"(dst), "r"(src), "r"(bytes) : "memory");
}
HOT void p_flusher(const Prm& p, int q_) {
    const int lane = threadIdx.x & 31, f = uni(threadIdx.x >> 5) - FW, q = uni(q_);
    const uint32_t NS = uni(p.NS), NT = uni(p.NT), s0 = q % GR;
    unsigned char* const ring = uni_ptr(p.ring);
    uint32_t pagebits;
    for (int it = 0; !((pagebits = uni(ld_relaxed(&g_ctl.pagebits))) >> 31);) backoff(it);
    uint32_t sta[4], stb[2];
#pragma unroll
    for (int j = 0; j < 4; j++) {
        const int pp = min(8 * j + (lane >> 2), 26), bin = min(32 * j + lane, NB - 1);
        sta[j] = SB + P_A + pp * 512 + (lane & 3) * 160 + ((pp % 9) & 3) * 4;
        if (j < 2) stb[j] = SB + P_B + bin * 128 + ((bin % NCP) & 15) * 8;
    }
    const uint32_t pfo = OFF_PF + (lane >> 2) * 32 + (lane & 1) * 8, pfc = (lane >> 2) * NCP + (lane & 2) * 5 + (lane & 1);
    const uint32_t wto = lane < NCP ? OFF_REL + lane * 4 : OFF_RDY + (lane % 6) * 4;
    PROF_DECL
#pragma unroll 1
    for (uint32_t n = f; n < NT; n += NF) {
        const uint32_t buf = (n + s0) % NBUF, h = n >> 1, lap = h / RB;
        const uint32_t qb = q_base(q, pagebits) ^ (((n + q) & 1) * 0x101000u), bb = qb ^ slot_off(h % RB);
        if (n == 2 * NF - 1) {
            float sc[4]; bool bad;
            wait_ge(&g_ctl.pieces_done, NPC);
            fence_acquire();
            get_scales(p, sc, bad, [] {});
            if (lane == 0) { *(float4*)(smem + S_MISC) = make_float4(sc[0], sc[1], sc[2], sc[3]); mbar_arrive(SB + S_MISC + 232); }
            __syncwarp();
        }
        if (h >= RA && !DEV_FREE) {
            const uint32_t hw = lane < NCP ? h : h + RB - RA;
            wait_all_ge(ring + (qb ^ slot_off(hw % RB) ^ wto), hw / RB);
        }
        PROF(0);
#pragma unroll
        for (int d = 2; d >= 0; d--) {
            const int nl = (int)min(n, NS) - d;
            if (nl >= 0) mbar_wait(bar_done(nl + s0), ((nl + s0) / NBUF) & 1);
        }
        PROF(1);
        uint32_t* cnt = (uint32_t*)(smem + P_CNT) + buf * NB;
        {
            const uint32_t oa = buf * (NB * KS * 4), ob = buf * (NB * KS * 2);
            unsigned char* da = ring + (qb ^ slot_off(h % RA) ^ R_A);
            unsigned char* db = ring + (bb ^ R_B);
#pragma unroll
            for (int k = lane; k < NB; k += 32) if (cnt[k] == 0) *(uint32_t*)(smem + P_A + oa + k * (KS * 4)) = 0;
            __syncwarp();
            p_stamp(sta, oa, 0x40000000u, (h / RA) & 1);
            p_stamp(stb, ob, 0x8000u, lap & 1);
            __syncwarp();
            if (elect_one()) {
                asm volatile("fence.proxy.async.shared::cta;" ::: "memory");
#pragma unroll
                for (int u = 0; u < UN; u++) {
                    bulk_store(da + u * R_UNIT, SB + P_A + oa + u * (NCP * KS * 4), 8 * KS * 4);
                    bulk_store(da + u * R_UNIT + 0x40000, SB + P_A + oa + (u * NCP + 8) * (KS * 4), (NCP - 8) * KS * 4);
                }
#pragma unroll
                for (int u = 0; u < UN; u++) bulk_store(db + u * R_UNIT, SB + P_B + ob + u * (NCP * KS * 2), NCP * KS * 2);
            }
            __syncwarp();
        }
        uint32_t wm = 0;
        if (lane < 4 * UN) {
#pragma unroll
            for (int u = 0; u < 5; u++) if (u < 4 || !(lane & 2)) wm |= (min(max(cnt[pfc + 2 * u] >> 1, 1u), (uint32_t)KS) - 1) << (6 * u);
        }
        const unsigned long long wm2 = wm | (unsigned long long)(__shfl_down_sync(0xffffffffu, wm, 2) | ((lap + 1) << 24)) << 32;
        __syncwarp();
        const uint32_t c0 = n + NBUF < NT ? 0 : KS * 2;
        if (lane < NB / 2) ((uint2*)cnt)[lane] = make_uint2(c0, c0);
        PROF(3);
        asm volatile("cp.async.bulk.commit_group;" ::: "memory");
        asm volatile("cp.async.bulk.wait_group 0;" ::: "memory");
        __syncwarp();
        PROF(2);
        const bool safe = h < RB;
        if (!safe && lane < 4 * UN && !(lane & 2)) st_relaxed64(ring + (bb ^ pfo), wm2);
        if (n > 0) mbar_wait(bar_free(n - 1 + s0), ((n - 1 + s0) / NBUF) & 1);
        if (lane == 0) mbar_arrive(bar_free(buf));
        if (safe) {
            fence_release();
            if (lane < 4 * UN && !(lane & 2)) st_relaxed64(ring + (bb ^ pfo), wm2);
        }
        PROF(4);
    }
    PROF_END;
}
__device__ __forceinline__ void p_cleanup(unsigned char* ring, int q) {
    const int k = threadIdx.x / 24;
    if (k < 2 * RB) *(uint4*)(ring + ((q << 20) ^ ((k & 1) << 12) ^ slot_off(k >> 1) ^ OFF_PF) + (threadIdx.x % 24) * 16) = make_uint4(0, 0, 0, 0);
}

HOT void m_worker(unsigned char* ring_, uint32_t NT_, int X_, int id_, int dev_free) {
    const int lane = threadIdx.x & 31, w = uni(threadIdx.x >> 5), X = uni(X_), id = uni(id_), ib = id >> 1, ty = id & 1;
    const uint32_t NT = uni(NT_);
    unsigned char* const ring = uni_ptr(ring_);
    const float* scs = (const float*)(smem + S_MISC);
    const uint32_t pagebits = ((uint32_t*)scs)[4];
    const int half = lane >> 4, k4 = (lane & 15) * 4;
    const float mag_lo = magic_lo(scs[2 * ty]), mag_hi = magic_hi(scs[2 * ty], scs[2 * ty + 1]), bias = 16384.f * scs[2 * ty + 1];
    const int il = ib / NG, gi = (ib % NG) * 2 + X;
    const uint32_t a_off = R_A + il * R_UNIT + lane * 16;
    const uint32_t f_off = OFF_PF + il * 32 + half * 8, r_off = OFF_REL + (lane % NCP) * 4;
    const uint32_t j = w % (NP / GR);
    constexpr uint32_t DN = MW / (NP / GR);
#define M_QB(n) q_base(((((gi - (n)) & (GR - 1)) + GR * j) ^ X), pagebits)
    uint2 cw = make_uint2(0, 0);
    PROF_DECL
#pragma unroll 1
    for (uint32_t n = w / (NP / GR); n < NT; n += DN) {
        const uint32_t h = n >> 1, qb = M_QB(n), bb = qb ^ slot_off(h % RB);
        const uint32_t tag = (h / RB + 1) << 24;
        int it = 0;
        while (!__all_sync(0xffffffffu, cw.y >= tag)) {
            if (dev_free) { cw.x = (cw.x & 1) + (62 | 58 << 6 | 53 << 12 | 55 << 18 | 62 << 24); cw.y = (cw.y & 1) + (58 | 61 << 6 | 54 << 12 | 59 << 18); break; }
            if (it || MFPF) backoff(it); else it = 1;
            cw = ld_relaxed64(ring + (bb ^ f_off));
        }
        PROF(0);
        const unsigned char* pa = ring + (qb ^ slot_off(h % RA) ^ a_off);
        unsigned char* pv = (unsigned char*)((uintptr_t)pa ^ (slot_off(h % RA) ^ slot_off(h % RV) ^ R_A ^ (ty * R_V1)));
        const uint32_t hv = h + RB - RV;
        const unsigned char* prel = ring + (qb ^ slot_off(hv % RB) ^ r_off);
        const uint32_t rel = RV < RB ? ld_relaxed(prel) : ~0u;
        const uint32_t vlap = h / RV;
        const float mag_hi0 = fmaf(bias, (vlap & 1) ? 3.f : 1.f, mag_hi);
        const uint32_t stamp = ((h / RA) & (0x40100401u >> lane) & 1) << 30;
        uint32_t a[9][4];
        while (true) {
            uint32_t late = 0;
#pragma unroll
            for (int ps = 0; ps < 9; ps++) {
                const uint4 t = ld_relaxed4(pa + ps * 512 + (ps < 4 ? 0 : R_HI));
                a[ps][0] = t.x; a[ps][1] = t.y; a[ps][2] = t.z; a[ps][3] = t.w;
            }
#pragma unroll
            for (int ps = 0; ps < 9; ps++) late |= a[ps][ps & 3] ^= stamp;
            if (!__any_sync(0xffffffffu, (late & 0x40000000u) != 0)) break;
            if (dev_free) { for (int ps = 0; ps < 9; ps++) a[ps][ps & 3] &= 0xbfffffffu; break; }
            if (++it > SPIN_MAX) __trap();
        }
        if (RARE(!__all_sync(0xffffffffu, rel >= hv / RB) && !dev_free)) wait_all_ge(prel, hv / RB);
        PROF(3);
#pragma unroll
        for (int g = 0; g < 9; g += MGRP) {
            uint32_t mv[MGRP][4];
#pragma unroll
            for (int u = 0; u < MGRP; u++) {
                const int ps = g + u;
                if (ps >= 9) break;
                const int rem = (int)(((ps < 5 ? cw.x : cw.y) >> (6 * (ps % 5))) & 0x3f) - k4;
#pragma unroll
                for (int e = 0; e < 4; e++)
                    asm volatile("{.reg .pred p; setp.ge.s32 p, %2, %3; dp2a.lo.u32.u32 %0, %1, 4, 0; selp.b32 %0, %0, 0, p; @p ld.shared.u32 %0, [%0+%4];}"
                                 : "=&r"(mv[u][e]) : "r"(a[ps][e]), "r"(rem), "r"(e), "n"(SB));
            }
            if (g + MGRP >= 9) {
                if (MFPF) cw = ld_relaxed64(ring + (M_QB(n + DN) ^ slot_off(((n + DN) >> 1) % RB) ^ f_off));
                else cw.y = 0;
            }
#pragma unroll
            for (int u = 0; u < MGRP; u++) {
                const int ps = g + u;
                if (ps >= 9) break;
                asm volatile("st.global.v4.u32 [%0], {%1,%2,%3,%4};" ::"l"(pv + ps * 512 + (ps < 4 ? 0 : R_HI)),
                             "r"(term(mv[u][0], bf_hi(a[ps][0]), mag_lo, mag_hi0)), "r"(term(mv[u][1], bf_hi(a[ps][1]), mag_lo, mag_hi)),
                             "r"(term(mv[u][2], bf_hi(a[ps][2]), mag_lo, mag_hi)), "r"(term(mv[u][3], bf_hi(a[ps][3]), mag_lo, mag_hi)) : "memory");
            }
        }
        if (vlap == 0) fence_release();
        st_lane0(ring + (bb ^ (OFF_RDY + (2 * il + ty) * 4)), tag >> 24, lane);
        PROF(1);
    }
    PROF_END;
}

__device__ __forceinline__ void m_role(const Prm& p, unsigned char* ring, int X, int id) {
    const int tid = threadIdx.x, lane = tid & 31, w = __shfl_sync(0xffffffffu, tid >> 5, 0);
    const int ib = id >> 1, ty = id & 1;
    float* scs = (float*)(smem + S_MISC);
    if (w == 0) {
        const uint32_t bar = SB + S_AUX;
        uint32_t pb;
        if (lane == 0) { mbar_init(bar, 1); ((uint32_t*)smem)[ROWS_I] = 0; }
        asm volatile("fence.proxy.async.shared::cta;" ::: "memory");
        for (int it = 0; !((pb = ld_relaxed(&g_ctl.pagebits)) >> 31);) backoff(it);
        wait_ge(&g_ctl.pieces_done, NPC);
        TS(5);
        fence_acquire();
        float sc[4]; bool bad;
        get_scales(p, sc, bad, [&] {
            if (elect_one()) {
                asm volatile("fence.proxy.async.global;" ::: "memory");
                asm volatile("mbarrier.arrive.expect_tx.shared.b64 _, [%0], %1;" ::"r"(bar), "r"(ROWS_I * 4) : "memory");
                constexpr uint32_t PART = (ROWS_I * 4 / 8 + 127) / 128 * 128;
#pragma unroll
                for (uint32_t o = 0; o < ROWS_I * 4; o += PART)
                    asm volatile("cp.async.bulk.shared::cluster.global.mbarrier::complete_tx::bytes [%0], [%1], %2, [%3];"
                                 ::"r"(SB + o), "l"((const char*)(g_md[ty] + ib * ROWS_I) + o), "r"(min(PART, ROWS_I * 4 - o)), "r"(bar) : "memory");
            }
            __syncwarp();
        });
        if (bad) st_relaxed(&g_ctl.bad, 1);
        if (lane == 0) { scs[0] = sc[0]; scs[1] = sc[1]; scs[2] = sc[2]; scs[3] = sc[3]; ((uint32_t*)scs)[4] = X ? ~pb : pb; ((uint32_t*)scs)[5] = bad; }
        TS(6);
        mbar_wait(bar, 0);
        TS(7);
    }
    __syncthreads();
    if (((uint32_t*)scs)[5]) {
        for (int k = tid; k < (int)ROWS_I; k += THREADS) ((uint32_t*)smem)[k] = 0;
        __syncthreads();
    }
    if (w < MW) m_worker(ring, p.NT, X, id, DEV_FREE);
}

__device__ __forceinline__ void c_wrap(uint32_t ad, uint32_t old, uint32_t w) {
    const uint32_t ov = ~(old ^ w) & (old ^ (old + w)), sh = (ad & 4) * 2;
    const int d = (int)(((ov >> 15) & 1) + ((ov >> 27) & 16)) - (int)((((ov & w) >> 14) & 2) + (((ov & w) >> 26) & 32));
    uint32_t c;
    asm volatile("atom.shared.add.u32 %0, [%1+%2], %3;" : "=r"(c) : "r"((ad >> 3) * 4), "n"(SB / 2 + C_WRAP), "r"(d << sh) : "memory");
    c = (c >> sh) + d;
    asm volatile("{.reg .pred p; setp.eq.u32 p, %1, 0; @p st.relaxed.gpu.global.u32 [%0], 1;}" ::"l"(&g_ctl.bad), "r"(min((c + 1) & 0xe, (c + 16) & 0xe0)) : "memory");
}

#define CGRP 6
struct CTask { uint4 v[3]; uint2 b[3]; };
struct CWork {
    unsigned char *pv, *pb, *pf;
    uint32_t acc, lap1, sv, sb, vtag, fw, stamp;
    static __device__ __forceinline__ unsigned char* flip(unsigned char* p, uint32_t bits) { return (unsigned char*)((uintptr_t)p ^ bits); }
    static __device__ __forceinline__ uint32_t step(uint32_t s, uint32_t r) { return slot_off(s) ^ slot_off(s + 1 == r ? 0 : s + 1); }
    uint32_t last; int dev_free;
    __device__ __forceinline__ void load(CTask& t, int odd) {
#pragma unroll
        for (int ps = 0; ps < 3; ps++) { t.v[ps] = ld_relaxed4(pv + ps * R_UNIT + (odd << 20)); t.b[ps] = ld_relaxed2(pb + ps * R_UNIT + (odd << 20)); }
    }
    template <int ODD> __device__ __forceinline__ void issue(CTask& t) {
        if (RARE(!__all_sync(0xffffffffu, fw + last >= lap1))) {
            int it = 0;
            do {
                if (dev_free) break;
                backoff(it);
                fw = ld_relaxed(pf + (ODD << 20));
            } while (!__all_sync(0xffffffffu, fw + last >= lap1));
        }
        load(t, ODD);
        fw = ld_relaxed(ODD ? flip(pf, step(sb, RB)) : pf + (1 << 20));
    }
    template <int ODD> __device__ __forceinline__ void arrive(CTask& t) {
        int it = 0;
        while (true) {
#pragma unroll
            for (int ps = 0; ps < 3; ps++) { t.b[ps].x ^= stamp; t.v[ps].x ^= vtag; }
            if (!RARE(__any_sync(0xffffffffu, ((t.v[0].x | t.v[1].x | t.v[2].x) & 0x80000000u) | ((t.b[0].x | t.b[1].x | t.b[2].x) & 0x8000u)))) break;
            if (dev_free) { for (int ps = 0; ps < 3; ps++) { t.v[ps].x &= 0x7fffffffu; t.b[ps].x &= 0xffff7fffu; } break; }
            if (++it > SPIN_MAX) __trap();
            load(t, ODD);
        }
        asm volatile("{.reg .pred p; setp.ne.u32 p, %2, 0; @p st.relaxed.gpu.global.u32 [%0], %1;}" ::"l"(pf + (ODD << 20)), "r"(lap1), "r"((uint32_t)last) : "memory");
        if (ODD) {
            pv = flip(pv, step(sv, RV)); pb = flip(pb, step(sb, RB)); pf = flip(pf, step(sb, RB));
            if (++sv == RV) { sv = 0; vtag ^= 0x80000000u; }
            if (++sb == RB) { sb = 0; lap1++; stamp ^= ((((uintptr_t)pb >> 4) ^ (uintptr_t)pb) & 0x78) == 0 ? 0x8000u : 0u; }
        }
    }
    __device__ __forceinline__ void add(const CTask& t) {
        const uint32_t vw[12] = {t.v[0].x - 0x40000000u, t.v[0].y, t.v[0].z, t.v[0].w, t.v[1].x - 0x40000000u, t.v[1].y, t.v[1].z, t.v[1].w, t.v[2].x - 0x40000000u, t.v[2].y, t.v[2].z, t.v[2].w};
        const uint32_t bw[6] = {t.b[0].x, t.b[0].y, t.b[1].x, t.b[1].y, t.b[2].x, t.b[2].y};
#pragma unroll
        for (int g = 0; g < 12; g += CGRP) {
            uint32_t old[CGRP], ov = 0;
#pragma unroll
            for (int e = g; e < g + CGRP; e++)
                asm volatile("atom.shared.add.u32 %0, [%1], %2;" : "=r"(old[e - g]) : "r"((e & 1) ? __dp2a_hi(bw[e >> 1], 0x08000008u, acc) : __dp2a_lo(bw[e >> 1], 0x08000008u, acc)), "r"(vw[e]) : "memory");
#pragma unroll
            for (int e = g; e < g + CGRP; e++) ov |= ~(old[e - g] ^ vw[e]) & (old[e - g] ^ (old[e - g] + vw[e]));
            if (RARE(__any_sync(0xffffffffu, ov & 0x80008000u))) {
#pragma unroll
                for (int e = g; e < g + CGRP; e++) c_wrap((e & 1) ? __dp2a_hi(bw[e >> 1], 0x08000008u, acc) : __dp2a_lo(bw[e >> 1], 0x08000008u, acc), old[e - g], vw[e]);
            }
        }
    }
};

HOT void c_worker(unsigned char* ring, uint32_t NT_, int c, int dev_free) {
    const int lane = threadIdx.x & 31, w = threadIdx.x >> 5;
    const uint32_t NT = uni(NT_), pagebits = ((const uint32_t*)(smem + S_MISC))[4];
    CWork W;
    const int par = lane >> 4;
    W.dev_free = dev_free;
    const uint32_t qb = q_base(2 * w, pagebits), k = lane & 15;
    W.last = __shfl_sync(0xffffffffu, lane == 31, lane);
    W.acc = __shfl_sync(0xffffffffu, SB + par * 4, lane);
    W.pv = ring + (qb ^ (par * R_V1 + (c < 8 ? 0 : R_HI) + c * 256 + k * 16));
    W.pb = ring + (qb ^ (R_B + c * 128 + k * 8));
    W.pf = ring + (qb ^ (lane == 31 ? OFF_REL + c * 4 : OFF_RDY + (lane % 6) * 4));
    W.lap1 = 1; W.sv = W.sb = W.fw = W.stamp = W.vtag = 0;
    CTask A, B;
    PROF_DECL
    W.issue<0>(A);
#pragma unroll 1
    for (uint32_t n = 2;; n += 2) {
        W.arrive<0>(A); PROF(1); W.issue<1>(B); PROF(0); W.add(A);
        W.arrive<1>(B);
        if (n >= NT) break;
        PROF(1); W.issue<0>(A); PROF(0); W.add(B);
    }
    W.add(B);
    PROF_END;
}

__device__ __forceinline__ void c_role(const Prm& p, unsigned char* ring, int X, int c) {
    const int tid = threadIdx.x, lane = tid & 31, w = __shfl_sync(0xffffffffu, tid >> 5, 0);
    uint32_t* misc = (uint32_t*)(smem + S_MISC);
    Wts* wt = (Wts*)(smem + S_AUX);
    load_wts(p, wt);
    if (tid == 0) misc[6] = TAB_N;
    __syncthreads();
    if (w == 0) {
        float sc[4]; bool bad;
        wait_ge(&g_ctl.pieces_done, NPC);
        fence_acquire();
        get_scales(p, sc, bad, [] {});
        const float s = (lane & 2) ? ((lane & 1) ? sc[3] : sc[2]) : ((lane & 1) ? sc[1] : sc[0]);
        wt->ws[lane] *= s;
        int it = 0; uint32_t pb;
        while (!((pb = ld_relaxed(&g_ctl.pagebits)) >> 31)) backoff(it);
        misc[4] = X ? ~pb : pb;
    } else {
        const int r0 = (X * NCP + c) * ROWS_O, nr = min((int)ROWS_O, p.E - r0);
#pragma unroll 4
        for (int r = tid - 32; r < (int)ROWS_O / 2; r += THREADS - 32) {
            const uint32_t d2 = 2 * r < nr ? __ldg((const uint32_t*)(p.dist + r0) + r) : TAB_LO * 0x10001u;
            uint32_t e[2] = {(d2 & 0xffff) - TAB_LO, (d2 >> 16) - TAB_LO};
#pragma unroll
            for (int k = 0; k < 2; k++)
                if (e[k] >= TAB_N) {
                    const uint32_t d = e[k] + TAB_LO;
                    if ((d & 0x7f80) == 0x7f80) st_relaxed(&g_ctl.bad, 1);
                    e[k] = min(atomicAdd(&misc[6], 1u), 0xffffu);
                    if (e[k] < TAB_N + TAB_X) ((uint32_t*)(smem + C_TAB))[e[k] * 4] = d;
                }
            ((uint2*)(smem + C_WRAP))[r] = make_uint2(e[0] << 16 | 0x8888u, e[1] << 16 | 0x8888u);
        }
    }
    __syncthreads();
    if (w < NP / 2) c_worker(ring, p.NT, c, DEV_FREE);
    else {
        const int nt = min(misc[6], (uint32_t)(TAB_N + TAB_X));
        for (int k = tid - NP * 16; k < nt; k += THREADS - NP * 16)
            ((uint4*)(smem + C_TAB))[k] = radial_bf16(wt, k < TAB_N ? TAB_LO + k : ((uint32_t*)(smem + C_TAB))[k * 4]);
        if (DEV_FREE) return;
        for (int it = 0; ld_relaxed(&g_ctl.late_done) == 0; it++) { __nanosleep(1000); if (it > SPIN_MAX) __trap(); }
        const int ob = X * NCP + c, nr = min((int)ROWS_O, p.E - ob * (int)ROWS_O);
        if (tid == THREADS - 1 && nr > 0) asm volatile("cp.async.bulk.prefetch.L2.global [%0], %1;" ::"l"(p.m + ob * ROWS_O), "r"(nr * 8) : "memory");
        for (int it = 0; ld_relaxed(&g_ctl.late_done) < NP; it++) { __nanosleep(100); if (it > SPIN_MAX) __trap(); }
            fence_acquire();
        constexpr int LQ = NP / (2 * (NW - NP / 2));
        const int q0 = (tid - NP * 16) >> 4;
        uint32_t n[LQ], nmax = 0;
#pragma unroll
        for (int j = 0; j < LQ; j++) n[j] = ld_relaxed((const uint32_t*)g_late_n[q0 * LQ + j] + ob);
#pragma unroll
        for (int j = 0; j < LQ; j++) { n[j] = min(n[j], (uint32_t)LATE_N); nmax = max(nmax, n[j]); }
        nmax = __reduce_max_sync(0xffffffffu, nmax);
        for (uint32_t k = lane & 15; k < ((nmax + 15) & ~15u); k += 16) {
            uint4 e[LQ];
            uint32_t o0[LQ], o1[LQ], ov = 0;
#pragma unroll
            for (int j = 0; j < LQ; j++) { e[j] = make_uint4(lane, 0, 0, 0); if (k < n[j]) e[j] = ld_relaxed4(g_late[ob][q0 * LQ + j][k]); }
#pragma unroll
            for (int j = 0; j < LQ; j++) { o0[j] = atomicAdd((uint32_t*)smem + 2 * e[j].x, e[j].y); o1[j] = atomicAdd((uint32_t*)smem + 2 * e[j].x + 1, e[j].z); }
#pragma unroll
            for (int j = 0; j < LQ; j++) ov |= (~(o0[j] ^ e[j].y) & (o0[j] ^ (o0[j] + e[j].y))) | (~(o1[j] ^ e[j].z) & (o1[j] ^ (o1[j] + e[j].z)));
            if (ov & 0x80008000u) {
#pragma unroll
                for (int j = 0; j < LQ; j++) { c_wrap(SB + e[j].x * 8, o0[j], e[j].y); c_wrap(SB + e[j].x * 8 + 4, o1[j], e[j].z); }
            }
        }
        __syncwarp();
        }
}

struct FinArg { const uint2* m; const __nv_bfloat16* dist; uint2* out; unsigned char* ring; int E, dev_free; };
__device__ __forceinline__ uint32_t bf2_mul(uint32_t a, uint32_t b) { uint32_t r; asm("mul.rn.bf16x2 %0, %1, %2;" : "=r"(r) : "r"(a), "r"(b)); return r; }
__device__ __forceinline__ uint32_t bf2_fma(uint32_t a, uint32_t b, uint32_t c) { uint32_t r; asm("fma.rn.bf16x2 %0, %1, %2, %3;" : "=r"(r) : "r"(a), "r"(b), "r"(c)); return r; }
__device__ __forceinline__ uint32_t c_agg(uint32_t a, uint32_t s, uint32_t wr, bool wrapped) {
    int x0 = (short)a, x1 = ((int)a >> 16) + ((a >> 15) & 1);
    if (wrapped) { const int w0 = (int)(wr & 15) - 8, w1 = (int)((wr >> 4) & 15) - 8; x0 += 65536 * w0; x1 += 65536 * w1 - w0; }
    return pack_bf16((float)x1 * bf_hi(s), (float)x0 * bf_lo(s));
}
__device__ __forceinline__ void c_epilogue(const FinArg& p, int X, int c) {
    constexpr int ET = THREADS - 32;
    const int tid = threadIdx.x, lane = tid & 31;
    const Wts* wt = (const Wts*)(smem + S_AUX);
    uint32_t bw[4];
#pragma unroll
    for (int k = 0; k < 4; k++) {
        const int col = (k >> 1) * 2 + ((lane >> 2) & 1), row = (k & 1) * 2;
        bw[k] = (lane >> 3) == (lane & 3) ? pack_bf16(wt->wu[(row + 1) * 4 + col], wt->wu[row * 4 + col]) : 0u;
    }
    const int r0 = (X * NCP + c) * ROWS_O, np = max(min((int)ROWS_O, p.E - r0), 0) / 2;
    const uint4* mp = (const uint4*)(p.m + r0);
    uint4* op = (uint4*)(p.out + r0);
    constexpr int EB = EB_;
#pragma unroll 1
    for (int rb = tid; rb - lane < np; rb += EB * ET) {
        uint4 mr[EB];
#pragma unroll
        for (int k = 0; k < EB; k++) mr[k] = __ldg(mp + min(rb + k * ET, np - 1));
#pragma unroll
        for (int k = 0; k < EB; k++) {
            if (rb - lane + k * ET >= np) break;
            const int r = min(rb + k * ET, np - 1);
            const uint4 a = ((const uint4*)smem)[r];
            const uint2 wr = ((const uint2*)(smem + C_WRAP))[r];
            const uint4 t0 = ((const uint4*)(smem + C_TAB))[min(wr.x >> 16, (uint32_t)(TAB_N + TAB_X - 1))];
            const uint4 t1 = ((const uint4*)(smem + C_TAB))[min(wr.y >> 16, (uint32_t)(TAB_N + TAB_X - 1))];
            const bool wrapped = __any_sync(0xffffffffu, prmt(wr.x, wr.y, 0x5410) != 0x88888888u);
            uint32_t a0, a1, a2, a3;
            if (wrapped) { a0 = c_agg(a.x, t0.x, wr.x, true); a2 = c_agg(a.y, t0.y, wr.x >> 8, true); a1 = c_agg(a.z, t1.x, wr.y, true); a3 = c_agg(a.w, t1.y, wr.y >> 8, true); }
            else { a0 = c_agg(a.x, t0.x, 0, false); a2 = c_agg(a.y, t0.y, 0, false); a1 = c_agg(a.z, t1.x, 0, false); a3 = c_agg(a.w, t1.y, 0, false); }
            float u[8];
#pragma unroll
            for (int h = 0; h < 2; h++)
                asm("mma.sync.aligned.m16n8k16.row.col.f32.bf16.bf16.f32 {%0,%1,%2,%3}, {%4,%5,%6,%7}, {%8,%9}, {%10,%10,%10,%10};"
                    : "=f"(u[4 * h]), "=f"(u[4 * h + 1]), "=f"(u[4 * h + 2]), "=f"(u[4 * h + 3])
                    : "r"(a0), "r"(a1), "r"(a2), "r"(a3), "r"(bw[2 * h]), "r"(bw[2 * h + 1]), "f"(0.f));
            const uint4 o = make_uint4(bf2_fma(pack_bf16(u[1], u[0]), t0.z, mr[k].x), bf2_fma(pack_bf16(u[5], u[4]), t0.w, mr[k].y),
                                       bf2_fma(pack_bf16(u[3], u[2]), t1.z, mr[k].z), bf2_fma(pack_bf16(u[7], u[6]), t1.w, mr[k].w));
            if (rb + k * ET < np) op[r] = o;
        }
    }
    if (((const uint32_t*)(smem + S_MISC))[6] > TAB_N + TAB_X) {
        for (int r = 2 * tid; r < 2 * np; r += (r & 1) ? 2 * ET - 1 : 1) {
            const uint32_t wr = ((const uint32_t*)(smem + C_WRAP))[r];
            if ((wr >> 16) < TAB_N + TAB_X) continue;
            const uint4 t = radial_bf16(wt, __bfloat16_as_ushort(p.dist[r0 + r]));
            const uint2 a = ((const uint2*)smem)[r];
            const uint32_t a0 = c_agg(a.x, t.x, wr, true), a1 = c_agg(a.y, t.y, wr >> 8, true);
            const float agg[4] = {bf_lo(a0), bf_hi(a0), bf_lo(a1), bf_hi(a1)}, g[4] = {bf_lo(t.z), bf_hi(t.z), bf_lo(t.w), bf_hi(t.w)};
            p.out[r0 + r] = finish_row(wt->wu, agg, g, p.m[r0 + r]);
        }
    }
}

__device__ __forceinline__ void leave() {
    if (atomicAdd(&g_ctl.exited, 1) == gridDim.x - 1)
        for (int k = 0; k < 6; k++) ((uint4*)&g_ctl)[k * 8] = make_uint4(0, 0, 0, 0);
}
__device__ __forceinline__ void grid_bar(unsigned* ctr) {
    __syncthreads();
    if (threadIdx.x == 0) { fence_gpu(); red_add(ctr, 1); wait_ge(ctr, gridDim.x); fence_gpu(); }
    __syncthreads();
}
__device__ __noinline__ void fallback(const Prm& p) {
    const int gt = blockIdx.x * THREADS + threadIdx.x, gs = gridDim.x * THREADS;
    Wts* wt = (Wts*)smem;
    __syncthreads();
    load_wts(p, wt);
    for (int e = gt; e < p.E; e += gs) g_acc[e] = make_float4(0.f, 0.f, 0.f, 0.f);
    grid_bar(&g_ctl.bar[0]);
    const float f = __bfloat162float(p.freq[0]);
    for (int t = gt; t < p.T; t += gs) {
        uint2 r = __ldg(p.m + p.idx_in[t]);
        float c = rbf16(cosf(rbf16(f * __bfloat162float(p.angle[t]))));
        asm volatile("red.global.add.v4.f32 [%0], {%1,%2,%3,%4};" ::"l"(g_acc + p.idx_out[t]), "f"(bf_lo(r.x) * c),
                     "f"(bf_hi(r.x) * c), "f"(bf_lo(r.y) * c), "f"(bf_hi(r.y) * c) : "memory");
    }
    grid_bar(&g_ctl.bar[1]);
    if (threadIdx.x == 0) leave();
    for (int e = gt; e < p.E; e += gs) {
        float4 a4 = __ldcg(g_acc + e);
        float a[4] = {a4.x, a4.y, a4.z, a4.w}, s[4], g[4];
        radial(wt, __bfloat162float(p.dist[e]), s, g);
        float agg[4];
#pragma unroll
        for (int j = 0; j < 4; j++) agg[j] = s[j] * (a[0] * wt->wd[j] + a[1] * wt->wd[4 + j] + a[2] * wt->wd[8 + j] + a[3] * wt->wd[12 + j]);
        p.out[e] = finish_row(wt->wu, agg, g, p.m[e]);
    }
}

__device__ __noinline__ bool finish(const FinArg p) {
    volatile uint32_t* misc = (volatile uint32_t*)(smem + S_MISC);
    const int pool = misc[8], id = misc[9];
    if (uni(threadIdx.x >> 5) == NW - 1) {
        if ((threadIdx.x & 31) == 0) { fence_release(); red_add(&g_ctl.fin, 1); }
        __syncwarp();
        wait_ge(&g_ctl.fin, NCTA);
        fence_acquire();
        const uint32_t bad = ld_relaxed(&g_ctl.bad) && !DEV_FREE;
        if ((threadIdx.x & 31) == 0) { misc[10] = bad; if (!bad) leave(); }
    } else if ((pool == 2 || pool == 3) && !DEV_FREE) c_epilogue(p, pool - 2, id);
    __syncthreads();
    if (pool == 4) p_cleanup(p.ring, id);
    return misc[10];
}
__device__ __forceinline__ void smem_init(bool isp, int from, int to) {
    for (int k = from / 16 + threadIdx.x; k < to / 16; k += THREADS) {
        const bool b = isp && k >= P_B / 16 && k < P_Q / 16;
        const uint32_t z = b ? (k & 7) * 0x20002u : 0u, y = b ? z + 0x10001u : 0u;
        ((uint4*)smem)[k] = make_uint4(z, z, y, y);
    }
}

__global__ void __launch_bounds__(THREADS, 1) gemnet_kernel(const __grid_constant__ Prm p) {
    const int tid = threadIdx.x, lane = tid & 31, w = __shfl_sync(0xffffffffu, tid >> 5, 0);
    uint32_t* misc = (uint32_t*)(smem + S_MISC);
    bool run_fallback = true;
    if (!p.force_bad && __cvta_generic_to_shared(smem) == SB) {
        unsigned char* const ring = p.ring;
        uint32_t vid, nsm;
        asm("mov.u32 %0, %%smid;" : "=r"(vid)); asm("mov.u32 %0, %%nsmid;" : "=r"(nsm));
        vid = __shfl_sync(0xffffffffu, nsm != NCTA ? blockIdx.x : vid, 0);
        constexpr uint32_t NPF = NP - 4, V1 = NM + NPF, VX = NCTA - 8;
        const int grp = vid < NM ? 0 : vid < V1 ? 2 : 1;
        const uint32_t v1 = vid - V1 - (vid >= VX + 4 ? 4 : 0);
        const uint32_t pos = grp == 0 ? vid : (vid & ~3u) == VX ? NC + ((vid ^ 2) & 3) : (v1 >> 1) + (v1 & 1) * NCP;
        const int piece = grp == 2 ? NPC : grp * NM + pos;
        if (grp != 2) {
            if (lane == 0) {
                if (w < 2) misc[16 + w] = probe(ring + OFF_PROBE + w * 4096 + ((vid >> 7) << 20) + (vid & 127) * 32);
                else if (vid == VX && w <= NPAGES) misc[16 + w] = probe(ring + ((size_t)(w - 1) << 21) + OFF_PROBE);
            }
            __syncthreads();
            if (tid == 0) {
                atomicAdd(&g_ctl.sides[grp], (1ull << 56) | ((unsigned long long)(misc[16] > misc[17]) << pos));
                if (piece < NPC) down_load(p, piece);
            }
            if (vid == VX && tid == 32) {
                uint32_t pb = 0x80000000u;
                for (int k = 1; k < NPAGES; k++) pb |= (uint32_t)((2 * misc[17 + k] > misc[16] + misc[17]) != (misc[16] > misc[17])) << k;
                st_relaxed(&g_ctl.pagebits, pb);
            }
            if (w == 2) {
                const uint32_t n = grp ? NC + 4 : NM, cap = grp ? NCP : NMP;
                uint2 v; int it = 0;
                while (((v = ld_relaxed2(&g_ctl.sides[grp])).y >> 24) < n) backoff(it);
                const unsigned long long all = (1ull << n) - 1, far = (((unsigned long long)v.y << 32) | v.x) & all;
                const uint32_t side = (far >> pos) & 1, n1 = __popcll(far), no = side ? n - n1 : n1;
                uint32_t pool = grp * 2 + side, id = __popcll((side ? far : ~far) & ((1ull << pos) - 1));
                if (id >= cap) {
                    id -= cap;
                    if (no < cap && id < cap - no) { pool ^= 1; id += no; }
                    else { pool = 4; id = NPF + (no < cap ? id - (cap - no) : side ? id + (no - cap) : id); }
                }
                misc[8] = pool; misc[9] = id;
            }
        } else if (tid == 0) { misc[8] = 4; misc[9] = vid - NM; }
        if (grp != 0) smem_init(piece >= NPC, 0, S_PC);
        if (piece < NPC) {
            float wd[16];
#pragma unroll
            for (int k = 0; k < 16; k++) wd[k] = __bfloat162float(p.w_down[k]);
            __syncthreads();
            down_piece(p, piece, wd);
        }
        __syncthreads();
        const int pool = __reduce_or_sync(0xffffffffu, misc[8]), id = __reduce_or_sync(0xffffffffu, misc[9]);
        if (piece < NPC && tid == THREADS - 32) { fence_release(); red_add(&g_ctl.pieces_done, 1); }
        TS(4);
        if (DEV_FREE && !(DEV_FREE & (pool == 4 ? 1 : pool < 2 ? 2 : 4))) {
        } else if (pool == 4) {
            smem_init(true, piece < NPC ? 0 : S_PC, S_MISC);
            __syncthreads();
            if (tid < 2 * NBUF) {
                const uint32_t a = tid < NBUF ? bar_done(tid) : bar_free(tid), cnt = tid < NBUF ? CPS : 1;
                mbar_init(a, cnt);
                if (tid % NBUF < id % GR) asm volatile("mbarrier.arrive.shared.b64 _, [%0], %1;" ::"r"(a), "r"(cnt) : "memory");
            }
            if (tid == 32) mbar_init(SB + S_MISC + 232, 1);
            __syncthreads();
            if (w < FW) { const uint3 st = p_stream(p, id); p_finish(PArg{p.idx_in, p.idx_out, p.angle, p.freq, p.T, p.NS}, st); }
            else if (w < FW + NF) p_flusher(p, id);
        } else if (pool < 2) {
            m_role(p, ring, pool, id);
        } else {
            smem_init(false, 0, piece < NPC ? 0 : S_PC);
            c_role(p, ring, pool - 2, id);
        }
        __syncthreads();
        run_fallback = finish(FinArg{p.m, p.dist, p.out, p.ring, p.E, DEV_FREE});
    }
    if (run_fallback) fallback(p);
}

cudaTextureObject_t make_tex(const void* ptr, size_t bytes, int words) {
    cudaResourceDesc rd = {};
    rd.resType = cudaResourceTypeLinear;
    rd.res.linear.devPtr = (void*)ptr;
    rd.res.linear.desc = words == 4 ? cudaCreateChannelDesc<uint4>() : cudaCreateChannelDesc<uint2>();
    rd.res.linear.sizeInBytes = bytes;
    cudaTextureDesc td = {};
    td.readMode = cudaReadModeElementType;
    cudaTextureObject_t t = 0;
    if (cudaCreateTextureObject(&t, &rd, &td, nullptr) != cudaSuccess) { cudaGetLastError(); return 0; }
    return t;
}

}

extern "C" void kernel_launch(void* const* d_in, const int* in_sizes, int n_in, void* d_out, int out_size) {
    static Prm p = {};
    static int grid = 0;
    const int E = in_sizes[3], T = in_sizes[1];
    if (grid == 0 || p.idx_in != d_in[1] || p.idx_out != d_in[2] || p.angle != d_in[4] || p.E != E || p.T != T) {
        int dev = 0, sms = 0;
        cudaGetDevice(&dev);
        cudaDeviceGetAttribute(&sms, cudaDevAttrMultiProcessorCount, dev);
        cudaFuncSetAttribute(gemnet_kernel, cudaFuncAttributeMaxDynamicSharedMemorySize, SMEM_BYTES);
        p.E = E; p.T = T;
        p.inv_e = 1.f / (float)E;
        p.kdeg = fminf(KAPPA * sqrtf(fmaxf(0.5f * (float)T / (float)E, 1.f)), 128.f);
        p.NS = (((T / 128 + NP * CB - 1) / (NP * CB)) * CB + CPS - 1) / CPS;
        if (p.NS < 3) p.NS = 3;
        p.NT = (p.NS + GR) & ~1;
        void* rp = nullptr;
        cudaGetSymbolAddress(&rp, g_ring);
        p.ring = (unsigned char*)(((uintptr_t)rp + ((2u << 20) - 1)) & ~(uintptr_t)((2u << 20) - 1));
        bool fast = sms >= NCTA && E <= (int)FAST_E && (E & 1) == 0 && T >= 128 && p.NS + GR < PER;
        if (fast) {
            p.t_in = make_tex(d_in[1], (size_t)(T / 128) * 512, 4);
            p.t_out = make_tex(d_in[2], (size_t)(T / 128) * 512, 4);
            p.t_ang = make_tex(d_in[4], (size_t)(T / 128) * 256, 2);
            fast = p.t_in && p.t_out && p.t_ang;
        }
        p.force_bad = !fast;
        grid = fast ? NCTA : sms;
    }
    p.m = (const uint2*)d_in[0];
    p.idx_in = (const int*)d_in[1];
    p.idx_out = (const int*)d_in[2];
    p.dist = (const __nv_bfloat16*)d_in[3];
    p.angle = (const __nv_bfloat16*)d_in[4];
    p.centers = (const __nv_bfloat16*)d_in[5];
    p.freq = (const __nv_bfloat16*)d_in[6];
    p.w_rbf = (const __nv_bfloat16*)d_in[7];
    p.w_sbf = (const __nv_bfloat16*)d_in[8];
    p.w_down = (const __nv_bfloat16*)d_in[9];
    p.w_up = (const __nv_bfloat16*)d_in[10];
    p.out = (uint2*)d_out;
    gemnet_kernel<<<grid, THREADS, SMEM_BYTES>>>(p);
}
```
